```python
import torch

def _softmax(x, axis=-1):
    return torch.softmax(x, dim=axis)
def _gelu(x):
    return torch.nn.functional.gelu(x, approximate="tanh")
def _silu(x):
    return torch.nn.functional.silu(x)
def _sigmoid(x):
    return torch.sigmoid(x)
def _layernorm(x, axis=-1, eps=1e-5):
    m = x.mean(dim=axis, keepdim=True)
    v = x.var(dim=axis, keepdim=True, unbiased=False)
    return (x - m) / torch.sqrt(v + eps)
def _scatter_add(tgt, idx, src, axis=0):
    return tgt.clone().index_add_(axis, idx, src)
def _segment_sum(src, seg, n):
    out = torch.zeros((n,) + src.shape[1:], dtype=src.dtype)
    return out.index_add_(0, seg, src)
def _pad(x, pw):
    flat = tuple(v for pair in reversed(pw) for v in pair)
    return torch.nn.functional.pad(x, flat)

kernel_name = 'sequential_preLN__ssm_conv_h3__glu_gated_glu__prompt'

def setup_inputs():

    _w = (lambda a: (lambda t: t.to(torch.bfloat16) if t.is_floating_point() else t)(torch.as_tensor(a)))
    def _A_setup():
        B, S, D = 1, 2048, 512
        ks = 4
        return {
            "q": _w((lambda *s: torch.randn(*s, dtype=torch.bfloat16) * 0.05)(B, S, D)),
            "k": _w((lambda *s: torch.randn(*s, dtype=torch.bfloat16) * 0.4)(B, S, D)),
            "v": _w((lambda *s: torch.randn(*s, dtype=torch.bfloat16) * 0.4)(B, S, D)),
            "shift_k": _w((lambda *s: torch.randn(*s, dtype=torch.bfloat16) * 0.4)(D, ks) * 0.5),
            "ssm_k": _w((lambda *s: torch.randn(*s, dtype=torch.bfloat16) * 0.4)(D, S) * (1.0 / S ** 0.5)),
            "ssm_D": _w((lambda *s: torch.randn(*s, dtype=torch.bfloat16) * 0.4)(D)),
        }
    _A_in = _A_setup()

    def _B_setup():
        B, S, D, F = 1, 2048, 512, 1792
        return {
            "x": _w((lambda *s: torch.randn(*s, dtype=torch.bfloat16) * 0.05)(B, S, D)),
            "w_gate": _w((lambda *s: torch.randn(*s, dtype=torch.bfloat16) * 0.05)(D, F)),
            "w_up": _w((lambda *s: torch.randn(*s, dtype=torch.bfloat16) * 0.05)(D, F)),
            "w_down": _w((lambda *s: torch.randn(*s, dtype=torch.bfloat16) * 0.05)(F, D)),
        }
    _B_in = _B_setup()

    return {
        "A_q": _A_in["q"],
        "A_k": _A_in["k"],
        "A_v": _A_in["v"],
        "A_shift_k": _A_in["shift_k"],
        "A_ssm_k": _A_in["ssm_k"],
        "A_ssm_D": _A_in["ssm_D"],
        "B_x": _B_in["x"],
        "B_w_gate": _B_in["w_gate"],
        "B_w_up": _B_in["w_up"],
        "B_w_down": _B_in["w_down"],
    }

def reference(A_q, A_k, A_v, A_shift_k, A_ssm_k, A_ssm_D, B_x, B_w_gate, B_w_up, B_w_down):
    def _A_ref(q, k, v, shift_k, ssm_k, ssm_D):
        B, S, D = q.shape
        ks = shift_k.shape[-1]
        k_pad = _pad(k, ((0, 0), (ks - 1, 0), (0, 0)))
        k_shift = torch.zeros_like(k)
        for t in range(ks):
            k_shift = k_shift + k_pad[:, t:t + S, :] * shift_k[:, ks - 1 - t][None, None, :]
        kv = k_shift * v
        L = 2 * S
        kv_pad = _pad(kv, ((0, 0), (0, S), (0, 0)))
        kf_pad = _pad(ssm_k, ((0, 0), (0, S)))
        kv_f = (lambda x, axes=(-2,-1): torch.fft.rfft2(x.float(), dim=axes))(kv_pad[:, None, :, :], axes=(1, 2))
        kf_f = (lambda x, axes=(-2,-1): torch.fft.rfft2(x.float(), dim=axes))(kf_pad[:, None, :], axes=(1, 2))
        kf_f = (lambda x, *d: x.permute(*d))(kf_f, 1, 2, 0)
        y_f = kv_f * kf_f[None, :, :, :]
        y = (lambda x, s, axes=(-2,-1): torch.fft.irfft2(x, s=s, dim=axes).to(torch.bfloat16))(y_f, (1, L), axes=(1, 2))[:, 0, :S, :]
        y = y + kv * ssm_D[None, None, :]
        return q * y

    def _B_ref(x, w_gate, w_up, w_down):
        g = torch.einsum("bsd,df->bsf", x, w_gate)
        u = torch.einsum("bsd,df->bsf", x, w_up)
        h = _sigmoid(g) * u
        return torch.einsum("bsf,fd->bsd", h, w_down)

    x = A_q
    h = x + _A_ref(_layernorm(x, axis=-1), A_k, A_v, A_shift_k, A_ssm_k, A_ssm_D)
    h2 = h + _B_ref(_layernorm(h, axis=-1), B_w_gate, B_w_up, B_w_down)
    return h2
```

```cpp
#include <cuda_runtime.h>
#include <cuda_bf16.h>
#include <cuda.h>
#include <stdint.h>

typedef __nv_bfloat16 bf16;
constexpr int S_ = 2048, D_ = 512, F_ = 1792;

__device__ bf16 g_h[S_ * D_];
__device__ bf16 g_hh[S_ * F_];
__device__ float2 g_stats1[S_];
__device__ float g_colsum[2 * F_];
__device__ unsigned int g_flag;

__device__ __forceinline__ uint32_t smem_u32(const void* p) { return (uint32_t)__cvta_generic_to_shared(p); }
__device__ __forceinline__ float bf16r(float x) { return __bfloat162float(__float2bfloat16_rn(x)); }
__device__ __forceinline__ float bf_lo(uint32_t w) { return __uint_as_float(w << 16); }
__device__ __forceinline__ float bf_hi(uint32_t w) { return __uint_as_float(w & 0xffff0000u); }
__device__ __forceinline__ uint32_t pack_bf16(float lo, float hi) {
    __nv_bfloat162 v = __floats2bfloat162_rn(lo, hi);
    return *reinterpret_cast<uint32_t*>(&v);
}
__device__ __forceinline__ uint32_t hmul2(uint32_t a, uint32_t b) {
    __nv_bfloat162 r = __hmul2_rn(*reinterpret_cast<__nv_bfloat162*>(&a), *reinterpret_cast<__nv_bfloat162*>(&b));
    return *reinterpret_cast<uint32_t*>(&r);
}
__device__ __forceinline__ uint32_t hadd2(uint32_t a, uint32_t b) {
    __nv_bfloat162 r = __hadd2_rn(*reinterpret_cast<__nv_bfloat162*>(&a), *reinterpret_cast<__nv_bfloat162*>(&b));
    return *reinterpret_cast<uint32_t*>(&r);
}
__device__ __forceinline__ void mbar_init(uint32_t bar, int cnt) { asm volatile("mbarrier.init.shared::cta.b64 [%0], %1;" :: "r"(bar), "r"(cnt)); }
__device__ __forceinline__ void mbar_expect_tx(uint32_t bar, uint32_t bytes) { asm volatile("mbarrier.arrive.expect_tx.shared::cta.b64 _, [%0], %1;" :: "r"(bar), "r"(bytes) : "memory"); }
__device__ __forceinline__ void mbar_arrive(uint32_t bar) { asm volatile("mbarrier.arrive.shared::cta.b64 _, [%0];" :: "r"(bar) : "memory"); }
__device__ __forceinline__ void mbar_wait(uint32_t bar, uint32_t parity) {
    asm volatile("{\n.reg .pred P1;\nLAB_WAIT:\nmbarrier.try_wait.parity.shared::cta.b64 P1, [%0], %1;\n@P1 bra DONE;\nbra LAB_WAIT;\nDONE:\n}" :: "r"(bar), "r"(parity) : "memory");
}
__device__ __forceinline__ void tma_load_2d(uint32_t dst, const CUtensorMap* map, uint32_t bar, int c0, int c1) {
    asm volatile("cp.async.bulk.tensor.2d.shared::cluster.global.mbarrier::complete_tx::bytes [%0], [%1, {%3, %4}], [%2];"
        :: "r"(dst), "l"(map), "r"(bar), "r"(c0), "r"(c1) : "memory");
}
__device__ __forceinline__ void tma_load_3d(uint32_t dst, const CUtensorMap* map, uint32_t bar, int c0, int c1, int c2) {
    asm volatile("cp.async.bulk.tensor.3d.shared::cluster.global.mbarrier::complete_tx::bytes [%0], [%1, {%3, %4, %5}], [%2];"
        :: "r"(dst), "l"(map), "r"(bar), "r"(c0), "r"(c1), "r"(c2) : "memory");
}
__device__ __forceinline__ void cluster_arrive() { asm volatile("barrier.cluster.arrive.aligned;" ::: "memory"); }
__device__ __forceinline__ void cluster_wait() { asm volatile("barrier.cluster.wait.aligned;" ::: "memory"); }
__device__ __forceinline__ uint32_t mapa(uint32_t addr, uint32_t cta) {
    uint32_t r; asm volatile("mapa.shared::cluster.u32 %0, %1, %2;" : "=r"(r) : "r"(addr), "r"(cta)); return r;
}
__device__ __forceinline__ void st_cluster_v2(uint32_t addr, uint32_t a, uint32_t b) {
    asm volatile("st.shared::cluster.v2.u32 [%0], {%1, %2};" :: "r"(addr), "r"(a), "r"(b) : "memory");
}
__device__ __forceinline__ void st_cluster_v4f(uint32_t addr, float a, float b, float c, float d) {
    asm volatile("st.shared::cluster.v4.f32 [%0], {%1, %2, %3, %4};" :: "r"(addr), "f"(a), "f"(b), "f"(c), "f"(d) : "memory");
}
__device__ __forceinline__ void wgmma_fence() { asm volatile("wgmma.fence.sync.aligned;" ::: "memory"); }
__device__ __forceinline__ void wgmma_commit() { asm volatile("wgmma.commit_group.sync.aligned;" ::: "memory"); }
template <int N> __device__ __forceinline__ void wgmma_wait() { asm volatile("wgmma.wait_group.sync.aligned %0;" :: "n"(N) : "memory"); }
__device__ __forceinline__ uint64_t make_desc(uint32_t addr, uint32_t lbo_bytes, uint32_t sbo_bytes, uint32_t layout) {
    return (uint64_t)((addr & 0x3FFFF) >> 4) | ((uint64_t)(lbo_bytes >> 4) << 16) | ((uint64_t)(sbo_bytes >> 4) << 32) | ((uint64_t)layout << 62);
}
template <int R> __device__ __forceinline__ void reg_alloc() { asm volatile("setmaxnreg.inc.sync.aligned.u32 %0;" :: "n"(R)); }
template <int R> __device__ __forceinline__ void reg_dealloc() { asm volatile("setmaxnreg.dec.sync.aligned.u32 %0;" :: "n"(R)); }

__device__ __forceinline__ void wgmma_m64n256k16_ss(float (&d)[128], uint64_t descA, uint64_t descB, int scaleD) {
    asm volatile("{\n.reg .pred p;\nsetp.ne.b32 p, %130, 0;\n"
        "wgmma.mma_async.sync.aligned.m64n256k16.f32.bf16.bf16 {%0, %1, %2, %3, %4, %5, %6, %7, %8, %9, %10, %11, %12, %13, %14, %15, %16, %17, %18, %19, %20, %21, %22, %23, %24, %25, %26, %27, %28, %29, %30, %31, %32, %33, %34, %35, %36, %37, %38, %39, %40, %41, %42, %43, %44, %45, %46, %47, %48, %49, %50, %51, %52, %53, %54, %55, %56, %57, %58, %59, %60, %61, %62, %63, %64, %65, %66, %67, %68, %69, %70, %71, %72, %73, %74, %75, %76, %77, %78, %79, %80, %81, %82, %83, %84, %85, %86, %87, %88, %89, %90, %91, %92, %93, %94, %95, %96, %97, %98, %99, %100, %101, %102, %103, %104, %105, %106, %107, %108, %109, %110, %111, %112, %113, %114, %115, %116, %117, %118, %119, %120, %121, %122, %123, %124, %125, %126, %127}, %128, %129, p, 1, 1, 0, 1;\n}\n"
        : "+f"(d[0]), "+f"(d[1]), "+f"(d[2]), "+f"(d[3]), "+f"(d[4]), "+f"(d[5]), "+f"(d[6]), "+f"(d[7]), "+f"(d[8]), "+f"(d[9]), "+f"(d[10]), "+f"(d[11]), "+f"(d[12]), "+f"(d[13]), "+f"(d[14]), "+f"(d[15]), "+f"(d[16]), "+f"(d[17]), "+f"(d[18]), "+f"(d[19]), "+f"(d[20]), "+f"(d[21]), "+f"(d[22]), "+f"(d[23]), "+f"(d[24]), "+f"(d[25]), "+f"(d[26]), "+f"(d[27]), "+f"(d[28]), "+f"(d[29]), "+f"(d[30]), "+f"(d[31]), "+f"(d[32]), "+f"(d[33]), "+f"(d[34]), "+f"(d[35]), "+f"(d[36]), "+f"(d[37]), "+f"(d[38]), "+f"(d[39]), "+f"(d[40]), "+f"(d[41]), "+f"(d[42]), "+f"(d[43]), "+f"(d[44]), "+f"(d[45]), "+f"(d[46]), "+f"(d[47]), "+f"(d[48]), "+f"(d[49]), "+f"(d[50]), "+f"(d[51]), "+f"(d[52]), "+f"(d[53]), "+f"(d[54]), "+f"(d[55]), "+f"(d[56]), "+f"(d[57]), "+f"(d[58]), "+f"(d[59]), "+f"(d[60]), "+f"(d[61]), "+f"(d[62]), "+f"(d[63]), "+f"(d[64]), "+f"(d[65]), "+f"(d[66]), "+f"(d[67]), "+f"(d[68]), "+f"(d[69]), "+f"(d[70]), "+f"(d[71]), "+f"(d[72]), "+f"(d[73]), "+f"(d[74]), "+f"(d[75]), "+f"(d[76]), "+f"(d[77]), "+f"(d[78]), "+f"(d[79]), "+f"(d[80]), "+f"(d[81]), "+f"(d[82]), "+f"(d[83]), "+f"(d[84]), "+f"(d[85]), "+f"(d[86]), "+f"(d[87]), "+f"(d[88]), "+f"(d[89]), "+f"(d[90]), "+f"(d[91]), "+f"(d[92]), "+f"(d[93]), "+f"(d[94]), "+f"(d[95]), "+f"(d[96]), "+f"(d[97]), "+f"(d[98]), "+f"(d[99]), "+f"(d[100]), "+f"(d[101]), "+f"(d[102]), "+f"(d[103]), "+f"(d[104]), "+f"(d[105]), "+f"(d[106]), "+f"(d[107]), "+f"(d[108]), "+f"(d[109]), "+f"(d[110]), "+f"(d[111]), "+f"(d[112]), "+f"(d[113]), "+f"(d[114]), "+f"(d[115]), "+f"(d[116]), "+f"(d[117]), "+f"(d[118]), "+f"(d[119]), "+f"(d[120]), "+f"(d[121]), "+f"(d[122]), "+f"(d[123]), "+f"(d[124]), "+f"(d[125]), "+f"(d[126]), "+f"(d[127])
        : "l"(descA), "l"(descB), "r"(scaleD));
}

__device__ __forceinline__ void wgmma_m64n192k16_ss(float (&d)[96], uint64_t descA, uint64_t descB, int scaleD) {
    asm volatile("{\n.reg .pred p;\nsetp.ne.b32 p, %98, 0;\n"
        "wgmma.mma_async.sync.aligned.m64n192k16.f32.bf16.bf16 {%0, %1, %2, %3, %4, %5, %6, %7, %8, %9, %10, %11, %12, %13, %14, %15, %16, %17, %18, %19, %20, %21, %22, %23, %24, %25, %26, %27, %28, %29, %30, %31, %32, %33, %34, %35, %36, %37, %38, %39, %40, %41, %42, %43, %44, %45, %46, %47, %48, %49, %50, %51, %52, %53, %54, %55, %56, %57, %58, %59, %60, %61, %62, %63, %64, %65, %66, %67, %68, %69, %70, %71, %72, %73, %74, %75, %76, %77, %78, %79, %80, %81, %82, %83, %84, %85, %86, %87, %88, %89, %90, %91, %92, %93, %94, %95}, %96, %97, p, 1, 1, 0, 1;\n}\n"
        : "+f"(d[0]), "+f"(d[1]), "+f"(d[2]), "+f"(d[3]), "+f"(d[4]), "+f"(d[5]), "+f"(d[6]), "+f"(d[7]), "+f"(d[8]), "+f"(d[9]), "+f"(d[10]), "+f"(d[11]), "+f"(d[12]), "+f"(d[13]), "+f"(d[14]), "+f"(d[15]), "+f"(d[16]), "+f"(d[17]), "+f"(d[18]), "+f"(d[19]), "+f"(d[20]), "+f"(d[21]), "+f"(d[22]), "+f"(d[23]), "+f"(d[24]), "+f"(d[25]), "+f"(d[26]), "+f"(d[27]), "+f"(d[28]), "+f"(d[29]), "+f"(d[30]), "+f"(d[31]), "+f"(d[32]), "+f"(d[33]), "+f"(d[34]), "+f"(d[35]), "+f"(d[36]), "+f"(d[37]), "+f"(d[38]), "+f"(d[39]), "+f"(d[40]), "+f"(d[41]), "+f"(d[42]), "+f"(d[43]), "+f"(d[44]), "+f"(d[45]), "+f"(d[46]), "+f"(d[47]), "+f"(d[48]), "+f"(d[49]), "+f"(d[50]), "+f"(d[51]), "+f"(d[52]), "+f"(d[53]), "+f"(d[54]), "+f"(d[55]), "+f"(d[56]), "+f"(d[57]), "+f"(d[58]), "+f"(d[59]), "+f"(d[60]), "+f"(d[61]), "+f"(d[62]), "+f"(d[63]), "+f"(d[64]), "+f"(d[65]), "+f"(d[66]), "+f"(d[67]), "+f"(d[68]), "+f"(d[69]), "+f"(d[70]), "+f"(d[71]), "+f"(d[72]), "+f"(d[73]), "+f"(d[74]), "+f"(d[75]), "+f"(d[76]), "+f"(d[77]), "+f"(d[78]), "+f"(d[79]), "+f"(d[80]), "+f"(d[81]), "+f"(d[82]), "+f"(d[83]), "+f"(d[84]), "+f"(d[85]), "+f"(d[86]), "+f"(d[87]), "+f"(d[88]), "+f"(d[89]), "+f"(d[90]), "+f"(d[91]), "+f"(d[92]), "+f"(d[93]), "+f"(d[94]), "+f"(d[95])
        : "l"(descA), "l"(descB), "r"(scaleD));
}

__device__ __forceinline__ void wgmma_m64n128k16_ss(float (&d)[64], uint64_t descA, uint64_t descB, int scaleD) {
    asm volatile("{\n.reg .pred p;\nsetp.ne.b32 p, %66, 0;\n"
        "wgmma.mma_async.sync.aligned.m64n128k16.f32.bf16.bf16 {%0, %1, %2, %3, %4, %5, %6, %7, %8, %9, %10, %11, %12, %13, %14, %15, %16, %17, %18, %19, %20, %21, %22, %23, %24, %25, %26, %27, %28, %29, %30, %31, %32, %33, %34, %35, %36, %37, %38, %39, %40, %41, %42, %43, %44, %45, %46, %47, %48, %49, %50, %51, %52, %53, %54, %55, %56, %57, %58, %59, %60, %61, %62, %63}, %64, %65, p, 1, 1, 0, 1;\n}\n"
        : "+f"(d[0]), "+f"(d[1]), "+f"(d[2]), "+f"(d[3]), "+f"(d[4]), "+f"(d[5]), "+f"(d[6]), "+f"(d[7]), "+f"(d[8]), "+f"(d[9]), "+f"(d[10]), "+f"(d[11]), "+f"(d[12]), "+f"(d[13]), "+f"(d[14]), "+f"(d[15]), "+f"(d[16]), "+f"(d[17]), "+f"(d[18]), "+f"(d[19]), "+f"(d[20]), "+f"(d[21]), "+f"(d[22]), "+f"(d[23]), "+f"(d[24]), "+f"(d[25]), "+f"(d[26]), "+f"(d[27]), "+f"(d[28]), "+f"(d[29]), "+f"(d[30]), "+f"(d[31]), "+f"(d[32]), "+f"(d[33]), "+f"(d[34]), "+f"(d[35]), "+f"(d[36]), "+f"(d[37]), "+f"(d[38]), "+f"(d[39]), "+f"(d[40]), "+f"(d[41]), "+f"(d[42]), "+f"(d[43]), "+f"(d[44]), "+f"(d[45]), "+f"(d[46]), "+f"(d[47]), "+f"(d[48]), "+f"(d[49]), "+f"(d[50]), "+f"(d[51]), "+f"(d[52]), "+f"(d[53]), "+f"(d[54]), "+f"(d[55]), "+f"(d[56]), "+f"(d[57]), "+f"(d[58]), "+f"(d[59]), "+f"(d[60]), "+f"(d[61]), "+f"(d[62]), "+f"(d[63])
        : "l"(descA), "l"(descB), "r"(scaleD));
}


__device__ __forceinline__ void quad_transpose(uint32_t& r0, uint32_t& r1, uint32_t& r2, uint32_t& r3, int t) {
    const bool o1 = t & 1, o2 = t & 2;
    uint32_t x, y;
    x = o1 ? r0 : r1; y = __shfl_xor_sync(0xffffffffu, x, 1); if (o1) r0 = y; else r1 = y;
    x = o1 ? r2 : r3; y = __shfl_xor_sync(0xffffffffu, x, 1); if (o1) r2 = y; else r3 = y;
    x = o2 ? r0 : r2; y = __shfl_xor_sync(0xffffffffu, x, 2); if (o2) r0 = y; else r2 = y;
    x = o2 ? r1 : r3; y = __shfl_xor_sync(0xffffffffu, x, 2); if (o2) r1 = y; else r3 = y;
}

constexpr int K1_THREADS = 256;
constexpr int UT_PAD = 128;
constexpr int UT_LEN = UT_PAD + S_;
constexpr int KR_LEN = 2080;

struct __align__(128) K1Smem {
    bf16 uT[4][UT_LEN];
    bf16 kr[4][2][KR_LEN];
    bf16 yS[S_][4];
    bf16 xS[S_][4];
    float red[8][32];
};

__device__ __forceinline__ void mma16816(float (&c)[4], uint32_t a0, uint32_t a1, uint32_t a2, uint32_t a3, uint32_t b0, uint32_t b1) {
    asm("mma.sync.aligned.m16n8k16.row.col.f32.bf16.bf16.f32 {%0,%1,%2,%3}, {%4,%5,%6,%7}, {%8,%9}, {%0,%1,%2,%3};"
        : "+f"(c[0]), "+f"(c[1]), "+f"(c[2]), "+f"(c[3])
        : "r"(a0), "r"(a1), "r"(a2), "r"(a3), "r"(b0), "r"(b1));
}
__device__ __forceinline__ void ldsm_x4(uint32_t& r0, uint32_t& r1, uint32_t& r2, uint32_t& r3, uint32_t addr) {
    asm volatile("ldmatrix.sync.aligned.m8n8.x4.shared.b16 {%0,%1,%2,%3}, [%4];" : "=r"(r0), "=r"(r1), "=r"(r2), "=r"(r3) : "r"(addr) : "memory");
}

template <int PAR>
__device__ __forceinline__ void conv_mma(const bf16* uTc, const bf16* krlane, float (&acc)[8][4], int lane) {
    const int lrow = lane & 7, lk = (lane >> 3) & 1, lt = lane >> 4;
    const uint32_t ubase = smem_u32(uTc) + (UT_PAD + 16 * (8 * lt + lrow) + 8 * lk) * 2;
#pragma unroll 1
    for (int p = 0; p < 8; p++) {
        uint32_t U[16][2];
#pragma unroll
        for (int j = 0; j < 16; j += 2) ldsm_x4(U[j][0], U[j][1], U[j + 1][0], U[j + 1][1], ubase + (j * 128 - p * 16) * 2);
        const uint32_t* kp = reinterpret_cast<const uint32_t*>(krlane - 16 * p);
#pragma unroll
        for (int q = 0; q < 16; q++) {
            if (q == 15 && PAR == 0) continue;
            const uint32_t a0 = kp[-64 * q], a1 = kp[-64 * q - 4], a2 = kp[-64 * q + 4];
#pragma unroll
            for (int n2 = 0; n2 < 8; n2++) {
                const int n = 2 * n2 + PAR;
                if (n >= q) mma16816(acc[n2], a0, a1, a2, a0, U[n - q][0], U[n - q][1]);
            }
        }
    }
}

__global__ void __cluster_dims__(4, 1, 1) __launch_bounds__(K1_THREADS, 1)
conv_kernel(const bf16* __restrict__ q, const bf16* __restrict__ k, const bf16* __restrict__ v,
            const bf16* __restrict__ shift_k, const bf16* __restrict__ ssm_k, const bf16* __restrict__ ssm_D,
            const bf16* __restrict__ wg, const bf16* __restrict__ wu) {
    extern __shared__ __align__(128) uint8_t smem_raw[];
    K1Smem& sm = *reinterpret_cast<K1Smem*>(smem_raw);
    const int tid = threadIdx.x, lane = tid & 31, warp = tid >> 5;
    const int bid = blockIdx.x;
    const int rank = bid & 3, cl = bid >> 2;
    const int c0 = 16 * cl;
    const int cown = c0 + 4 * rank;

    cluster_arrive();

    const int rg = tid >> 1, hf = tid & 1;
    const int s0 = 512 * rank + 4 * rg;
    const int ch8 = c0 + 8 * hf;
    uint4 kk[7], vv[4], sw[4];
#pragma unroll
    for (int i = 0; i < 7; i++) {
        const int s = s0 - 3 + i;
        kk[i] = (s >= 0) ? __ldg(reinterpret_cast<const uint4*>(k + (size_t)s * D_ + ch8)) : make_uint4(0, 0, 0, 0);
    }
#pragma unroll
    for (int i = 0; i < 4; i++) vv[i] = __ldg(reinterpret_cast<const uint4*>(v + (size_t)(s0 + i) * D_ + ch8));
#pragma unroll
    for (int i = 0; i < 4; i++) sw[i] = __ldg(reinterpret_cast<const uint4*>(shift_k + (size_t)ch8 * 4) + i);
    uint4 kq[4]; uint32_t nx[4];
#pragma unroll
    for (int c = 0; c < 4; c++) {
        const bf16* kr = ssm_k + (size_t)(cown + c) * S_;
        kq[c] = __ldg(reinterpret_cast<const uint4*>(kr) + tid);
        nx[c] = (tid < 255) ? (uint32_t)__ldg(reinterpret_cast<const unsigned short*>(kr) + 8 * tid + 8) : 0u;
    }
    uint4 qr[2][2];
#pragma unroll
    for (int r = 0; r < 2; r++) {
        const bf16* qp = q + (size_t)(16 * bid + 2 * warp + r) * D_;
        qr[r][0] = __ldg(reinterpret_cast<const uint4*>(qp) + lane);
        qr[r][1] = __ldg(reinterpret_cast<const uint4*>(qp) + 32 + lane);
    }
#pragma unroll
    for (int j = 0; j < 8; j++) {
        const int s = 256 * j + tid;
        asm volatile("cp.async.ca.shared.global [%0], [%1], 8;" :: "r"(smem_u32(&sm.xS[s][0])), "l"(q + (size_t)s * D_ + cown) : "memory");
    }
    asm volatile("cp.async.commit_group;" ::: "memory");
    if (tid < 64) *reinterpret_cast<uint4*>(&sm.uT[tid >> 4][(tid & 15) * 8]) = make_uint4(0, 0, 0, 0);

    {
        uint32_t kvw[4][4];
        const uint32_t* kkw = reinterpret_cast<const uint32_t*>(kk);
        const uint32_t* vvw = reinterpret_cast<const uint32_t*>(vv);
#pragma unroll
        for (int i2 = 0; i2 < 4; i2++) {
            const uint32_t t0 = __byte_perm(sw[i2].x, sw[i2].z, 0x5410), t1 = __byte_perm(sw[i2].x, sw[i2].z, 0x7632);
            const uint32_t t2 = __byte_perm(sw[i2].y, sw[i2].w, 0x5410), t3 = __byte_perm(sw[i2].y, sw[i2].w, 0x7632);
#pragma unroll
            for (int r = 0; r < 4; r++) {
                uint32_t a = hmul2(kkw[(r + 0) * 4 + i2], t3);
                a = hadd2(a, hmul2(kkw[(r + 1) * 4 + i2], t2));
                a = hadd2(a, hmul2(kkw[(r + 2) * 4 + i2], t1));
                a = hadd2(a, hmul2(kkw[(r + 3) * 4 + i2], t0));
                kvw[r][i2] = hmul2(a, vvw[r * 4 + i2]);
            }
        }
        cluster_wait();
#pragma unroll
        for (int i2 = 0; i2 < 4; i2++) {
#pragma unroll
            for (int e = 0; e < 2; e++) {
                const uint32_t sel = e ? 0x7632 : 0x5410;
                const uint32_t w0 = __byte_perm(kvw[0][i2], kvw[1][i2], sel), w1 = __byte_perm(kvw[2][i2], kvw[3][i2], sel);
                const int cc = 8 * hf + 2 * i2 + e;
                const uint32_t addr = mapa(smem_u32(&sm.uT[cc & 3][UT_PAD + s0]), (uint32_t)(cc >> 2));
                st_cluster_v2(addr, w0, w1);
            }
        }
    }
#pragma unroll
    for (int c = 0; c < 4; c++) {
        uint4 a, b;
        a.x = __byte_perm(kq[c].w, 0, 0x1032); a.y = __byte_perm(kq[c].z, 0, 0x1032);
        a.z = __byte_perm(kq[c].y, 0, 0x1032); a.w = __byte_perm(kq[c].x, 0, 0x1032);
        b.x = __byte_perm(nx[c], kq[c].w, 0x7610); b.y = __byte_perm(kq[c].w, kq[c].z, 0x7610);
        b.z = __byte_perm(kq[c].z, kq[c].y, 0x7610); b.w = __byte_perm(kq[c].y, kq[c].x, 0x7610);
        *reinterpret_cast<uint4*>(&sm.kr[c][0][2040 - 8 * tid]) = a;
        *reinterpret_cast<uint4*>(&sm.kr[c][1][2040 - 8 * tid]) = b;
        if (tid == 0) {
            *reinterpret_cast<uint4*>(&sm.kr[c][1][2048]) = make_uint4(kq[c].x & 0xffffu, 0, 0, 0);
        } else if (tid < 8) {
            if (tid < 4) *reinterpret_cast<uint4*>(&sm.kr[c][1][2048 + 8 * tid]) = make_uint4(0, 0, 0, 0);
            else *reinterpret_cast<uint4*>(&sm.kr[c][0][2048 + 8 * (tid - 4)]) = make_uint4(0, 0, 0, 0);
        }
    }
#pragma unroll
    for (int r = 0; r < 2; r++) {
        const uint32_t* w = reinterpret_cast<const uint32_t*>(&qr[r][0]);
        float s = 0.f;
#pragma unroll
        for (int i = 0; i < 8; i++) s += bf_lo(w[i]) + bf_hi(w[i]);
#pragma unroll
        for (int o = 16; o > 0; o >>= 1) s += __shfl_xor_sync(0xffffffffu, s, o);
        const float mean = s * (1.0f / D_);
        float ss = 0.f;
#pragma unroll
        for (int i = 0; i < 8; i++) { float a = bf_lo(w[i]) - mean, b = bf_hi(w[i]) - mean; ss += a * a + b * b; }
#pragma unroll
        for (int o = 16; o > 0; o >>= 1) ss += __shfl_xor_sync(0xffffffffu, ss, o);
        if (lane == 0) {
            const float var = bf16r(ss * (1.0f / D_));
            const float den = bf16r(sqrtf(bf16r(var + 1e-5f)));
            g_stats1[16 * bid + 2 * warp + r] = make_float2(bf16r(mean), den);
            __threadfence();
        }
    }
    if (bid < 112) {
        const bf16* wp = (bid < 56) ? (wg + 32 * bid) : (wu + 32 * (bid - 56));
        const int cq = tid & 3, rgp = tid >> 2;
        float cs[8];
#pragma unroll
        for (int i = 0; i < 8; i++) cs[i] = 0.f;
#pragma unroll
        for (int r = 0; r < 8; r++) {
            const uint4 w = __ldg(reinterpret_cast<const uint4*>(wp + (size_t)(rgp * 8 + r) * F_ + cq * 8));
            cs[0] += bf_lo(w.x); cs[1] += bf_hi(w.x); cs[2] += bf_lo(w.y); cs[3] += bf_hi(w.y);
            cs[4] += bf_lo(w.z); cs[5] += bf_hi(w.z); cs[6] += bf_lo(w.w); cs[7] += bf_hi(w.w);
        }
#pragma unroll
        for (int i = 0; i < 8; i++) {
            cs[i] += __shfl_xor_sync(0xffffffffu, cs[i], 4);
            cs[i] += __shfl_xor_sync(0xffffffffu, cs[i], 8);
            cs[i] += __shfl_xor_sync(0xffffffffu, cs[i], 16);
        }
        if (lane < 4) {
#pragma unroll
            for (int i = 0; i < 8; i++) sm.red[warp][lane * 8 + i] = cs[i];
        }
    }
    cluster_arrive();
    cluster_wait();
    if (tid == 0) { __threadfence(); atomicAdd(&g_flag, 1u); }
    if (bid < 112 && tid < 32) {
        float s = 0.f;
#pragma unroll
        for (int w = 0; w < 8; w++) s += sm.red[w][tid];
        g_colsum[32 * bid + tid] = s;
    }

    const int ch = warp >> 1;
    const int par = (warp & 1) ^ ((warp >> 2) & 1);
    const int g = lane >> 2, t = lane & 3;
    float acc[8][4];
#pragma unroll
    for (int i = 0; i < 8; i++) { acc[i][0] = acc[i][1] = acc[i][2] = acc[i][3] = 0.f; }
    const bf16* krlane = (g & 1) ? &sm.kr[ch][0][2047 - g + 2 * t] : &sm.kr[ch][1][2048 - g + 2 * t];
    if (par) conv_mma<1>(sm.uT[ch], krlane, acc, lane);
    else conv_mma<0>(sm.uT[ch], krlane, acc, lane);

#pragma unroll
    for (int n2 = 0; n2 < 8; n2++) {
        const int s = 128 * (2 * n2 + par) + 32 * t + g;
        sm.yS[s][ch] = __float2bfloat16_rn(acc[n2][0]);
        sm.yS[s + 16][ch] = __float2bfloat16_rn(acc[n2][1]);
        sm.yS[s + 8][ch] = __float2bfloat16_rn(acc[n2][2]);
        sm.yS[s + 24][ch] = __float2bfloat16_rn(acc[n2][3]);
    }
    asm volatile("cp.async.wait_group 0;" ::: "memory");
    if (tid == 0) {
        unsigned int vflag;
        long long it = 0;
        do { asm volatile("ld.acquire.gpu.global.u32 %0, [%1];" : "=r"(vflag) : "l"(&g_flag) : "memory"); } while (vflag < gridDim.x && ++it < (1ll << 26));
    }
    __syncthreads();

    float dd[4];
#pragma unroll
    for (int c = 0; c < 4; c++) dd[c] = __bfloat162float(ssm_D[cown + c]);
#pragma unroll
    for (int j = 0; j < 8; j++) {
        const int s = 256 * j + tid;
        const float2 st = __ldcg(&g_stats1[s]);
        const uint2 yw = *reinterpret_cast<const uint2*>(&sm.yS[s][0]);
        const uint2 xw = *reinterpret_cast<const uint2*>(&sm.xS[s][0]);
        const float yv[4] = {bf_lo(yw.x), bf_hi(yw.x), bf_lo(yw.y), bf_hi(yw.y)};
        const float xv[4] = {bf_lo(xw.x), bf_hi(xw.x), bf_lo(xw.y), bf_hi(xw.y)};
        float hv[4];
#pragma unroll
        for (int c = 0; c < 4; c++) {
            const float kvv = __bfloat162float(sm.uT[c][UT_PAD + s]);
            const float y2 = bf16r(yv[c] + bf16r(kvv * dd[c]));
            const float qn = bf16r(__fdiv_rn(bf16r(xv[c] - st.x), st.y));
            hv[c] = xv[c] + bf16r(qn * y2);
        }
        uint2 o; o.x = pack_bf16(hv[0], hv[1]); o.y = pack_bf16(hv[2], hv[3]);
        *reinterpret_cast<uint2*>(g_h + (size_t)s * D_ + cown) = o;
    }
}

constexpr int G1_THREADS = 384;
constexpr int G1_STAGES = 3;
constexpr int G1_A_BYTES = 8 * 16384;
constexpr int G1_B_STAGE = 32768;
constexpr int G1_OFF_B = G1_A_BYTES;
constexpr int G1_OFF_STATS = G1_OFF_B + G1_STAGES * G1_B_STAGE;
constexpr int G1_OFF_CS = G1_OFF_STATS + 1024;
constexpr int G1_OFF_BAR = G1_OFF_CS + 1792;
constexpr int G1_SMEM = G1_OFF_BAR + 128;

template <int NT>
__device__ __forceinline__ void g1_epilogue(float (&acc)[NT * 8], const float* cs_g, const float* cs_u, float2 st0, float2 st1,
                                            bf16* out0, bf16* out1, int t) {
#pragma unroll
    for (int j0 = 0; j0 < NT; j0 += 4) {
        uint32_t P0[4], P1[4];
#pragma unroll
        for (int jj = 0; jj < 4; jj++) {
            const int j = j0 + jj;
            const float2 cg = *reinterpret_cast<const float2*>(cs_g + 8 * j + 2 * t);
            const float2 cu = *reinterpret_cast<const float2*>(cs_u + 8 * j + 2 * t);
            float r[4];
#pragma unroll
            for (int e = 0; e < 4; e++) {
                const float2 st = (e < 2) ? st0 : st1;
                const float cgv = (e & 1) ? cg.y : cg.x, cuv = (e & 1) ? cu.y : cu.x;
                const float gv = bf16r((acc[4 * j + e] - st.x * cgv) * st.y);
                const float uv = bf16r((acc[4 * (NT + j) + e] - st.x * cuv) * st.y);
                const float sg = bf16r(__fdividef(1.0f, 1.0f + __expf(-gv)));
                r[e] = sg * uv;
            }
            P0[jj] = pack_bf16(r[0], r[1]);
            P1[jj] = pack_bf16(r[2], r[3]);
        }
        quad_transpose(P0[0], P0[1], P0[2], P0[3], t);
        quad_transpose(P1[0], P1[1], P1[2], P1[3], t);
        *reinterpret_cast<uint4*>(out0 + 8 * (j0 + t)) = make_uint4(P0[0], P0[1], P0[2], P0[3]);
        *reinterpret_cast<uint4*>(out1 + 8 * (j0 + t)) = make_uint4(P1[0], P1[1], P1[2], P1[3]);
    }
}

__global__ void __launch_bounds__(G1_THREADS, 1)
gemm1_kernel(const __grid_constant__ CUtensorMap mapA, const __grid_constant__ CUtensorMap mapG4, const __grid_constant__ CUtensorMap mapU4,
             const __grid_constant__ CUtensorMap mapG3, const __grid_constant__ CUtensorMap mapU3) {
    extern __shared__ __align__(1024) uint8_t smem_raw[];
    const uint32_t sb = smem_u32(smem_raw);
    const int tid = threadIdx.x, lane = tid & 31, warp = tid >> 5, wgi = tid >> 7;
    const int rb = blockIdx.x >> 3, cb = blockIdx.x & 7;
    const uint32_t barA = sb + G1_OFF_BAR;
    const uint32_t barF = barA + 64;
    const uint32_t barE = barF + 24;
    const uint32_t barS = barE + 24;
    if (tid == 0) {
        for (int i = 0; i < 8; i++) mbar_init(barA + 8 * i, 1);
        for (int i = 0; i < G1_STAGES; i++) { mbar_init(barF + 8 * i, 1); mbar_init(barE + 8 * i, 2); }
        mbar_init(barS, 3);
        asm volatile("fence.mbarrier_init.release.cluster;" ::: "memory");
    }
    __syncthreads();

    if (wgi == 0) {
        reg_dealloc<56>();
        if (warp == 0) {
            if (lane == 0) {
                int st = 0, ph = 1;
                for (int it = 0; it < 16; it++) {
                    const int kc = it & 7;
                    if (it < 8) {
                        mbar_expect_tx(barA + 8 * it, 16384);
                        tma_load_2d(sb + it * 16384, &mapA, barA + 8 * it, it * 64, rb * 128);
                    }
                    mbar_wait(barE + 8 * st, ph);
                    const uint32_t dst = sb + G1_OFF_B + st * G1_B_STAGE;
                    if (it < 8) {
                        mbar_expect_tx(barF + 8 * st, 32768);
                        tma_load_3d(dst, &mapG4, barF + 8 * st, 0, kc * 64, cb * 7);
                        tma_load_3d(dst + 16384, &mapU4, barF + 8 * st, 0, kc * 64, cb * 7);
                    } else {
                        mbar_expect_tx(barF + 8 * st, 24576);
                        tma_load_3d(dst, &mapG3, barF + 8 * st, 0, kc * 64, cb * 7 + 4);
                        tma_load_3d(dst + 12288, &mapU3, barF + 8 * st, 0, kc * 64, cb * 7 + 4);
                    }
                    if (++st == G1_STAGES) { st = 0; ph ^= 1; }
                }
            }
        } else {
            float* cs = reinterpret_cast<float*>(smem_raw + G1_OFF_CS);
            for (int i = tid - 32; i < 448; i += 96) cs[i] = (i < 224) ? g_colsum[cb * 224 + i] : g_colsum[F_ + cb * 224 + (i - 224)];
            for (int i = 0; i < 8; i++) mbar_wait(barA + 8 * i, 0);
            float2* stats = reinterpret_cast<float2*>(smem_raw + G1_OFF_STATS);
            const int r8 = lane >> 2, qd = lane & 3;
            for (int grp = warp - 1; grp < 16; grp += 3) {
                const int row = grp * 8 + r8;
                const uint8_t* rp = smem_raw + row * 128;
                const int o0 = ((2 * qd) ^ r8) * 16, o1 = ((2 * qd + 1) ^ r8) * 16;
                float s = 0.f;
#pragma unroll
                for (int kc = 0; kc < 8; kc++) {
                    const uint4 a = *reinterpret_cast<const uint4*>(rp + kc * 16384 + o0);
                    const uint4 b = *reinterpret_cast<const uint4*>(rp + kc * 16384 + o1);
                    s += (bf_lo(a.x) + bf_hi(a.x)) + (bf_lo(a.y) + bf_hi(a.y)) + (bf_lo(a.z) + bf_hi(a.z)) + (bf_lo(a.w) + bf_hi(a.w));
                    s += (bf_lo(b.x) + bf_hi(b.x)) + (bf_lo(b.y) + bf_hi(b.y)) + (bf_lo(b.z) + bf_hi(b.z)) + (bf_lo(b.w) + bf_hi(b.w));
                }
                s += __shfl_xor_sync(0xffffffffu, s, 1);
                s += __shfl_xor_sync(0xffffffffu, s, 2);
                const float mean = s * (1.0f / D_);
                float ss = 0.f;
#pragma unroll
                for (int kc = 0; kc < 8; kc++) {
                    const uint4 a = *reinterpret_cast<const uint4*>(rp + kc * 16384 + o0);
                    const uint4 b = *reinterpret_cast<const uint4*>(rp + kc * 16384 + o1);
                    const uint32_t w[8] = {a.x, a.y, a.z, a.w, b.x, b.y, b.z, b.w};
#pragma unroll
                    for (int i = 0; i < 8; i++) { const float x0 = bf_lo(w[i]) - mean, x1 = bf_hi(w[i]) - mean; ss += x0 * x0; ss += x1 * x1; }
                }
                ss += __shfl_xor_sync(0xffffffffu, ss, 1);
                ss += __shfl_xor_sync(0xffffffffu, ss, 2);
                if (qd == 0) {
                    const float var = bf16r(ss * (1.0f / D_));
                    const float den = bf16r(sqrtf(bf16r(var + 1e-5f)));
                    stats[row] = make_float2(bf16r(mean), 1.0f / den);
                }
            }
            __syncwarp();
            if (lane == 0) mbar_arrive(barS);
        }
    } else {
        reg_alloc<224>();
        const int cw = wgi - 1;
        const int g = lane >> 2, t = lane & 3;
        const int wl = warp & 3;
        int st = 0, ph = 0;
        const int row0 = rb * 128 + cw * 64 + wl * 16 + g;
        const float* cs = reinterpret_cast<const float*>(smem_raw + G1_OFF_CS);
        const float2* stats = reinterpret_cast<const float2*>(smem_raw + G1_OFF_STATS);
        {
            float acc[128];
#pragma unroll 1
            for (int kc = 0; kc < 8; kc++) {
                mbar_wait(barA + 8 * kc, 0);
                mbar_wait(barF + 8 * st, ph);
                wgmma_fence();
                const uint32_t aaddr = sb + kc * 16384 + cw * 8192;
                const uint32_t baddr = sb + G1_OFF_B + st * G1_B_STAGE;
#pragma unroll
                for (int kk = 0; kk < 4; kk++)
                    wgmma_m64n256k16_ss(acc, make_desc(aaddr + kk * 32, 16, 1024, 1), make_desc(baddr + kk * 1024, 4096, 512, 2), (kc | kk) != 0);
                wgmma_commit();
                wgmma_wait<0>();
                if ((tid & 127) == 0) mbar_arrive(barE + 8 * st);
                if (++st == G1_STAGES) { st = 0; ph ^= 1; }
            }
            mbar_wait(barS, 0);
            const float2 st0 = stats[cw * 64 + wl * 16 + g], st1 = stats[cw * 64 + wl * 16 + g + 8];
            bf16* o0 = g_hh + (size_t)row0 * F_ + cb * 224;
            g1_epilogue<16>(acc, cs, cs + 224, st0, st1, o0, o0 + 8 * F_, t);
        }
        {
            float acc[96];
#pragma unroll 1
            for (int kc = 0; kc < 8; kc++) {
                mbar_wait(barF + 8 * st, ph);
                wgmma_fence();
                const uint32_t aaddr = sb + kc * 16384 + cw * 8192;
                const uint32_t baddr = sb + G1_OFF_B + st * G1_B_STAGE;
#pragma unroll
                for (int kk = 0; kk < 4; kk++)
                    wgmma_m64n192k16_ss(acc, make_desc(aaddr + kk * 32, 16, 1024, 1), make_desc(baddr + kk * 1024, 4096, 512, 2), (kc | kk) != 0);
                wgmma_commit();
                wgmma_wait<0>();
                if ((tid & 127) == 0) mbar_arrive(barE + 8 * st);
                if (++st == G1_STAGES) { st = 0; ph ^= 1; }
            }
            const float2 st0 = stats[cw * 64 + wl * 16 + g], st1 = stats[cw * 64 + wl * 16 + g + 8];
            bf16* o0 = g_hh + (size_t)row0 * F_ + cb * 224 + 128;
            g1_epilogue<12>(acc, cs + 128, cs + 224 + 128, st0, st1, o0, o0 + 8 * F_, t);
        }
    }
}

constexpr int G2_THREADS = 384;
constexpr int G2_STAGES = 6;
constexpr int G2_STAGE = 32768;
constexpr int G2_OFF_X = G2_STAGES * G2_STAGE;
constexpr int G2_OFF_BAR = G2_OFF_X + 32768;
constexpr int G2_SMEM = G2_OFF_BAR + 128;
constexpr int G2_KSTEPS = 14;

__global__ void __cluster_dims__(2, 1, 1) __launch_bounds__(G2_THREADS, 1)
gemm2_kernel(const __grid_constant__ CUtensorMap mapHH, const __grid_constant__ CUtensorMap mapWd, bf16* __restrict__ out) {
    extern __shared__ __align__(1024) uint8_t smem_raw[];
    const uint32_t sb = smem_u32(smem_raw);
    const int tid = threadIdx.x, lane = tid & 31, warp = tid >> 5, wgi = tid >> 7;
    const int ks = blockIdx.x & 1, nb = (blockIdx.x >> 1) & 3, rb = blockIdx.x >> 3;
    const uint32_t barF = sb + G2_OFF_BAR;
    const uint32_t barE = barF + 8 * G2_STAGES;
    if (tid == 0) {
        for (int i = 0; i < G2_STAGES; i++) { mbar_init(barF + 8 * i, 1); mbar_init(barE + 8 * i, 2); }
        asm volatile("fence.mbarrier_init.release.cluster;" ::: "memory");
        if (blockIdx.x == 0) g_flag = 0;
    }
    __syncthreads();
    cluster_arrive();

    if (wgi == 0) {
        if (tid == 0) {
            int st = 0, ph = 1;
            for (int it = 0; it < G2_KSTEPS; it++) {
                mbar_wait(barE + 8 * st, ph);
                const uint32_t dst = sb + st * G2_STAGE;
                const int k0 = ks * 896 + it * 64;
                mbar_expect_tx(barF + 8 * st, 32768);
                tma_load_2d(dst, &mapHH, barF + 8 * st, k0, rb * 128);
                tma_load_3d(dst + 16384, &mapWd, barF + 8 * st, 0, k0, nb * 2);
                if (++st == G2_STAGES) { st = 0; ph ^= 1; }
            }
        }
        __syncwarp();
        cluster_wait();
        cluster_arrive();
        cluster_wait();
    } else {
        const int cw = wgi - 1;
        const int g = lane >> 2, t = lane & 3, wl = warp & 3;
        const int tl = tid & 127;
        int st = 0, ph = 0;
        float acc[64];
#pragma unroll 1
        for (int it = 0; it < G2_KSTEPS; it++) {
            mbar_wait(barF + 8 * st, ph);
            wgmma_fence();
            const uint32_t aaddr = sb + st * G2_STAGE + cw * 8192;
            const uint32_t baddr = sb + st * G2_STAGE + 16384;
#pragma unroll
            for (int kk = 0; kk < 4; kk++)
                wgmma_m64n128k16_ss(acc, make_desc(aaddr + kk * 32, 16, 1024, 1), make_desc(baddr + kk * 2048, 8192, 1024, 1), (it | kk) != 0);
            wgmma_commit();
            wgmma_wait<0>();
            if (tl == 0) mbar_arrive(barE + 8 * st);
            if (++st == G2_STAGES) { st = 0; ph ^= 1; }
        }
        cluster_wait();
        if (cw != ks) {
            const uint32_t dst = mapa(sb + G2_OFF_X + tl * 16, (uint32_t)(ks ^ 1));
#pragma unroll
            for (int i = 0; i < 16; i++) st_cluster_v4f(dst + i * 2048, acc[4 * i], acc[4 * i + 1], acc[4 * i + 2], acc[4 * i + 3]);
        }
        cluster_arrive();
        cluster_wait();
        if (cw == ks) {
            const float4* xb = reinterpret_cast<const float4*>(smem_raw + G2_OFF_X) + tl;
            const int row0 = rb * 128 + cw * 64 + wl * 16 + g;
            const bf16* h0 = g_h + (size_t)row0 * D_ + nb * 128;
            bf16* o0 = out + (size_t)row0 * D_ + nb * 128;
#pragma unroll
            for (int j0 = 0; j0 < 16; j0 += 4) {
                uint32_t P0[4], P1[4];
#pragma unroll
                for (int jj = 0; jj < 4; jj++) {
                    const int j = j0 + jj;
                    const float4 x = xb[j * 128];
                    const uint32_t ha = *reinterpret_cast<const uint32_t*>(h0 + 8 * j + 2 * t);
                    const uint32_t hb = *reinterpret_cast<const uint32_t*>(h0 + 8 * D_ + 8 * j + 2 * t);
                    P0[jj] = pack_bf16(bf_lo(ha) + bf16r(acc[4 * j] + x.x), bf_hi(ha) + bf16r(acc[4 * j + 1] + x.y));
                    P1[jj] = pack_bf16(bf_lo(hb) + bf16r(acc[4 * j + 2] + x.z), bf_hi(hb) + bf16r(acc[4 * j + 3] + x.w));
                }
                quad_transpose(P0[0], P0[1], P0[2], P0[3], t);
                quad_transpose(P1[0], P1[1], P1[2], P1[3], t);
                *reinterpret_cast<uint4*>(o0 + 8 * (j0 + t)) = make_uint4(P0[0], P0[1], P0[2], P0[3]);
                *reinterpret_cast<uint4*>(o0 + 8 * D_ + 8 * (j0 + t)) = make_uint4(P1[0], P1[1], P1[2], P1[3]);
            }
        }
    }
}

typedef CUresult (*EncodeFn)(CUtensorMap*, CUtensorMapDataType, cuuint32_t, void*, const cuuint64_t*, const cuuint64_t*,
                             const cuuint32_t*, const cuuint32_t*, CUtensorMapInterleave, CUtensorMapSwizzle,
                             CUtensorMapL2promotion, CUtensorMapFloatOOBfill);

static void enc2d(EncodeFn enc, CUtensorMap* m, const void* p, int rows, int cols, int brows, int bcols) {
    cuuint64_t dims[2] = {(cuuint64_t)cols, (cuuint64_t)rows};
    cuuint64_t strides[1] = {(cuuint64_t)cols * 2};
    cuuint32_t box[2] = {(cuuint32_t)bcols, (cuuint32_t)brows};
    cuuint32_t es[2] = {1, 1};
    enc(m, CU_TENSOR_MAP_DATA_TYPE_BFLOAT16, 2, const_cast<void*>(p), dims, strides, box, es, CU_TENSOR_MAP_INTERLEAVE_NONE,
        CU_TENSOR_MAP_SWIZZLE_128B, CU_TENSOR_MAP_L2_PROMOTION_L2_128B, CU_TENSOR_MAP_FLOAT_OOB_FILL_NONE);
}
static void enc3d(EncodeFn enc, CUtensorMap* m, const void* p, int rows, int cols, int atom, int brows, int natoms) {
    cuuint64_t dims[3] = {(cuuint64_t)atom, (cuuint64_t)rows, (cuuint64_t)(cols / atom)};
    cuuint64_t strides[2] = {(cuuint64_t)cols * 2, (cuuint64_t)atom * 2};
    cuuint32_t box[3] = {(cuuint32_t)atom, (cuuint32_t)brows, (cuuint32_t)natoms};
    cuuint32_t es[3] = {1, 1, 1};
    enc(m, CU_TENSOR_MAP_DATA_TYPE_BFLOAT16, 3, const_cast<void*>(p), dims, strides, box, es, CU_TENSOR_MAP_INTERLEAVE_NONE,
        atom == 32 ? CU_TENSOR_MAP_SWIZZLE_64B : CU_TENSOR_MAP_SWIZZLE_128B, CU_TENSOR_MAP_L2_PROMOTION_L2_128B, CU_TENSOR_MAP_FLOAT_OOB_FILL_NONE);
}

extern "C" void kernel_launch(void* const* d_in, const int* in_sizes, int n_in, void* d_out, int out_size) {
    const bf16* q = (const bf16*)d_in[0];
    const bf16* k = (const bf16*)d_in[1];
    const bf16* v = (const bf16*)d_in[2];
    const bf16* shift_k = (const bf16*)d_in[3];
    const bf16* ssm_k = (const bf16*)d_in[4];
    const bf16* ssm_D = (const bf16*)d_in[5];
    const bf16* wg = (const bf16*)d_in[7];
    const bf16* wu = (const bf16*)d_in[8];
    const bf16* wd = (const bf16*)d_in[9];
    bf16* out = (bf16*)d_out;

    static EncodeFn enc = nullptr;
    static void *p_h = nullptr, *p_hh = nullptr;
    if (!enc) {
        void* fn = nullptr; cudaDriverEntryPointQueryResult qr;
        cudaGetDriverEntryPoint("cuTensorMapEncodeTiled", &fn, cudaEnableDefault, &qr);
        enc = (EncodeFn)fn;
        cudaGetSymbolAddress(&p_h, g_h);
        cudaGetSymbolAddress(&p_hh, g_hh);
        cudaFuncSetAttribute(conv_kernel, cudaFuncAttributeMaxDynamicSharedMemorySize, (int)sizeof(K1Smem));
        cudaFuncSetAttribute(gemm1_kernel, cudaFuncAttributeMaxDynamicSharedMemorySize, G1_SMEM);
        cudaFuncSetAttribute(gemm2_kernel, cudaFuncAttributeMaxDynamicSharedMemorySize, G2_SMEM);
    }
    CUtensorMap mA, mG4, mU4, mG3, mU3, mHH, mWd;
    enc2d(enc, &mA, p_h, S_, D_, 128, 64);
    enc3d(enc, &mG4, wg, D_, F_, 32, 64, 4);
    enc3d(enc, &mU4, wu, D_, F_, 32, 64, 4);
    enc3d(enc, &mG3, wg, D_, F_, 32, 64, 3);
    enc3d(enc, &mU3, wu, D_, F_, 32, 64, 3);
    enc2d(enc, &mHH, p_hh, S_, F_, 128, 64);
    enc3d(enc, &mWd, wd, F_, D_, 64, 64, 2);

    cudaStream_t st = cudaStreamPerThread;
    conv_kernel<<<128, K1_THREADS, sizeof(K1Smem), st>>>(q, k, v, shift_k, ssm_k, ssm_D, wg, wu);
    gemm1_kernel<<<128, G1_THREADS, G1_SMEM, st>>>(mA, mG4, mU4, mG3, mU3);
    gemm2_kernel<<<128, G2_THREADS, G2_SMEM, st>>>(mHH, mWd, out);
}
```

```cpp
#include <cuda_runtime.h>
#include <cuda_bf16.h>
#include <cuda.h>
#include <stdint.h>

typedef __nv_bfloat16 bf16;
constexpr int S_ = 2048, D_ = 512, F_ = 1792;

__device__ bf16 g_yT[D_ * S_];
__device__ bf16 g_h[S_ * D_];
__device__ bf16 g_hn[S_ * D_];
__device__ bf16 g_hh[S_ * F_];

#define TM(k, i)
#define TR(k, i)
__device__ __forceinline__ uint32_t smem_u32(const void* p) { return (uint32_t)__cvta_generic_to_shared(p); }
__device__ __forceinline__ float bf16r(float x) { return __bfloat162float(__float2bfloat16_rn(x)); }
__device__ __forceinline__ float bf_lo(uint32_t w) { return __uint_as_float(w << 16); }
__device__ __forceinline__ float bf_hi(uint32_t w) { return __uint_as_float(w & 0xffff0000u); }
__device__ __forceinline__ uint32_t pack_bf16(float lo, float hi) {
    __nv_bfloat162 v = __floats2bfloat162_rn(lo, hi);
    return *reinterpret_cast<uint32_t*>(&v);
}
__device__ __forceinline__ uint32_t hmul2(uint32_t a, uint32_t b) {
    __nv_bfloat162 r = __hmul2_rn(*reinterpret_cast<__nv_bfloat162*>(&a), *reinterpret_cast<__nv_bfloat162*>(&b));
    return *reinterpret_cast<uint32_t*>(&r);
}
__device__ __forceinline__ uint32_t hadd2(uint32_t a, uint32_t b) {
    __nv_bfloat162 r = __hadd2_rn(*reinterpret_cast<__nv_bfloat162*>(&a), *reinterpret_cast<__nv_bfloat162*>(&b));
    return *reinterpret_cast<uint32_t*>(&r);
}
__device__ __forceinline__ void mbar_init(uint32_t bar, int cnt) { asm volatile("mbarrier.init.shared::cta.b64 [%0], %1;" :: "r"(bar), "r"(cnt)); }
__device__ __forceinline__ void mbar_expect_tx(uint32_t bar, uint32_t bytes) { asm volatile("mbarrier.arrive.expect_tx.shared::cta.b64 _, [%0], %1;" :: "r"(bar), "r"(bytes) : "memory"); }
__device__ __forceinline__ void mbar_arrive(uint32_t bar) { asm volatile("mbarrier.arrive.shared::cta.b64 _, [%0];" :: "r"(bar) : "memory"); }
__device__ __forceinline__ void mbar_arrive_cluster(uint32_t bar, uint32_t cta) {
    asm volatile("{\n.reg .b32 ra;\nmapa.shared::cluster.u32 ra, %0, %1;\nmbarrier.arrive.shared::cluster.b64 _, [ra];\n}" :: "r"(bar), "r"(cta) : "memory");
}
__device__ __forceinline__ void mbar_wait(uint32_t bar, uint32_t parity) {
    asm volatile("{\n.reg .pred P1;\nLAB_WAIT:\nmbarrier.try_wait.parity.shared::cta.b64 P1, [%0], %1;\n@P1 bra DONE;\nbra LAB_WAIT;\nDONE:\n}" :: "r"(bar), "r"(parity) : "memory");
}
__device__ __forceinline__ void mbar_wait_cluster(uint32_t bar, uint32_t parity) {
    asm volatile("{\n.reg .pred P1;\nLAB_WAIT:\nmbarrier.try_wait.parity.acquire.cluster.shared::cta.b64 P1, [%0], %1;\n@P1 bra DONE;\nbra LAB_WAIT;\nDONE:\n}" :: "r"(bar), "r"(parity) : "memory");
}
__device__ __forceinline__ void tma_load_2d(uint32_t dst, const CUtensorMap* map, uint32_t bar, int c0, int c1) {
    asm volatile("cp.async.bulk.tensor.2d.shared::cluster.global.mbarrier::complete_tx::bytes [%0], [%1, {%3, %4}], [%2];"
        :: "r"(dst), "l"(map), "r"(bar), "r"(c0), "r"(c1) : "memory");
}
__device__ __forceinline__ void tma_load_2d_mc(uint32_t dst, const CUtensorMap* map, uint32_t bar, int c0, int c1, uint16_t mask) {
    asm volatile("cp.async.bulk.tensor.2d.shared::cluster.global.mbarrier::complete_tx::bytes.multicast::cluster [%0], [%1, {%3, %4}], [%2], %5;"
        :: "r"(dst), "l"(map), "r"(bar), "r"(c0), "r"(c1), "h"(mask) : "memory");
}
__device__ __forceinline__ void tma_load_3d(uint32_t dst, const CUtensorMap* map, uint32_t bar, int c0, int c1, int c2) {
    asm volatile("cp.async.bulk.tensor.3d.shared::cluster.global.mbarrier::complete_tx::bytes [%0], [%1, {%3, %4, %5}], [%2];"
        :: "r"(dst), "l"(map), "r"(bar), "r"(c0), "r"(c1), "r"(c2) : "memory");
}
__device__ __forceinline__ void cluster_arrive() { asm volatile("barrier.cluster.arrive.aligned;" ::: "memory"); }
__device__ __forceinline__ void cluster_arrive_relaxed() { asm volatile("barrier.cluster.arrive.relaxed.aligned;" ::: "memory"); }
__device__ __forceinline__ void cluster_wait() { asm volatile("barrier.cluster.wait.aligned;" ::: "memory"); }
__device__ __forceinline__ uint32_t mapa(uint32_t addr, uint32_t cta) {
    uint32_t r; asm volatile("mapa.shared::cluster.u32 %0, %1, %2;" : "=r"(r) : "r"(addr), "r"(cta)); return r;
}
__device__ __forceinline__ void st_async_v2(uint32_t addr, uint32_t a, uint32_t b, uint32_t rbar) {
    asm volatile("st.async.weak.shared::cluster.mbarrier::complete_tx::bytes.v2.b32 [%0], {%1, %2}, [%3];" :: "r"(addr), "r"(a), "r"(b), "r"(rbar) : "memory");
}
__device__ __forceinline__ void st_async_v4f(uint32_t addr, float a, float b, float c, float d, uint32_t rbar) {
    asm volatile("st.async.weak.shared::cluster.mbarrier::complete_tx::bytes.v4.f32 [%0], {%1, %2, %3, %4}, [%5];" :: "r"(addr), "f"(a), "f"(b), "f"(c), "f"(d), "r"(rbar) : "memory");
}
__device__ __forceinline__ void wgmma_fence() { asm volatile("wgmma.fence.sync.aligned;" ::: "memory"); }
__device__ __forceinline__ void wgmma_commit() { asm volatile("wgmma.commit_group.sync.aligned;" ::: "memory"); }
template <int N> __device__ __forceinline__ void wgmma_wait() { asm volatile("wgmma.wait_group.sync.aligned %0;" :: "n"(N) : "memory"); }
__device__ __forceinline__ uint64_t make_desc(uint32_t addr, uint32_t lbo_bytes, uint32_t sbo_bytes, uint32_t layout) {
    return (uint64_t)((addr & 0x3FFFF) >> 4) | ((uint64_t)(lbo_bytes >> 4) << 16) | ((uint64_t)(sbo_bytes >> 4) << 32) | ((uint64_t)layout << 62);
}
template <int R> __device__ __forceinline__ void reg_alloc() { asm volatile("setmaxnreg.inc.sync.aligned.u32 %0;" :: "n"(R)); }
template <int R> __device__ __forceinline__ void reg_dealloc() { asm volatile("setmaxnreg.dec.sync.aligned.u32 %0;" :: "n"(R)); }
__device__ __forceinline__ void named_bar(int id, int n) { asm volatile("bar.sync %0, %1;" :: "r"(id), "r"(n) : "memory"); }

__device__ __forceinline__ void wgmma_m64n128k16_ss(float (&d)[64], uint64_t descA, uint64_t descB, int scaleD) {
    asm volatile("{\n.reg .pred p;\nsetp.ne.b32 p, %66, 0;\n"
        "wgmma.mma_async.sync.aligned.m64n128k16.f32.bf16.bf16 {%0, %1, %2, %3, %4, %5, %6, %7, %8, %9, %10, %11, %12, %13, %14, %15, %16, %17, %18, %19, %20, %21, %22, %23, %24, %25, %26, %27, %28, %29, %30, %31, %32, %33, %34, %35, %36, %37, %38, %39, %40, %41, %42, %43, %44, %45, %46, %47, %48, %49, %50, %51, %52, %53, %54, %55, %56, %57, %58, %59, %60, %61, %62, %63}, %64, %65, p, 1, 1, 0, 1;\n}\n"
        : "+f"(d[0]), "+f"(d[1]), "+f"(d[2]), "+f"(d[3]), "+f"(d[4]), "+f"(d[5]), "+f"(d[6]), "+f"(d[7]), "+f"(d[8]), "+f"(d[9]), "+f"(d[10]), "+f"(d[11]), "+f"(d[12]), "+f"(d[13]), "+f"(d[14]), "+f"(d[15]), "+f"(d[16]), "+f"(d[17]), "+f"(d[18]), "+f"(d[19]), "+f"(d[20]), "+f"(d[21]), "+f"(d[22]), "+f"(d[23]), "+f"(d[24]), "+f"(d[25]), "+f"(d[26]), "+f"(d[27]), "+f"(d[28]), "+f"(d[29]), "+f"(d[30]), "+f"(d[31]), "+f"(d[32]), "+f"(d[33]), "+f"(d[34]), "+f"(d[35]), "+f"(d[36]), "+f"(d[37]), "+f"(d[38]), "+f"(d[39]), "+f"(d[40]), "+f"(d[41]), "+f"(d[42]), "+f"(d[43]), "+f"(d[44]), "+f"(d[45]), "+f"(d[46]), "+f"(d[47]), "+f"(d[48]), "+f"(d[49]), "+f"(d[50]), "+f"(d[51]), "+f"(d[52]), "+f"(d[53]), "+f"(d[54]), "+f"(d[55]), "+f"(d[56]), "+f"(d[57]), "+f"(d[58]), "+f"(d[59]), "+f"(d[60]), "+f"(d[61]), "+f"(d[62]), "+f"(d[63])
        : "l"(descA), "l"(descB), "r"(scaleD));
}

__device__ __forceinline__ void wgmma_m64n64k16_ss(float (&d)[32], uint64_t descA, uint64_t descB, int scaleD) {
    asm volatile("{\n.reg .pred p;\nsetp.ne.b32 p, %34, 0;\n"
        "wgmma.mma_async.sync.aligned.m64n64k16.f32.bf16.bf16 {%0, %1, %2, %3, %4, %5, %6, %7, %8, %9, %10, %11, %12, %13, %14, %15, %16, %17, %18, %19, %20, %21, %22, %23, %24, %25, %26, %27, %28, %29, %30, %31}, %32, %33, p, 1, 1, 0, 1;\n}\n"
        : "+f"(d[0]), "+f"(d[1]), "+f"(d[2]), "+f"(d[3]), "+f"(d[4]), "+f"(d[5]), "+f"(d[6]), "+f"(d[7]), "+f"(d[8]), "+f"(d[9]), "+f"(d[10]), "+f"(d[11]), "+f"(d[12]), "+f"(d[13]), "+f"(d[14]), "+f"(d[15]), "+f"(d[16]), "+f"(d[17]), "+f"(d[18]), "+f"(d[19]), "+f"(d[20]), "+f"(d[21]), "+f"(d[22]), "+f"(d[23]), "+f"(d[24]), "+f"(d[25]), "+f"(d[26]), "+f"(d[27]), "+f"(d[28]), "+f"(d[29]), "+f"(d[30]), "+f"(d[31])
        : "l"(descA), "l"(descB), "r"(scaleD));
}

__device__ __forceinline__ void quad_transpose(uint32_t& r0, uint32_t& r1, uint32_t& r2, uint32_t& r3, int t) {
    const bool o1 = t & 1, o2 = t & 2;
    uint32_t x, y;
    x = o1 ? r0 : r1; y = __shfl_xor_sync(0xffffffffu, x, 1); if (o1) r0 = y; else r1 = y;
    x = o1 ? r2 : r3; y = __shfl_xor_sync(0xffffffffu, x, 1); if (o1) r2 = y; else r3 = y;
    x = o2 ? r0 : r2; y = __shfl_xor_sync(0xffffffffu, x, 2); if (o2) r0 = y; else r2 = y;
    x = o2 ? r1 : r3; y = __shfl_xor_sync(0xffffffffu, x, 2); if (o2) r1 = y; else r3 = y;
}

constexpr int K1_THREADS = 256;
constexpr int UT_PAD = 128;
constexpr int UT_LEN = UT_PAD + S_;
constexpr int KR_LEN = 2080;
constexpr int YP_LEN = S_ + (S_ / 32) * 8;

struct __align__(128) K1Smem {
    bf16 uT[4][UT_LEN];
    bf16 kr[4][2][KR_LEN];
    float yP[4][YP_LEN];
    uint64_t bar;
    uint8_t pad[32768];
};

__device__ __forceinline__ void mma16816(float (&c)[4], uint32_t a0, uint32_t a1, uint32_t a2, uint32_t a3, uint32_t b0, uint32_t b1) {
    asm("mma.sync.aligned.m16n8k16.row.col.f32.bf16.bf16.f32 {%0,%1,%2,%3}, {%4,%5,%6,%7}, {%8,%9}, {%0,%1,%2,%3};"
        : "+f"(c[0]), "+f"(c[1]), "+f"(c[2]), "+f"(c[3])
        : "r"(a0), "r"(a1), "r"(a2), "r"(a3), "r"(b0), "r"(b1));
}
__device__ __forceinline__ void ldsm_x4(uint32_t& r0, uint32_t& r1, uint32_t& r2, uint32_t& r3, uint32_t addr) {
    asm volatile("ldmatrix.sync.aligned.m8n8.x4.shared.b16 {%0,%1,%2,%3}, [%4];" : "=r"(r0), "=r"(r1), "=r"(r2), "=r"(r3) : "r"(addr) : "memory");
}

__device__ __forceinline__ void conv_mma(const bf16* uTc, const bf16* krlane, float (&acc)[16][4], int lane, int half) {
    const int lrow = lane & 7, lk = (lane >> 3) & 1, lt = lane >> 4;
    const uint32_t ubase = smem_u32(uTc) + (UT_PAD + 16 * (8 * lt + lrow) + 8 * lk) * 2;
#pragma unroll 1
    for (int pp = 0; pp < 4; pp++) {
        const int p = half * 4 + pp;
        uint32_t U[16][2];
#pragma unroll
        for (int j = 0; j < 16; j += 2) ldsm_x4(U[j][0], U[j][1], U[j + 1][0], U[j + 1][1], ubase + (j * 128 - p * 16) * 2);
        const uint32_t* kp = reinterpret_cast<const uint32_t*>(krlane - 16 * p);
        const volatile uint32_t* kpv = kp;
        uint32_t a0 = kp[0], a1 = kp[-4], a2 = kp[4], a3 = kpv[0];
#pragma unroll
        for (int q = 0; q < 16; q++) {
            uint32_t b0 = 0, b1 = 0, b2 = 0, b3 = 0;
            if (q < 15) { b0 = kp[-64 * (q + 1)]; b1 = kp[-64 * (q + 1) - 4]; b2 = kp[-64 * (q + 1) + 4]; b3 = kpv[-64 * (q + 1)]; }
#pragma unroll
            for (int n = 15; n >= q; n--) mma16816(acc[n], a0, a1, a2, a3, U[n - q][0], U[n - q][1]);
            a0 = b0; a1 = b1; a2 = b2; a3 = b3;
        }
    }
}

__global__ void __cluster_dims__(2, 1, 1) __launch_bounds__(K1_THREADS, 1)
conv_kernel(const bf16* __restrict__ k, const bf16* __restrict__ v,
            const bf16* __restrict__ shift_k, const bf16* __restrict__ ssm_k) {
    extern __shared__ __align__(1024) uint8_t smem_raw[];
    K1Smem& sm = *reinterpret_cast<K1Smem*>(smem_raw);
    const int tid = threadIdx.x, lane = tid & 31, warp = tid >> 5;
    const int bid = blockIdx.x;
    const int rank = bid & 1;
    const int c0 = 8 * (bid >> 1);
    const int cown = c0 + 4 * rank;
#define TMT 0
    TM(0, 0);
    const uint32_t bar = smem_u32(&sm.bar);
    if (tid == 0) {
        mbar_init(bar, 1);
        asm volatile("fence.mbarrier_init.release.cluster;" ::: "memory");
        mbar_expect_tx(bar, 1024 * 4 * 2);
    }
    cluster_arrive_relaxed();

    const int s0 = 1024 * rank + 4 * tid;
    uint4 kk[7], vv[4], sw[4];
#pragma unroll
    for (int i = 0; i < 4; i++) kk[3 + i] = __ldg(reinterpret_cast<const uint4*>(k + (size_t)(s0 + i) * D_ + c0));
#pragma unroll
    for (int i = 0; i < 4; i++) vv[i] = __ldg(reinterpret_cast<const uint4*>(v + (size_t)(s0 + i) * D_ + c0));
    if (lane == 0) {
#pragma unroll
        for (int i = 0; i < 3; i++) {
            const int s = s0 - 3 + i;
            kk[i] = (s >= 0) ? __ldg(reinterpret_cast<const uint4*>(k + (size_t)s * D_ + c0)) : make_uint4(0, 0, 0, 0);
        }
    }
#pragma unroll
    for (int i = 0; i < 4; i++) sw[i] = __ldg(reinterpret_cast<const uint4*>(shift_k + (size_t)c0 * 4) + i);
    uint4 kq[4]; uint32_t nx[4];
#pragma unroll
    for (int c = 0; c < 4; c++) {
        const bf16* kr = ssm_k + (size_t)(cown + c) * S_;
        kq[c] = __ldg(reinterpret_cast<const uint4*>(kr) + tid);
        nx[c] = (tid < 255) ? (uint32_t)__ldg(reinterpret_cast<const unsigned short*>(kr) + 8 * tid + 8) : 0u;
    }
    if (tid < 64) *reinterpret_cast<uint4*>(&sm.uT[tid >> 4][(tid & 15) * 8]) = make_uint4(0, 0, 0, 0);
#pragma unroll
    for (int i = 0; i < 3; i++) {
        uint4 t;
        t.x = __shfl_up_sync(0xffffffffu, kk[4 + i].x, 1); t.y = __shfl_up_sync(0xffffffffu, kk[4 + i].y, 1);
        t.z = __shfl_up_sync(0xffffffffu, kk[4 + i].z, 1); t.w = __shfl_up_sync(0xffffffffu, kk[4 + i].w, 1);
        if (lane != 0) kk[i] = t;
    }
    uint32_t kvw[4][4];
    const uint32_t* kkw = reinterpret_cast<const uint32_t*>(kk);
    const uint32_t* vvw = reinterpret_cast<const uint32_t*>(vv);
#pragma unroll
    for (int i2 = 0; i2 < 4; i2++) {
        const uint32_t t0 = __byte_perm(sw[i2].x, sw[i2].z, 0x5410), t1 = __byte_perm(sw[i2].x, sw[i2].z, 0x7632);
        const uint32_t t2 = __byte_perm(sw[i2].y, sw[i2].w, 0x5410), t3 = __byte_perm(sw[i2].y, sw[i2].w, 0x7632);
#pragma unroll
        for (int r = 0; r < 4; r++) {
            uint32_t a = hmul2(kkw[(r + 0) * 4 + i2], t3);
            a = hadd2(a, hmul2(kkw[(r + 1) * 4 + i2], t2));
            a = hadd2(a, hmul2(kkw[(r + 2) * 4 + i2], t1));
            a = hadd2(a, hmul2(kkw[(r + 3) * 4 + i2], t0));
            kvw[r][i2] = hmul2(a, vvw[r * 4 + i2]);
        }
    }
    TM(0, 1);
    cluster_wait();
    {
        const uint32_t rbar = mapa(bar, (uint32_t)(rank ^ 1));
#pragma unroll
        for (int i2 = 0; i2 < 4; i2++) {
#pragma unroll
            for (int e = 0; e < 2; e++) {
                const uint32_t sel = e ? 0x7632 : 0x5410;
                const uint32_t w0 = __byte_perm(kvw[0][i2], kvw[1][i2], sel), w1 = __byte_perm(kvw[2][i2], kvw[3][i2], sel);
                const int cc = 2 * i2 + e;
                if ((cc >> 2) == rank) {
                    *reinterpret_cast<uint2*>(&sm.uT[cc & 3][UT_PAD + s0]) = make_uint2(w0, w1);
                } else {
                    st_async_v2(mapa(smem_u32(&sm.uT[cc & 3][UT_PAD + s0]), (uint32_t)(rank ^ 1)), w0, w1, rbar);
                }
            }
        }
    }
#pragma unroll
    for (int c = 0; c < 4; c++) {
        uint4 a, b;
        a.x = __byte_perm(kq[c].w, 0, 0x1032); a.y = __byte_perm(kq[c].z, 0, 0x1032);
        a.z = __byte_perm(kq[c].y, 0, 0x1032); a.w = __byte_perm(kq[c].x, 0, 0x1032);
        b.x = __byte_perm(nx[c], kq[c].w, 0x7610); b.y = __byte_perm(kq[c].w, kq[c].z, 0x7610);
        b.z = __byte_perm(kq[c].z, kq[c].y, 0x7610); b.w = __byte_perm(kq[c].y, kq[c].x, 0x7610);
        *reinterpret_cast<uint4*>(&sm.kr[c][0][2040 - 8 * tid]) = a;
        *reinterpret_cast<uint4*>(&sm.kr[c][1][2040 - 8 * tid]) = b;
        if (tid == 0) {
            *reinterpret_cast<uint4*>(&sm.kr[c][1][2048]) = make_uint4(kq[c].x & 0xffffu, 0, 0, 0);
        } else if (tid < 8) {
            if (tid < 4) *reinterpret_cast<uint4*>(&sm.kr[c][1][2048 + 8 * tid]) = make_uint4(0, 0, 0, 0);
            else *reinterpret_cast<uint4*>(&sm.kr[c][0][2048 + 8 * (tid - 4)]) = make_uint4(0, 0, 0, 0);
        }
    }
    TM(0, 3);
    __syncthreads();
    mbar_wait_cluster(bar, 0);
    TM(0, 4);

    const int ch = warp >> 1, half = warp & 1;
    const int g = lane >> 2, t = lane & 3;
    float acc[16][4];
#pragma unroll
    for (int i = 0; i < 16; i++) { acc[i][0] = acc[i][1] = acc[i][2] = acc[i][3] = 0.f; }
    const bf16* krlane = (g & 1) ? &sm.kr[ch][0][2047 - g + 2 * t] : &sm.kr[ch][1][2048 - g + 2 * t];
    conv_mma(sm.uT[ch], krlane, acc, lane, half);
    TM(0, 5);
    float* yp = &sm.yP[ch][40 * t + g];
    if (half) {
#pragma unroll
        for (int n = 0; n < 16; n++) {
            yp[160 * n] = acc[n][0];
            yp[160 * n + 16] = acc[n][1];
            yp[160 * n + 8] = acc[n][2];
            yp[160 * n + 24] = acc[n][3];
        }
    }
    named_bar(1 + ch, 64);
    if (!half) {
#pragma unroll
        for (int n = 0; n < 16; n++) {
            yp[160 * n] += acc[n][0];
            yp[160 * n + 16] += acc[n][1];
            yp[160 * n + 8] += acc[n][2];
            yp[160 * n + 24] += acc[n][3];
        }
    }
    named_bar(1 + ch, 64);
    TM(0, 6);
    {
        const int tt = tid & 63;
        bf16* dst = g_yT + (size_t)(cown + ch) * S_;
#pragma unroll
        for (int j = 0; j < 4; j++) {
            const int s = (j * 64 + tt) * 8;
            const float* src = &sm.yP[ch][s + (s >> 5) * 8];
            const float4 a = *reinterpret_cast<const float4*>(src), b = *reinterpret_cast<const float4*>(src + 4);
            *reinterpret_cast<uint4*>(dst + s) = make_uint4(pack_bf16(a.x, a.y), pack_bf16(a.z, a.w), pack_bf16(b.x, b.y), pack_bf16(b.z, b.w));
        }
    }
    TM(0, 7);
#undef TMT
}

constexpr int R_THREADS = 512;
constexpr int R_ROWS = 16;

__device__ __forceinline__ float warp_sum(float s) {
#pragma unroll
    for (int o = 16; o > 0; o >>= 1) s += __shfl_xor_sync(0xffffffffu, s, o);
    return s;
}
__device__ __forceinline__ uint32_t hsub2(uint32_t a, uint32_t b) {
    __nv_bfloat162 r = __hsub2_rn(*reinterpret_cast<__nv_bfloat162*>(&a), *reinterpret_cast<__nv_bfloat162*>(&b));
    return *reinterpret_cast<uint32_t*>(&r);
}
__device__ __forceinline__ void ln_row(const uint32_t (&x)[8], uint32_t (&o)[8]) {
    float s0 = 0.f, s1 = 0.f;
#pragma unroll
    for (int i = 0; i < 8; i++) { s0 += bf_lo(x[i]); s1 += bf_hi(x[i]); }
    const float mean = warp_sum(s0 + s1) * (1.0f / D_);
    float ss0 = 0.f, ss1 = 0.f;
#pragma unroll
    for (int i = 0; i < 8; i++) { const float d0 = bf_lo(x[i]) - mean, d1 = bf_hi(x[i]) - mean; ss0 += d0 * d0; ss1 += d1 * d1; }
    const float var = bf16r(warp_sum(ss0 + ss1) * (1.0f / D_));
    const float rinv = 1.0f / bf16r(sqrtf(bf16r(var + 1e-5f)));
    const uint32_t m2 = pack_bf16(mean, mean);
#pragma unroll
    for (int i = 0; i < 8; i++) {
        const uint32_t d = hsub2(x[i], m2);
        o[i] = pack_bf16(bf_lo(d) * rinv, bf_hi(d) * rinv);
    }
}

__global__ void __launch_bounds__(R_THREADS)
row_kernel(const bf16* __restrict__ q, const bf16* __restrict__ k, const bf16* __restrict__ v,
           const bf16* __restrict__ shift_k, const bf16* __restrict__ ssm_D) {
    __shared__ __align__(16) uint32_t ys[R_ROWS][D_ / 2 + 4];
    const int tid = threadIdx.x, lane = tid & 31, warp = tid >> 5;
    const int s0 = blockIdx.x * R_ROWS;
#define TMT 0
    TM(1, 0);
    const int r0 = s0 + warp;
    uint4 qq[2], vv[2], kk[4][2], sw[2][4], dd[2];
#pragma unroll
    for (int i = 0; i < 2; i++) {
        const int cb = 8 * (lane + 32 * i);
        qq[i] = __ldg(reinterpret_cast<const uint4*>(q + (size_t)r0 * D_ + cb));
        vv[i] = __ldg(reinterpret_cast<const uint4*>(v + (size_t)r0 * D_ + cb));
#pragma unroll
        for (int r = 0; r < 4; r++) {
            const int s = r0 - 3 + r;
            kk[r][i] = (s >= 0) ? __ldg(reinterpret_cast<const uint4*>(k + (size_t)s * D_ + cb)) : make_uint4(0, 0, 0, 0);
        }
#pragma unroll
        for (int j = 0; j < 4; j++) sw[i][j] = __ldg(reinterpret_cast<const uint4*>(shift_k + (size_t)cb * 4) + j);
        dd[i] = __ldg(reinterpret_cast<const uint4*>(ssm_D + cb));
    }
    {
        const int p = tid & 255, hs = tid >> 8;
        const bf16* y0 = g_yT + (size_t)(2 * p) * S_ + s0 + 8 * hs;
        const uint4 a0 = __ldcg(reinterpret_cast<const uint4*>(y0));
        const uint4 b0 = __ldcg(reinterpret_cast<const uint4*>(y0 + S_));
        const uint32_t aw[4] = {a0.x, a0.y, a0.z, a0.w};
        const uint32_t bw[4] = {b0.x, b0.y, b0.z, b0.w};
#pragma unroll
        for (int j = 0; j < 4; j++) {
            ys[8 * hs + 2 * j][p] = __byte_perm(aw[j], bw[j], 0x5410);
            ys[8 * hs + 2 * j + 1][p] = __byte_perm(aw[j], bw[j], 0x7632);
        }
    }
    uint32_t x[8], kvd[8], qn[8];
#pragma unroll
    for (int i = 0; i < 2; i++) {
        const uint32_t* qw = reinterpret_cast<const uint32_t*>(&qq[i]);
        const uint32_t* vw = reinterpret_cast<const uint32_t*>(&vv[i]);
        const uint32_t* dw = reinterpret_cast<const uint32_t*>(&dd[i]);
#pragma unroll
        for (int j = 0; j < 4; j++) {
            const uint4 w = sw[i][j];
            const uint32_t t0 = __byte_perm(w.x, w.z, 0x5410), t1 = __byte_perm(w.x, w.z, 0x7632);
            const uint32_t t2 = __byte_perm(w.y, w.w, 0x5410), t3 = __byte_perm(w.y, w.w, 0x7632);
            uint32_t a = hmul2(reinterpret_cast<const uint32_t*>(&kk[0][i])[j], t3);
            a = hadd2(a, hmul2(reinterpret_cast<const uint32_t*>(&kk[1][i])[j], t2));
            a = hadd2(a, hmul2(reinterpret_cast<const uint32_t*>(&kk[2][i])[j], t1));
            a = hadd2(a, hmul2(reinterpret_cast<const uint32_t*>(&kk[3][i])[j], t0));
            kvd[4 * i + j] = hmul2(hmul2(a, vw[j]), dw[j]);
            x[4 * i + j] = qw[j];
        }
    }
    ln_row(x, qn);
    __syncthreads();
    TM(1, 1);
    uint32_t h[8], hn[8];
#pragma unroll
    for (int i = 0; i < 2; i++) {
        const uint4 yw4 = *reinterpret_cast<const uint4*>(&ys[warp][4 * (lane + 32 * i)]);
        const uint32_t yw[4] = {yw4.x, yw4.y, yw4.z, yw4.w};
#pragma unroll
        for (int j = 0; j < 4; j++) h[4 * i + j] = hadd2(x[4 * i + j], hmul2(qn[4 * i + j], hadd2(yw[j], kvd[4 * i + j])));
    }
    ln_row(h, hn);
#pragma unroll
    for (int i = 0; i < 2; i++) {
        const size_t off = (size_t)r0 * D_ + 8 * (lane + 32 * i);
        *reinterpret_cast<uint4*>(g_h + off) = make_uint4(h[4 * i], h[4 * i + 1], h[4 * i + 2], h[4 * i + 3]);
        *reinterpret_cast<uint4*>(g_hn + off) = make_uint4(hn[4 * i], hn[4 * i + 1], hn[4 * i + 2], hn[4 * i + 3]);
    }
    TM(1, 2);
#undef TMT
}

constexpr int G1_THREADS = 384;
constexpr int G1_STAGES = 6;
constexpr int G1_A_BYTES = 8 * 16384;
constexpr int G1_B_STAGE = 16384;
constexpr int G1_OFF_B = G1_A_BYTES;
constexpr int G1_OFF_BAR = G1_OFF_B + G1_STAGES * G1_B_STAGE;
constexpr int G1_SMEM = G1_OFF_BAR + 256;

__device__ __forceinline__ float sigmoid_fast(float x) {
    float t; asm("tanh.approx.f32 %0, %1;" : "=f"(t) : "f"(0.5f * x));
    return fmaf(t, 0.5f, 0.5f);
}

template <int NT>
__device__ __forceinline__ void g1_epilogue(const float (&acc)[NT * 8], bf16* out0, int t) {
#pragma unroll
    for (int j0 = 0; j0 < NT; j0 += 4) {
        uint32_t P0[4], P1[4];
#pragma unroll
        for (int jj = 0; jj < 4; jj++) {
            const int j = j0 + jj;
            float r[4];
#pragma unroll
            for (int e = 0; e < 4; e++) r[e] = sigmoid_fast(acc[4 * j + e]) * acc[4 * (NT + j) + e];
            P0[jj] = pack_bf16(r[0], r[1]);
            P1[jj] = pack_bf16(r[2], r[3]);
        }
        quad_transpose(P0[0], P0[1], P0[2], P0[3], t);
        quad_transpose(P1[0], P1[1], P1[2], P1[3], t);
        *reinterpret_cast<uint4*>(out0 + 8 * (j0 + t)) = make_uint4(P0[0], P0[1], P0[2], P0[3]);
        *reinterpret_cast<uint4*>(out0 + 8 * F_ + 8 * (j0 + t)) = make_uint4(P1[0], P1[1], P1[2], P1[3]);
    }
}

__host__ __device__ constexpr int g1_parity(int it) {
    int cnt = 0;
    for (int j = 0; j < it; j++) if ((((j >> 3) ^ (it >> 3)) & 1) == 0 && (j % G1_STAGES) == (it % G1_STAGES)) cnt++;
    return cnt & 1;
}
template <int NT, int U>
__device__ __forceinline__ void g1_unit(uint32_t sb, uint32_t barA, uint32_t barF, uint32_t barE, uint32_t peer, int tl, bf16* outp, int t) {
    float acc[2][NT * 8];
#pragma unroll
    for (int kc = 0; kc < 8; kc++) {
        const int it = 8 * U + kc;
        const int st = it % G1_STAGES, ph = g1_parity(it);
        if (U < 2) mbar_wait(barA + 8 * kc, 0);
        mbar_wait(barF + 8 * st, ph);
        if (tl == 0) TR(1, it);
        wgmma_fence();
        const uint32_t aaddr = sb + kc * 16384;
        const uint32_t baddr = sb + G1_OFF_B + st * G1_B_STAGE;
#pragma unroll
        for (int kk = 0; kk < 4; kk++) {
#pragma unroll
            for (int hf = 0; hf < 2; hf++) {
                if constexpr (NT == 8)
                    wgmma_m64n128k16_ss(acc[hf], make_desc(aaddr + hf * 8192 + kk * 32, 16, 1024, 1), make_desc(baddr + kk * 2048, 8192, 1024, 1), (kc | kk) != 0);
                else
                    wgmma_m64n64k16_ss(acc[hf], make_desc(aaddr + hf * 8192 + kk * 32, 16, 1024, 1), make_desc(baddr + kk * 1024, 4096, 512, 2), (kc | kk) != 0);
            }
        }
        wgmma_commit();
        if (kc > 0) {
            wgmma_wait<1>();
            const int pst = (it - 1) % G1_STAGES;
            if (tl == 0) mbar_arrive(barE + 8 * pst);
        }
    }
    wgmma_wait<0>();
    {
        const int pst = (8 * U + 7) % G1_STAGES;
        if (tl == 0) mbar_arrive(barE + 8 * pst);
    }
    if (tl == 0) TR(2, U);
    g1_epilogue<NT>(acc[0], outp + 64 * U, t);
    g1_epilogue<NT>(acc[1], outp + 64 * U + (size_t)64 * F_, t);
    if (tl == 0) TR(2, 4 + U);
}

__global__ void __cluster_dims__(2, 1, 1) __launch_bounds__(G1_THREADS, 1)
gemm1_kernel(const __grid_constant__ CUtensorMap mapA, const __grid_constant__ CUtensorMap mapG64, const __grid_constant__ CUtensorMap mapU64,
             const __grid_constant__ CUtensorMap mapG32, const __grid_constant__ CUtensorMap mapU32) {
    extern __shared__ __align__(1024) uint8_t smem_raw[];
    const uint32_t sb = smem_u32(smem_raw);
    const int tid = threadIdx.x, lane = tid & 31, warp = tid >> 5, wgi = tid >> 7;
    const int rank = blockIdx.x & 1;
    const int cb = blockIdx.x & 7, rb = blockIdx.x >> 3;
#define TMT 128
    TM(2, 0);
    const uint32_t barA = sb + G1_OFF_BAR;
    const uint32_t barF = barA + 64;
    const uint32_t barE = barF + 16 * G1_STAGES;
    if (tid == 0) {
        for (int i = 0; i < 8; i++) mbar_init(barA + 8 * i, 1);
        for (int i = 0; i < G1_STAGES; i++) { mbar_init(barF + 8 * i, 1); mbar_init(barF + 8 * G1_STAGES + 8 * i, 1); mbar_init(barE + 8 * i, 1); }
        for (int i = 0; i < 8; i++) mbar_expect_tx(barA + 8 * i, 16384);
        asm volatile("fence.mbarrier_init.release.cluster;" ::: "memory");
    }
    __syncthreads();
    cluster_arrive_relaxed();
    cluster_wait();

    if (wgi == 0) {
        reg_dealloc<40>();
        if (tid == 0) {
            int st = 0, ph = 1;
            for (int it = 0; it < 32; it++) {
                const int kc = it & 7, u = it >> 3;
                if (it < 4) {
                    const int c = 2 * it + rank;
                    tma_load_2d_mc(sb + c * 16384, &mapA, barA + 8 * c, c * 64, rb * 128, (uint16_t)3);
                }
                mbar_wait(barE + 8 * st, ph);
                TR(0, it);
                const uint32_t dst = sb + G1_OFF_B + st * G1_B_STAGE;
                const uint32_t bf = barF + (u & 1) * 8 * G1_STAGES + 8 * st;
                if (u < 3) {
                    mbar_expect_tx(bf, 16384);
                    tma_load_2d(dst, &mapG64, bf, cb * 224 + 64 * u, kc * 64);
                    tma_load_2d(dst + 8192, &mapU64, bf, cb * 224 + 64 * u, kc * 64);
                } else {
                    mbar_expect_tx(bf, 8192);
                    tma_load_2d(dst, &mapG32, bf, cb * 224 + 192, kc * 64);
                    tma_load_2d(dst + 4096, &mapU32, bf, cb * 224 + 192, kc * 64);
                }
                if (++st == G1_STAGES) { st = 0; ph ^= 1; }
            }
        }
        __syncwarp();
    } else {
        reg_alloc<232>();
        const int g = lane >> 2, t = lane & 3, wl = warp & 3, tl = tid & 127;
        bf16* outp = g_hh + (size_t)(rb * 128 + wl * 16 + g) * F_ + cb * 224;
        const uint32_t peer = (uint32_t)(rank ^ 1);
        if (wgi == 1) {
            g1_unit<8, 0>(sb, barA, barF, barE, peer, tl, outp, t);
            TM(2, 1);
            g1_unit<8, 2>(sb, barA, barF, barE, peer, tl, outp, t);
            TM(2, 2);
        } else {
            g1_unit<8, 1>(sb, barA, barF + 8 * G1_STAGES, barE, peer, tl, outp, t);
            g1_unit<4, 3>(sb, barA, barF + 8 * G1_STAGES, barE, peer, tl, outp, t);
        }
    }
    cluster_arrive_relaxed();
    cluster_wait();
    TM(2, 3);
}

constexpr int G2_THREADS = 384;
constexpr int G2_STAGES = 6;
constexpr int G2_STAGE = 32768;
constexpr int G2_OFF_X = G2_STAGES * G2_STAGE;
constexpr int G2_OFF_BAR = G2_OFF_X + 32768;
constexpr int G2_SMEM = G2_OFF_BAR + 128;
constexpr int G2_KSTEPS = 14;

__global__ void __cluster_dims__(2, 1, 1) __launch_bounds__(G2_THREADS, 1)
gemm2_kernel(const __grid_constant__ CUtensorMap mapHH, const __grid_constant__ CUtensorMap mapWd, bf16* __restrict__ out) {
    extern __shared__ __align__(1024) uint8_t smem_raw[];
    const uint32_t sb = smem_u32(smem_raw);
    const int tid = threadIdx.x, lane = tid & 31, warp = tid >> 5, wgi = tid >> 7;
    const int ks = blockIdx.x & 1, nb = (blockIdx.x >> 1) & 3, rb = blockIdx.x >> 3;
    TM(3, 0);
    const uint32_t barF = sb + G2_OFF_BAR;
    const uint32_t barE = barF + 8 * G2_STAGES;
    const uint32_t barX = barE + 8 * G2_STAGES;
    if (tid == 0) {
        for (int i = 0; i < G2_STAGES; i++) { mbar_init(barF + 8 * i, 1); mbar_init(barE + 8 * i, 2); }
        mbar_init(barX, 1);
        asm volatile("fence.mbarrier_init.release.cluster;" ::: "memory");
        mbar_expect_tx(barX, 32768);
    }
    __syncthreads();
    cluster_arrive_relaxed();

    if (wgi == 0) {
        if (tid == 0) {
            int st = 0, ph = 1;
            for (int it = 0; it < G2_KSTEPS; it++) {
                mbar_wait(barE + 8 * st, ph);
                const uint32_t dst = sb + st * G2_STAGE;
                const int k0 = ks * 896 + it * 64;
                mbar_expect_tx(barF + 8 * st, 32768);
                tma_load_2d(dst, &mapHH, barF + 8 * st, k0, rb * 128);
                tma_load_3d(dst + 16384, &mapWd, barF + 8 * st, 0, k0, nb * 2);
                if (++st == G2_STAGES) { st = 0; ph ^= 1; }
            }
        }
        __syncwarp();
        cluster_wait();
    } else {
        const int cw = wgi - 1;
        const int g = lane >> 2, t = lane & 3, wl = warp & 3;
        const int tl = tid & 127;
        int st = 0, ph = 0;
        float acc[64];
#pragma unroll 1
        for (int it = 0; it < G2_KSTEPS; it++) {
            mbar_wait(barF + 8 * st, ph);
            if (it == 0) TM(3, 1);
            wgmma_fence();
            const uint32_t aaddr = sb + st * G2_STAGE + cw * 8192;
            const uint32_t baddr = sb + st * G2_STAGE + 16384;
#pragma unroll
            for (int kk = 0; kk < 4; kk++)
                wgmma_m64n128k16_ss(acc, make_desc(aaddr + kk * 32, 16, 1024, 1), make_desc(baddr + kk * 2048, 8192, 1024, 1), (it | kk) != 0);
            wgmma_commit();
            wgmma_wait<0>();
            if (tl == 0) mbar_arrive(barE + 8 * st);
            if (++st == G2_STAGES) { st = 0; ph ^= 1; }
        }
        TM(3, 2);
        cluster_wait();
        if (cw != ks) {
            const uint32_t dst = mapa(sb + G2_OFF_X + tl * 16, (uint32_t)(ks ^ 1));
            const uint32_t rbar = mapa(barX, (uint32_t)(ks ^ 1));
#pragma unroll
            for (int i = 0; i < 16; i++) st_async_v4f(dst + i * 2048, acc[4 * i], acc[4 * i + 1], acc[4 * i + 2], acc[4 * i + 3], rbar);
        } else {
            const float4* xb = reinterpret_cast<const float4*>(smem_raw + G2_OFF_X) + tl;
            const int row0 = rb * 128 + cw * 64 + wl * 16 + g;
            const bf16* h0 = g_h + (size_t)row0 * D_ + nb * 128;
            bf16* o0 = out + (size_t)row0 * D_ + nb * 128;
            uint32_t ha[16], hb[16];
#pragma unroll
            for (int j = 0; j < 16; j++) {
                ha[j] = __ldcg(reinterpret_cast<const uint32_t*>(h0 + 8 * j + 2 * t));
                hb[j] = __ldcg(reinterpret_cast<const uint32_t*>(h0 + 8 * D_ + 8 * j + 2 * t));
            }
            mbar_wait_cluster(barX, 0);
            TM(3, 4);
#pragma unroll
            for (int j0 = 0; j0 < 16; j0 += 4) {
                uint32_t P0[4], P1[4];
#pragma unroll
                for (int jj = 0; jj < 4; jj++) {
                    const int j = j0 + jj;
                    const float4 x = xb[j * 128];
                    P0[jj] = pack_bf16(bf_lo(ha[j]) + bf16r(acc[4 * j] + x.x), bf_hi(ha[j]) + bf16r(acc[4 * j + 1] + x.y));
                    P1[jj] = pack_bf16(bf_lo(hb[j]) + bf16r(acc[4 * j + 2] + x.z), bf_hi(hb[j]) + bf16r(acc[4 * j + 3] + x.w));
                }
                quad_transpose(P0[0], P0[1], P0[2], P0[3], t);
                quad_transpose(P1[0], P1[1], P1[2], P1[3], t);
                *reinterpret_cast<uint4*>(o0 + 8 * (j0 + t)) = make_uint4(P0[0], P0[1], P0[2], P0[3]);
                *reinterpret_cast<uint4*>(o0 + 8 * D_ + 8 * (j0 + t)) = make_uint4(P1[0], P1[1], P1[2], P1[3]);
            }
        }
        TM(3, 5);
    }
#undef TMT
}

typedef CUresult (*EncodeFn)(CUtensorMap*, CUtensorMapDataType, cuuint32_t, void*, const cuuint64_t*, const cuuint64_t*,
                             const cuuint32_t*, const cuuint32_t*, CUtensorMapInterleave, CUtensorMapSwizzle,
                             CUtensorMapL2promotion, CUtensorMapFloatOOBfill);

static void enc2d(EncodeFn enc, CUtensorMap* m, const void* p, int rows, int cols, int brows, int bcols) {
    cuuint64_t dims[2] = {(cuuint64_t)cols, (cuuint64_t)rows};
    cuuint64_t strides[1] = {(cuuint64_t)cols * 2};
    cuuint32_t box[2] = {(cuuint32_t)bcols, (cuuint32_t)brows};
    cuuint32_t es[2] = {1, 1};
    enc(m, CU_TENSOR_MAP_DATA_TYPE_BFLOAT16, 2, const_cast<void*>(p), dims, strides, box, es, CU_TENSOR_MAP_INTERLEAVE_NONE,
        bcols == 32 ? CU_TENSOR_MAP_SWIZZLE_64B : CU_TENSOR_MAP_SWIZZLE_128B, CU_TENSOR_MAP_L2_PROMOTION_L2_128B, CU_TENSOR_MAP_FLOAT_OOB_FILL_NONE);
}
static void enc3d(EncodeFn enc, CUtensorMap* m, const void* p, int rows, int cols, int atom, int brows, int natoms) {
    cuuint64_t dims[3] = {(cuuint64_t)atom, (cuuint64_t)rows, (cuuint64_t)(cols / atom)};
    cuuint64_t strides[2] = {(cuuint64_t)cols * 2, (cuuint64_t)atom * 2};
    cuuint32_t box[3] = {(cuuint32_t)atom, (cuuint32_t)brows, (cuuint32_t)natoms};
    cuuint32_t es[3] = {1, 1, 1};
    enc(m, CU_TENSOR_MAP_DATA_TYPE_BFLOAT16, 3, const_cast<void*>(p), dims, strides, box, es, CU_TENSOR_MAP_INTERLEAVE_NONE,
        atom == 32 ? CU_TENSOR_MAP_SWIZZLE_64B : CU_TENSOR_MAP_SWIZZLE_128B, CU_TENSOR_MAP_L2_PROMOTION_L2_128B, CU_TENSOR_MAP_FLOAT_OOB_FILL_NONE);
}

extern "C" void kernel_launch(void* const* d_in, const int* in_sizes, int n_in, void* d_out, int out_size) {
    const bf16* q = (const bf16*)d_in[0];
    const bf16* k = (const bf16*)d_in[1];
    const bf16* v = (const bf16*)d_in[2];
    const bf16* shift_k = (const bf16*)d_in[3];
    const bf16* ssm_k = (const bf16*)d_in[4];
    const bf16* ssm_D = (const bf16*)d_in[5];
    const bf16* wg = (const bf16*)d_in[7];
    const bf16* wu = (const bf16*)d_in[8];
    const bf16* wd = (const bf16*)d_in[9];
    bf16* out = (bf16*)d_out;

    static EncodeFn enc = nullptr;
    static void *p_hn = nullptr, *p_hh = nullptr;
    if (!enc) {
        void* fn = nullptr; cudaDriverEntryPointQueryResult qr;
        cudaGetDriverEntryPoint("cuTensorMapEncodeTiled", &fn, cudaEnableDefault, &qr);
        enc = (EncodeFn)fn;
        cudaGetSymbolAddress(&p_hn, g_hn);
        cudaGetSymbolAddress(&p_hh, g_hh);
        cudaFuncSetAttribute(conv_kernel, cudaFuncAttributeMaxDynamicSharedMemorySize, (int)sizeof(K1Smem));
        cudaFuncSetAttribute(gemm1_kernel, cudaFuncAttributeMaxDynamicSharedMemorySize, G1_SMEM);
        cudaFuncSetAttribute(gemm2_kernel, cudaFuncAttributeMaxDynamicSharedMemorySize, G2_SMEM);
    }
    CUtensorMap mA, mG64, mU64, mG32, mU32, mHH, mWd;
    enc2d(enc, &mA, p_hn, S_, D_, 128, 64);
    enc2d(enc, &mG64, wg, D_, F_, 64, 64);
    enc2d(enc, &mU64, wu, D_, F_, 64, 64);
    enc2d(enc, &mG32, wg, D_, F_, 64, 32);
    enc2d(enc, &mU32, wu, D_, F_, 64, 32);
    enc2d(enc, &mHH, p_hh, S_, F_, 128, 64);
    enc3d(enc, &mWd, wd, F_, D_, 64, 64, 2);

    cudaStream_t st = cudaStreamPerThread;
#define CHK(n)
    conv_kernel<<<128, K1_THREADS, sizeof(K1Smem), st>>>(k, v, shift_k, ssm_k);
    CHK("conv");
    row_kernel<<<S_ / R_ROWS, R_THREADS, 0, st>>>(q, k, v, shift_k, ssm_D);
    CHK("row");
    gemm1_kernel<<<128, G1_THREADS, G1_SMEM, st>>>(mA, mG64, mU64, mG32, mU32);
    CHK("gemm1");
    gemm2_kernel<<<128, G2_THREADS, G2_SMEM, st>>>(mHH, mWd, out);
    CHK("gemm2");
}
```

```cpp
#include <cuda_runtime.h>
#include <cuda_bf16.h>
#include <cuda.h>
#include <stdint.h>

typedef __nv_bfloat16 bf16;
constexpr int S_ = 2048, D_ = 512, F_ = 1792;

__device__ bf16 g_yT[D_ * S_];
__device__ bf16 g_h[S_ * D_];
__device__ bf16 g_hn[S_ * D_];
__device__ bf16 g_hh[S_ * F_];

#define TM(k, i)
#define TR(k, i)
__device__ __forceinline__ uint32_t smem_u32(const void* p) { return (uint32_t)__cvta_generic_to_shared(p); }
__device__ __forceinline__ float bf16r(float x) { return __bfloat162float(__float2bfloat16_rn(x)); }
__device__ __forceinline__ float bf_lo(uint32_t w) { return __uint_as_float(w << 16); }
__device__ __forceinline__ float bf_hi(uint32_t w) { return __uint_as_float(w & 0xffff0000u); }
__device__ __forceinline__ uint32_t pack_bf16(float lo, float hi) {
    __nv_bfloat162 v = __floats2bfloat162_rn(lo, hi);
    return *reinterpret_cast<uint32_t*>(&v);
}
__device__ __forceinline__ uint32_t hmul2(uint32_t a, uint32_t b) {
    __nv_bfloat162 r = __hmul2_rn(*reinterpret_cast<__nv_bfloat162*>(&a), *reinterpret_cast<__nv_bfloat162*>(&b));
    return *reinterpret_cast<uint32_t*>(&r);
}
__device__ __forceinline__ uint32_t hadd2(uint32_t a, uint32_t b) {
    __nv_bfloat162 r = __hadd2_rn(*reinterpret_cast<__nv_bfloat162*>(&a), *reinterpret_cast<__nv_bfloat162*>(&b));
    return *reinterpret_cast<uint32_t*>(&r);
}
__device__ __forceinline__ uint4 ldg128(const void* p) {
    uint4 r; asm volatile("ld.global.nc.v4.u32 {%0,%1,%2,%3}, [%4];" : "=r"(r.x), "=r"(r.y), "=r"(r.z), "=r"(r.w) : "l"(p)); return r;
}
__device__ __forceinline__ uint4 ldcg128(const void* p) {
    uint4 r; asm volatile("ld.global.cg.v4.u32 {%0,%1,%2,%3}, [%4];" : "=r"(r.x), "=r"(r.y), "=r"(r.z), "=r"(r.w) : "l"(p)); return r;
}
__device__ __forceinline__ uint32_t ldg16(const void* p) {
    unsigned short r; asm volatile("ld.global.nc.u16 %0, [%1];" : "=h"(r) : "l"(p)); return (uint32_t)r;
}
__device__ __forceinline__ void mbar_init(uint32_t bar, int cnt) { asm volatile("mbarrier.init.shared::cta.b64 [%0], %1;" :: "r"(bar), "r"(cnt)); }
__device__ __forceinline__ void mbar_expect_tx(uint32_t bar, uint32_t bytes) { asm volatile("mbarrier.arrive.expect_tx.shared::cta.b64 _, [%0], %1;" :: "r"(bar), "r"(bytes) : "memory"); }
__device__ __forceinline__ void mbar_arrive(uint32_t bar) { asm volatile("mbarrier.arrive.shared::cta.b64 _, [%0];" :: "r"(bar) : "memory"); }
__device__ __forceinline__ void mbar_arrive_cluster(uint32_t bar, uint32_t cta) {
    asm volatile("{\n.reg .b32 ra;\nmapa.shared::cluster.u32 ra, %0, %1;\nmbarrier.arrive.shared::cluster.b64 _, [ra];\n}" :: "r"(bar), "r"(cta) : "memory");
}
__device__ __forceinline__ void mbar_wait(uint32_t bar, uint32_t parity) {
    asm volatile("{\n.reg .pred P1;\nLAB_WAIT:\nmbarrier.try_wait.parity.shared::cta.b64 P1, [%0], %1;\n@P1 bra DONE;\nbra LAB_WAIT;\nDONE:\n}" :: "r"(bar), "r"(parity) : "memory");
}
__device__ __forceinline__ void mbar_wait_cluster(uint32_t bar, uint32_t parity) {
    asm volatile("{\n.reg .pred P1;\nLAB_WAIT:\nmbarrier.try_wait.parity.acquire.cluster.shared::cta.b64 P1, [%0], %1;\n@P1 bra DONE;\nbra LAB_WAIT;\nDONE:\n}" :: "r"(bar), "r"(parity) : "memory");
}
__device__ __forceinline__ void tma_load_2d(uint32_t dst, const CUtensorMap* map, uint32_t bar, int c0, int c1) {
    asm volatile("cp.async.bulk.tensor.2d.shared::cluster.global.mbarrier::complete_tx::bytes [%0], [%1, {%3, %4}], [%2];"
        :: "r"(dst), "l"(map), "r"(bar), "r"(c0), "r"(c1) : "memory");
}
__device__ __forceinline__ void tma_load_2d_mc(uint32_t dst, const CUtensorMap* map, uint32_t bar, int c0, int c1, uint16_t mask) {
    asm volatile("cp.async.bulk.tensor.2d.shared::cluster.global.mbarrier::complete_tx::bytes.multicast::cluster [%0], [%1, {%3, %4}], [%2], %5;"
        :: "r"(dst), "l"(map), "r"(bar), "r"(c0), "r"(c1), "h"(mask) : "memory");
}
__device__ __forceinline__ void tma_load_3d(uint32_t dst, const CUtensorMap* map, uint32_t bar, int c0, int c1, int c2) {
    asm volatile("cp.async.bulk.tensor.3d.shared::cluster.global.mbarrier::complete_tx::bytes [%0], [%1, {%3, %4, %5}], [%2];"
        :: "r"(dst), "l"(map), "r"(bar), "r"(c0), "r"(c1), "r"(c2) : "memory");
}
__device__ __forceinline__ void cluster_arrive() { asm volatile("barrier.cluster.arrive.aligned;" ::: "memory"); }
__device__ __forceinline__ void cluster_arrive_relaxed() { asm volatile("barrier.cluster.arrive.relaxed.aligned;" ::: "memory"); }
__device__ __forceinline__ void cluster_wait() { asm volatile("barrier.cluster.wait.aligned;" ::: "memory"); }
__device__ __forceinline__ uint32_t mapa(uint32_t addr, uint32_t cta) {
    uint32_t r; asm volatile("mapa.shared::cluster.u32 %0, %1, %2;" : "=r"(r) : "r"(addr), "r"(cta)); return r;
}
__device__ __forceinline__ void st_async_v2(uint32_t addr, uint32_t a, uint32_t b, uint32_t rbar) {
    asm volatile("st.async.weak.shared::cluster.mbarrier::complete_tx::bytes.v2.b32 [%0], {%1, %2}, [%3];" :: "r"(addr), "r"(a), "r"(b), "r"(rbar) : "memory");
}
__device__ __forceinline__ void st_async_v4f(uint32_t addr, float a, float b, float c, float d, uint32_t rbar) {
    asm volatile("st.async.weak.shared::cluster.mbarrier::complete_tx::bytes.v4.f32 [%0], {%1, %2, %3, %4}, [%5];" :: "r"(addr), "f"(a), "f"(b), "f"(c), "f"(d), "r"(rbar) : "memory");
}
__device__ __forceinline__ void wgmma_fence() { asm volatile("wgmma.fence.sync.aligned;" ::: "memory"); }
__device__ __forceinline__ void wgmma_commit() { asm volatile("wgmma.commit_group.sync.aligned;" ::: "memory"); }
template <int N> __device__ __forceinline__ void wgmma_wait() { asm volatile("wgmma.wait_group.sync.aligned %0;" :: "n"(N) : "memory"); }
__device__ __forceinline__ uint64_t make_desc(uint32_t addr, uint32_t lbo_bytes, uint32_t sbo_bytes, uint32_t layout) {
    return (uint64_t)((addr & 0x3FFFF) >> 4) | ((uint64_t)(lbo_bytes >> 4) << 16) | ((uint64_t)(sbo_bytes >> 4) << 32) | ((uint64_t)layout << 62);
}
template <int R> __device__ __forceinline__ void reg_alloc() { asm volatile("setmaxnreg.inc.sync.aligned.u32 %0;" :: "n"(R)); }
template <int R> __device__ __forceinline__ void reg_dealloc() { asm volatile("setmaxnreg.dec.sync.aligned.u32 %0;" :: "n"(R)); }
__device__ __forceinline__ void named_bar(int id, int n) { asm volatile("bar.sync %0, %1;" :: "r"(id), "r"(n) : "memory"); }

__device__ __forceinline__ void wgmma_m64n128k16_ss(float (&d)[64], uint64_t descA, uint64_t descB, int scaleD) {
    asm volatile("{\n.reg .pred p;\nsetp.ne.b32 p, %66, 0;\n"
        "wgmma.mma_async.sync.aligned.m64n128k16.f32.bf16.bf16 {%0, %1, %2, %3, %4, %5, %6, %7, %8, %9, %10, %11, %12, %13, %14, %15, %16, %17, %18, %19, %20, %21, %22, %23, %24, %25, %26, %27, %28, %29, %30, %31, %32, %33, %34, %35, %36, %37, %38, %39, %40, %41, %42, %43, %44, %45, %46, %47, %48, %49, %50, %51, %52, %53, %54, %55, %56, %57, %58, %59, %60, %61, %62, %63}, %64, %65, p, 1, 1, 0, 1;\n}\n"
        : "+f"(d[0]), "+f"(d[1]), "+f"(d[2]), "+f"(d[3]), "+f"(d[4]), "+f"(d[5]), "+f"(d[6]), "+f"(d[7]), "+f"(d[8]), "+f"(d[9]), "+f"(d[10]), "+f"(d[11]), "+f"(d[12]), "+f"(d[13]), "+f"(d[14]), "+f"(d[15]), "+f"(d[16]), "+f"(d[17]), "+f"(d[18]), "+f"(d[19]), "+f"(d[20]), "+f"(d[21]), "+f"(d[22]), "+f"(d[23]), "+f"(d[24]), "+f"(d[25]), "+f"(d[26]), "+f"(d[27]), "+f"(d[28]), "+f"(d[29]), "+f"(d[30]), "+f"(d[31]), "+f"(d[32]), "+f"(d[33]), "+f"(d[34]), "+f"(d[35]), "+f"(d[36]), "+f"(d[37]), "+f"(d[38]), "+f"(d[39]), "+f"(d[40]), "+f"(d[41]), "+f"(d[42]), "+f"(d[43]), "+f"(d[44]), "+f"(d[45]), "+f"(d[46]), "+f"(d[47]), "+f"(d[48]), "+f"(d[49]), "+f"(d[50]), "+f"(d[51]), "+f"(d[52]), "+f"(d[53]), "+f"(d[54]), "+f"(d[55]), "+f"(d[56]), "+f"(d[57]), "+f"(d[58]), "+f"(d[59]), "+f"(d[60]), "+f"(d[61]), "+f"(d[62]), "+f"(d[63])
        : "l"(descA), "l"(descB), "r"(scaleD));
}

__device__ __forceinline__ void wgmma_m64n64k16_ss(float (&d)[32], uint64_t descA, uint64_t descB, int scaleD) {
    asm volatile("{\n.reg .pred p;\nsetp.ne.b32 p, %34, 0;\n"
        "wgmma.mma_async.sync.aligned.m64n64k16.f32.bf16.bf16 {%0, %1, %2, %3, %4, %5, %6, %7, %8, %9, %10, %11, %12, %13, %14, %15, %16, %17, %18, %19, %20, %21, %22, %23, %24, %25, %26, %27, %28, %29, %30, %31}, %32, %33, p, 1, 1, 0, 1;\n}\n"
        : "+f"(d[0]), "+f"(d[1]), "+f"(d[2]), "+f"(d[3]), "+f"(d[4]), "+f"(d[5]), "+f"(d[6]), "+f"(d[7]), "+f"(d[8]), "+f"(d[9]), "+f"(d[10]), "+f"(d[11]), "+f"(d[12]), "+f"(d[13]), "+f"(d[14]), "+f"(d[15]), "+f"(d[16]), "+f"(d[17]), "+f"(d[18]), "+f"(d[19]), "+f"(d[20]), "+f"(d[21]), "+f"(d[22]), "+f"(d[23]), "+f"(d[24]), "+f"(d[25]), "+f"(d[26]), "+f"(d[27]), "+f"(d[28]), "+f"(d[29]), "+f"(d[30]), "+f"(d[31])
        : "l"(descA), "l"(descB), "r"(scaleD));
}

__device__ __forceinline__ void quad_transpose(uint32_t& r0, uint32_t& r1, uint32_t& r2, uint32_t& r3, int t) {
    const bool o1 = t & 1, o2 = t & 2;
    uint32_t x, y;
    x = o1 ? r0 : r1; y = __shfl_xor_sync(0xffffffffu, x, 1); if (o1) r0 = y; else r1 = y;
    x = o1 ? r2 : r3; y = __shfl_xor_sync(0xffffffffu, x, 1); if (o1) r2 = y; else r3 = y;
    x = o2 ? r0 : r2; y = __shfl_xor_sync(0xffffffffu, x, 2); if (o2) r0 = y; else r2 = y;
    x = o2 ? r1 : r3; y = __shfl_xor_sync(0xffffffffu, x, 2); if (o2) r1 = y; else r3 = y;
}

constexpr int K1_THREADS = 256;
constexpr int UT_PAD = 128;
constexpr int UT_LEN = UT_PAD + S_;
constexpr int KR_LEN = 2080;
constexpr int YP_LEN = S_ + (S_ / 32) * 8;

struct __align__(128) K1Smem {
    bf16 uT[4][UT_LEN];
    bf16 kr[4][2][KR_LEN];
    float yP[4][YP_LEN];
    uint64_t bar;
    uint8_t pad[32768];
};

__device__ __forceinline__ void mma16816(float (&c)[4], uint32_t a0, uint32_t a1, uint32_t a2, uint32_t a3, uint32_t b0, uint32_t b1) {
    asm("mma.sync.aligned.m16n8k16.row.col.f32.bf16.bf16.f32 {%0,%1,%2,%3}, {%4,%5,%6,%7}, {%8,%9}, {%0,%1,%2,%3};"
        : "+f"(c[0]), "+f"(c[1]), "+f"(c[2]), "+f"(c[3])
        : "r"(a0), "r"(a1), "r"(a2), "r"(a3), "r"(b0), "r"(b1));
}
__device__ __forceinline__ void ldsm_x4(uint32_t& r0, uint32_t& r1, uint32_t& r2, uint32_t& r3, uint32_t addr) {
    asm volatile("ldmatrix.sync.aligned.m8n8.x4.shared.b16 {%0,%1,%2,%3}, [%4];" : "=r"(r0), "=r"(r1), "=r"(r2), "=r"(r3) : "r"(addr) : "memory");
}

__device__ __forceinline__ void conv_mma(const bf16* uTc, const bf16* krlane, float (&acc)[16][4], int lane, int half) {
    const int lrow = lane & 7, lk = (lane >> 3) & 1, lt = lane >> 4;
    const uint32_t ubase = smem_u32(uTc) + (UT_PAD + 16 * (8 * lt + lrow) + 8 * lk) * 2;
#pragma unroll 1
    for (int pp = 0; pp < 4; pp++) {
        const int p = half * 4 + pp;
        uint32_t U[16][2];
#pragma unroll
        for (int j = 0; j < 16; j += 2) ldsm_x4(U[j][0], U[j][1], U[j + 1][0], U[j + 1][1], ubase + (j * 128 - p * 16) * 2);
        const uint32_t* kp = reinterpret_cast<const uint32_t*>(krlane - 16 * p);
        const volatile uint32_t* kpv = kp;
        uint32_t a0 = kp[0], a1 = kp[-4], a2 = kp[4], a3 = kpv[0];
#pragma unroll
        for (int q = 0; q < 16; q++) {
            uint32_t b0 = 0, b1 = 0, b2 = 0, b3 = 0;
            if (q < 15) { b0 = kp[-64 * (q + 1)]; b1 = kp[-64 * (q + 1) - 4]; b2 = kp[-64 * (q + 1) + 4]; b3 = kpv[-64 * (q + 1)]; }
#pragma unroll
            for (int n = 15; n >= q; n--) mma16816(acc[n], a0, a1, a2, a3, U[n - q][0], U[n - q][1]);
            a0 = b0; a1 = b1; a2 = b2; a3 = b3;
        }
    }
}

__global__ void __cluster_dims__(2, 1, 1) __launch_bounds__(K1_THREADS, 1)
conv_kernel(const bf16* __restrict__ k, const bf16* __restrict__ v,
            const bf16* __restrict__ shift_k, const bf16* __restrict__ ssm_k) {
    extern __shared__ __align__(1024) uint8_t smem_raw[];
    K1Smem& sm = *reinterpret_cast<K1Smem*>(smem_raw);
    const int tid = threadIdx.x, lane = tid & 31, warp = tid >> 5;
    const int bid = blockIdx.x;
    const int rank = bid & 1;
    const int c0 = 8 * (bid >> 1);
    const int cown = c0 + 4 * rank;
#define TMT 0
    TM(0, 0);
    const uint32_t bar = smem_u32(&sm.bar);
    if (tid == 0) {
        mbar_init(bar, 1);
        asm volatile("fence.mbarrier_init.release.cluster;" ::: "memory");
        mbar_expect_tx(bar, 1024 * 4 * 2);
    }
    cluster_arrive_relaxed();

    const int s0 = 1024 * rank + 4 * tid;
    uint4 kk[7], vv[4], sw[4];
#pragma unroll
    for (int i = 0; i < 4; i++) kk[3 + i] = ldg128(k + (size_t)(s0 + i) * D_ + c0);
#pragma unroll
    for (int i = 0; i < 4; i++) vv[i] = ldg128(v + (size_t)(s0 + i) * D_ + c0);
    if (lane == 0) {
#pragma unroll
        for (int i = 0; i < 3; i++) {
            const int s = s0 - 3 + i;
            kk[i] = make_uint4(0, 0, 0, 0);
            if (s >= 0) kk[i] = ldg128(k + (size_t)s * D_ + c0);
        }
    }
#pragma unroll
    for (int i = 0; i < 4; i++) sw[i] = ldg128(shift_k + (size_t)c0 * 4 + 8 * i);
    uint4 kq[4]; uint32_t nx[4];
#pragma unroll
    for (int c = 0; c < 4; c++) {
        const bf16* kr = ssm_k + (size_t)(cown + c) * S_;
        kq[c] = ldg128(kr + 8 * tid);
        nx[c] = 0u;
        if (tid < 255) nx[c] = ldg16(kr + 8 * tid + 8);
    }
    if (tid < 64) *reinterpret_cast<uint4*>(&sm.uT[tid >> 4][(tid & 15) * 8]) = make_uint4(0, 0, 0, 0);
#pragma unroll
    for (int i = 0; i < 3; i++) {
        uint4 t;
        t.x = __shfl_up_sync(0xffffffffu, kk[4 + i].x, 1); t.y = __shfl_up_sync(0xffffffffu, kk[4 + i].y, 1);
        t.z = __shfl_up_sync(0xffffffffu, kk[4 + i].z, 1); t.w = __shfl_up_sync(0xffffffffu, kk[4 + i].w, 1);
        if (lane != 0) kk[i] = t;
    }
    uint32_t kvw[4][4];
    const uint32_t* kkw = reinterpret_cast<const uint32_t*>(kk);
    const uint32_t* vvw = reinterpret_cast<const uint32_t*>(vv);
#pragma unroll
    for (int i2 = 0; i2 < 4; i2++) {
        const uint32_t t0 = __byte_perm(sw[i2].x, sw[i2].z, 0x5410), t1 = __byte_perm(sw[i2].x, sw[i2].z, 0x7632);
        const uint32_t t2 = __byte_perm(sw[i2].y, sw[i2].w, 0x5410), t3 = __byte_perm(sw[i2].y, sw[i2].w, 0x7632);
#pragma unroll
        for (int r = 0; r < 4; r++) {
            uint32_t a = hmul2(kkw[(r + 0) * 4 + i2], t3);
            a = hadd2(a, hmul2(kkw[(r + 1) * 4 + i2], t2));
            a = hadd2(a, hmul2(kkw[(r + 2) * 4 + i2], t1));
            a = hadd2(a, hmul2(kkw[(r + 3) * 4 + i2], t0));
            kvw[r][i2] = hmul2(a, vvw[r * 4 + i2]);
        }
    }
    TM(0, 1);
    cluster_wait();
    {
        const uint32_t rbar = mapa(bar, (uint32_t)(rank ^ 1));
#pragma unroll
        for (int i2 = 0; i2 < 4; i2++) {
#pragma unroll
            for (int e = 0; e < 2; e++) {
                const uint32_t sel = e ? 0x7632 : 0x5410;
                const uint32_t w0 = __byte_perm(kvw[0][i2], kvw[1][i2], sel), w1 = __byte_perm(kvw[2][i2], kvw[3][i2], sel);
                const int cc = 2 * i2 + e;
                if ((cc >> 2) == rank) {
                    *reinterpret_cast<uint2*>(&sm.uT[cc & 3][UT_PAD + s0]) = make_uint2(w0, w1);
                } else {
                    st_async_v2(mapa(smem_u32(&sm.uT[cc & 3][UT_PAD + s0]), (uint32_t)(rank ^ 1)), w0, w1, rbar);
                }
            }
        }
    }
#pragma unroll
    for (int c = 0; c < 4; c++) {
        uint4 a, b;
        a.x = __byte_perm(kq[c].w, 0, 0x1032); a.y = __byte_perm(kq[c].z, 0, 0x1032);
        a.z = __byte_perm(kq[c].y, 0, 0x1032); a.w = __byte_perm(kq[c].x, 0, 0x1032);
        b.x = __byte_perm(nx[c], kq[c].w, 0x7610); b.y = __byte_perm(kq[c].w, kq[c].z, 0x7610);
        b.z = __byte_perm(kq[c].z, kq[c].y, 0x7610); b.w = __byte_perm(kq[c].y, kq[c].x, 0x7610);
        *reinterpret_cast<uint4*>(&sm.kr[c][0][2040 - 8 * tid]) = a;
        *reinterpret_cast<uint4*>(&sm.kr[c][1][2040 - 8 * tid]) = b;
        if (tid == 0) {
            *reinterpret_cast<uint4*>(&sm.kr[c][1][2048]) = make_uint4(kq[c].x & 0xffffu, 0, 0, 0);
        } else if (tid < 8) {
            if (tid < 4) *reinterpret_cast<uint4*>(&sm.kr[c][1][2048 + 8 * tid]) = make_uint4(0, 0, 0, 0);
            else *reinterpret_cast<uint4*>(&sm.kr[c][0][2048 + 8 * (tid - 4)]) = make_uint4(0, 0, 0, 0);
        }
    }
    TM(0, 3);
    __syncthreads();
    mbar_wait_cluster(bar, 0);
    TM(0, 4);

    const int ch = warp >> 1, half = warp & 1;
    const int g = lane >> 2, t = lane & 3;
    float acc[16][4];
#pragma unroll
    for (int i = 0; i < 16; i++) { acc[i][0] = acc[i][1] = acc[i][2] = acc[i][3] = 0.f; }
    const bf16* krlane = (g & 1) ? &sm.kr[ch][0][2047 - g + 2 * t] : &sm.kr[ch][1][2048 - g + 2 * t];
    conv_mma(sm.uT[ch], krlane, acc, lane, half);
    TM(0, 5);
    float* yp = &sm.yP[ch][40 * t + g];
    if (half) {
#pragma unroll
        for (int n = 0; n < 16; n++) {
            yp[160 * n] = acc[n][0];
            yp[160 * n + 16] = acc[n][1];
            yp[160 * n + 8] = acc[n][2];
            yp[160 * n + 24] = acc[n][3];
        }
    }
    named_bar(1 + ch, 64);
    if (!half) {
#pragma unroll
        for (int n = 0; n < 16; n++) {
            yp[160 * n] += acc[n][0];
            yp[160 * n + 16] += acc[n][1];
            yp[160 * n + 8] += acc[n][2];
            yp[160 * n + 24] += acc[n][3];
        }
    }
    named_bar(1 + ch, 64);
    TM(0, 6);
    {
        const int tt = tid & 63;
        bf16* dst = g_yT + (size_t)(cown + ch) * S_;
#pragma unroll
        for (int j = 0; j < 4; j++) {
            const int s = (j * 64 + tt) * 8;
            const float* src = &sm.yP[ch][s + (s >> 5) * 8];
            const float4 a = *reinterpret_cast<const float4*>(src), b = *reinterpret_cast<const float4*>(src + 4);
            *reinterpret_cast<uint4*>(dst + s) = make_uint4(pack_bf16(a.x, a.y), pack_bf16(a.z, a.w), pack_bf16(b.x, b.y), pack_bf16(b.z, b.w));
        }
    }
    TM(0, 7);
#undef TMT
}

constexpr int R_THREADS = 512;
constexpr int R_ROWS = 16;

__device__ __forceinline__ float warp_sum(float s) {
#pragma unroll
    for (int o = 16; o > 0; o >>= 1) s += __shfl_xor_sync(0xffffffffu, s, o);
    return s;
}
__device__ __forceinline__ uint32_t hsub2(uint32_t a, uint32_t b) {
    __nv_bfloat162 r = __hsub2_rn(*reinterpret_cast<__nv_bfloat162*>(&a), *reinterpret_cast<__nv_bfloat162*>(&b));
    return *reinterpret_cast<uint32_t*>(&r);
}
__device__ __forceinline__ void ln_row(const uint32_t (&x)[8], uint32_t (&o)[8]) {
    float s0 = 0.f, s1 = 0.f;
#pragma unroll
    for (int i = 0; i < 8; i++) { s0 += bf_lo(x[i]); s1 += bf_hi(x[i]); }
    const float mean = warp_sum(s0 + s1) * (1.0f / D_);
    float ss0 = 0.f, ss1 = 0.f;
#pragma unroll
    for (int i = 0; i < 8; i++) { const float d0 = bf_lo(x[i]) - mean, d1 = bf_hi(x[i]) - mean; ss0 += d0 * d0; ss1 += d1 * d1; }
    const float var = bf16r(warp_sum(ss0 + ss1) * (1.0f / D_));
    const float rinv = 1.0f / bf16r(sqrtf(bf16r(var + 1e-5f)));
    const uint32_t m2 = pack_bf16(mean, mean);
#pragma unroll
    for (int i = 0; i < 8; i++) {
        const uint32_t d = hsub2(x[i], m2);
        o[i] = pack_bf16(bf_lo(d) * rinv, bf_hi(d) * rinv);
    }
}

__global__ void __launch_bounds__(R_THREADS, 1)
row_kernel(const bf16* __restrict__ q, const bf16* __restrict__ k, const bf16* __restrict__ v,
           const bf16* __restrict__ shift_k, const bf16* __restrict__ ssm_D) {
    __shared__ __align__(16) uint32_t ys[R_ROWS][D_ / 2 + 4];
    const int tid = threadIdx.x, lane = tid & 31, warp = tid >> 5;
    const int s0 = blockIdx.x * R_ROWS;
#define TMT 0
    TM(1, 0);
    const int r0 = s0 + warp;
    const int p = tid & 255, hs = tid >> 8;
    uint4 qq[2], vv[2], kk[4][2], sw[2][4], dd[2];
#pragma unroll
    for (int i = 0; i < 2; i++) {
        const int cb = 8 * (lane + 32 * i);
        qq[i] = ldg128(q + (size_t)r0 * D_ + cb);
        vv[i] = ldg128(v + (size_t)r0 * D_ + cb);
#pragma unroll
        for (int r = 0; r < 4; r++) {
            const int s = r0 - 3 + r;
            kk[r][i] = make_uint4(0, 0, 0, 0);
            if (s >= 0) kk[r][i] = ldg128(k + (size_t)s * D_ + cb);
        }
#pragma unroll
        for (int j = 0; j < 4; j++) sw[i][j] = ldg128(shift_k + (size_t)cb * 4 + 8 * j);
        dd[i] = ldg128(ssm_D + cb);
    }
    const bf16* y0 = g_yT + (size_t)(2 * p) * S_ + s0 + 8 * hs;
    const uint4 ya = ldcg128(y0);
    const uint4 yb = ldcg128(y0 + S_);
    uint32_t x[8], kvd[8], qn[8];
#pragma unroll
    for (int i = 0; i < 2; i++) {
        const uint32_t* qw = reinterpret_cast<const uint32_t*>(&qq[i]);
        const uint32_t* vw = reinterpret_cast<const uint32_t*>(&vv[i]);
        const uint32_t* dw = reinterpret_cast<const uint32_t*>(&dd[i]);
#pragma unroll
        for (int j = 0; j < 4; j++) {
            const uint4 w = sw[i][j];
            const uint32_t t0 = __byte_perm(w.x, w.z, 0x5410), t1 = __byte_perm(w.x, w.z, 0x7632);
            const uint32_t t2 = __byte_perm(w.y, w.w, 0x5410), t3 = __byte_perm(w.y, w.w, 0x7632);
            uint32_t a = hmul2(reinterpret_cast<const uint32_t*>(&kk[0][i])[j], t3);
            a = hadd2(a, hmul2(reinterpret_cast<const uint32_t*>(&kk[1][i])[j], t2));
            a = hadd2(a, hmul2(reinterpret_cast<const uint32_t*>(&kk[2][i])[j], t1));
            a = hadd2(a, hmul2(reinterpret_cast<const uint32_t*>(&kk[3][i])[j], t0));
            kvd[4 * i + j] = hmul2(hmul2(a, vw[j]), dw[j]);
            x[4 * i + j] = qw[j];
        }
    }
    ln_row(x, qn);
    {
        const uint32_t aw[4] = {ya.x, ya.y, ya.z, ya.w};
        const uint32_t bw[4] = {yb.x, yb.y, yb.z, yb.w};
#pragma unroll
        for (int j = 0; j < 4; j++) {
            ys[8 * hs + 2 * j][p] = __byte_perm(aw[j], bw[j], 0x5410);
            ys[8 * hs + 2 * j + 1][p] = __byte_perm(aw[j], bw[j], 0x7632);
        }
    }
    __syncthreads();
    TM(1, 1);
    uint32_t h[8], hn[8];
#pragma unroll
    for (int i = 0; i < 2; i++) {
        const uint4 yw4 = *reinterpret_cast<const uint4*>(&ys[warp][4 * (lane + 32 * i)]);
        const uint32_t yw[4] = {yw4.x, yw4.y, yw4.z, yw4.w};
#pragma unroll
        for (int j = 0; j < 4; j++) h[4 * i + j] = hadd2(x[4 * i + j], hmul2(qn[4 * i + j], hadd2(yw[j], kvd[4 * i + j])));
    }
    ln_row(h, hn);
#pragma unroll
    for (int i = 0; i < 2; i++) {
        const size_t off = (size_t)r0 * D_ + 8 * (lane + 32 * i);
        *reinterpret_cast<uint4*>(g_h + off) = make_uint4(h[4 * i], h[4 * i + 1], h[4 * i + 2], h[4 * i + 3]);
        *reinterpret_cast<uint4*>(g_hn + off) = make_uint4(hn[4 * i], hn[4 * i + 1], hn[4 * i + 2], hn[4 * i + 3]);
    }
    TM(1, 2);
#undef TMT
}

constexpr int G1_THREADS = 384;
constexpr int G1_STAGES = 6;
constexpr int G1_A_BYTES = 8 * 16384;
constexpr int G1_B_STAGE = 16384;
constexpr int G1_OFF_B = G1_A_BYTES;
constexpr int G1_OFF_BAR = G1_OFF_B + G1_STAGES * G1_B_STAGE;
constexpr int G1_SMEM = G1_OFF_BAR + 256;

__device__ __forceinline__ float sigmoid_fast(float x) {
    float t; asm("tanh.approx.f32 %0, %1;" : "=f"(t) : "f"(0.5f * x));
    return fmaf(t, 0.5f, 0.5f);
}

template <int NT>
__device__ __forceinline__ void g1_epilogue(const float (&acc)[NT * 8], bf16* out0, int t) {
#pragma unroll
    for (int j0 = 0; j0 < NT; j0 += 4) {
        uint32_t P0[4], P1[4];
#pragma unroll
        for (int jj = 0; jj < 4; jj++) {
            const int j = j0 + jj;
            float r[4];
#pragma unroll
            for (int e = 0; e < 4; e++) r[e] = sigmoid_fast(acc[4 * j + e]) * acc[4 * (NT + j) + e];
            P0[jj] = pack_bf16(r[0], r[1]);
            P1[jj] = pack_bf16(r[2], r[3]);
        }
        quad_transpose(P0[0], P0[1], P0[2], P0[3], t);
        quad_transpose(P1[0], P1[1], P1[2], P1[3], t);
        *reinterpret_cast<uint4*>(out0 + 8 * (j0 + t)) = make_uint4(P0[0], P0[1], P0[2], P0[3]);
        *reinterpret_cast<uint4*>(out0 + 8 * F_ + 8 * (j0 + t)) = make_uint4(P1[0], P1[1], P1[2], P1[3]);
    }
}

__host__ __device__ constexpr int g1_parity(int it) {
    int cnt = 0;
    for (int j = 0; j < it; j++) if ((((j >> 3) ^ (it >> 3)) & 1) == 0 && (j % G1_STAGES) == (it % G1_STAGES)) cnt++;
    return cnt & 1;
}
template <int NT, int U>
__device__ __forceinline__ void g1_unit(uint32_t sb, uint32_t barA, uint32_t barF, uint32_t barE, uint32_t peer, int tl, bf16* outp, int t) {
    float acc[2][NT * 8];
#pragma unroll
    for (int kc = 0; kc < 8; kc++) {
        const int it = 8 * U + kc;
        const int st = it % G1_STAGES, ph = g1_parity(it);
        if (U < 2) mbar_wait(barA + 8 * kc, 0);
        mbar_wait(barF + 8 * st, ph);
        if (tl == 0) TR(1, it);
        wgmma_fence();
        const uint32_t aaddr = sb + kc * 16384;
        const uint32_t baddr = sb + G1_OFF_B + st * G1_B_STAGE;
#pragma unroll
        for (int kk = 0; kk < 4; kk++) {
#pragma unroll
            for (int hf = 0; hf < 2; hf++) {
                if constexpr (NT == 8)
                    wgmma_m64n128k16_ss(acc[hf], make_desc(aaddr + hf * 8192 + kk * 32, 16, 1024, 1), make_desc(baddr + kk * 2048, 8192, 1024, 1), (kc | kk) != 0);
                else
                    wgmma_m64n64k16_ss(acc[hf], make_desc(aaddr + hf * 8192 + kk * 32, 16, 1024, 1), make_desc(baddr + kk * 1024, 4096, 512, 2), (kc | kk) != 0);
            }
        }
        wgmma_commit();
        if (kc > 0) {
            wgmma_wait<1>();
            const int pst = (it - 1) % G1_STAGES;
            if (tl == 0) mbar_arrive(barE + 8 * pst);
        }
    }
    wgmma_wait<0>();
    {
        const int pst = (8 * U + 7) % G1_STAGES;
        if (tl == 0) mbar_arrive(barE + 8 * pst);
    }
    if (tl == 0) TR(2, U);
    g1_epilogue<NT>(acc[0], outp + 64 * U, t);
    g1_epilogue<NT>(acc[1], outp + 64 * U + (size_t)64 * F_, t);
    if (tl == 0) TR(2, 4 + U);
}

__global__ void __cluster_dims__(2, 1, 1) __launch_bounds__(G1_THREADS, 1)
gemm1_kernel(const __grid_constant__ CUtensorMap mapA, const __grid_constant__ CUtensorMap mapG64, const __grid_constant__ CUtensorMap mapU64,
             const __grid_constant__ CUtensorMap mapG32, const __grid_constant__ CUtensorMap mapU32) {
    extern __shared__ __align__(1024) uint8_t smem_raw[];
    const uint32_t sb = smem_u32(smem_raw);
    const int tid = threadIdx.x, lane = tid & 31, warp = tid >> 5, wgi = tid >> 7;
    const int rank = blockIdx.x & 1;
    const int cb = blockIdx.x & 7, rb = blockIdx.x >> 3;
#define TMT 128
    TM(2, 0);
    const uint32_t barA = sb + G1_OFF_BAR;
    const uint32_t barF = barA + 64;
    const uint32_t barE = barF + 16 * G1_STAGES;
    if (tid == 0) {
        for (int i = 0; i < 8; i++) mbar_init(barA + 8 * i, 1);
        for (int i = 0; i < G1_STAGES; i++) { mbar_init(barF + 8 * i, 1); mbar_init(barF + 8 * G1_STAGES + 8 * i, 1); mbar_init(barE + 8 * i, 1); }
        for (int i = 0; i < 8; i++) mbar_expect_tx(barA + 8 * i, 16384);
        asm volatile("fence.mbarrier_init.release.cluster;" ::: "memory");
    }
    __syncthreads();
    cluster_arrive_relaxed();
    cluster_wait();

    if (wgi == 0) {
        reg_dealloc<40>();
        if (tid == 0) {
            int st = 0, ph = 1;
            for (int it = 0; it < 32; it++) {
                const int kc = it & 7, u = it >> 3;
                if (it < 4) {
                    const int c = 2 * it + rank;
                    tma_load_2d_mc(sb + c * 16384, &mapA, barA + 8 * c, c * 64, rb * 128, (uint16_t)3);
                }
                mbar_wait(barE + 8 * st, ph);
                TR(0, it);
                const uint32_t dst = sb + G1_OFF_B + st * G1_B_STAGE;
                const uint32_t bf = barF + (u & 1) * 8 * G1_STAGES + 8 * st;
                if (u < 3) {
                    mbar_expect_tx(bf, 16384);
                    tma_load_2d(dst, &mapG64, bf, cb * 224 + 64 * u, kc * 64);
                    tma_load_2d(dst + 8192, &mapU64, bf, cb * 224 + 64 * u, kc * 64);
                } else {
                    mbar_expect_tx(bf, 8192);
                    tma_load_2d(dst, &mapG32, bf, cb * 224 + 192, kc * 64);
                    tma_load_2d(dst + 4096, &mapU32, bf, cb * 224 + 192, kc * 64);
                }
                if (++st == G1_STAGES) { st = 0; ph ^= 1; }
            }
        }
        __syncwarp();
    } else {
        reg_alloc<232>();
        const int g = lane >> 2, t = lane & 3, wl = warp & 3, tl = tid & 127;
        bf16* outp = g_hh + (size_t)(rb * 128 + wl * 16 + g) * F_ + cb * 224;
        const uint32_t peer = (uint32_t)(rank ^ 1);
        if (wgi == 1) {
            g1_unit<8, 0>(sb, barA, barF, barE, peer, tl, outp, t);
            TM(2, 1);
            g1_unit<8, 2>(sb, barA, barF, barE, peer, tl, outp, t);
            TM(2, 2);
        } else {
            g1_unit<8, 1>(sb, barA, barF + 8 * G1_STAGES, barE, peer, tl, outp, t);
            g1_unit<4, 3>(sb, barA, barF + 8 * G1_STAGES, barE, peer, tl, outp, t);
        }
    }
    cluster_arrive_relaxed();
    cluster_wait();
    TM(2, 3);
}

constexpr int G2_THREADS = 384;
constexpr int G2_STAGES = 6;
constexpr int G2_STAGE = 32768;
constexpr int G2_OFF_X = G2_STAGES * G2_STAGE;
constexpr int G2_OFF_BAR = G2_OFF_X + 32768;
constexpr int G2_SMEM = G2_OFF_BAR + 128;
constexpr int G2_KSTEPS = 14;

__global__ void __cluster_dims__(2, 1, 1) __launch_bounds__(G2_THREADS, 1)
gemm2_kernel(const __grid_constant__ CUtensorMap mapHH, const __grid_constant__ CUtensorMap mapWd, bf16* __restrict__ out) {
    extern __shared__ __align__(1024) uint8_t smem_raw[];
    const uint32_t sb = smem_u32(smem_raw);
    const int tid = threadIdx.x, lane = tid & 31, warp = tid >> 5, wgi = tid >> 7;
    const int ks = blockIdx.x & 1, nb = (blockIdx.x >> 1) & 3, rb = blockIdx.x >> 3;
    TM(3, 0);
    const uint32_t barF = sb + G2_OFF_BAR;
    const uint32_t barE = barF + 8 * G2_STAGES;
    const uint32_t barX = barE + 8 * G2_STAGES;
    if (tid == 0) {
        for (int i = 0; i < G2_STAGES; i++) { mbar_init(barF + 8 * i, 1); mbar_init(barE + 8 * i, 2); }
        mbar_init(barX, 1);
        asm volatile("fence.mbarrier_init.release.cluster;" ::: "memory");
        mbar_expect_tx(barX, 32768);
    }
    __syncthreads();
    cluster_arrive_relaxed();

    if (wgi == 0) {
        if (tid == 0) {
            int st = 0, ph = 1;
            for (int it = 0; it < G2_KSTEPS; it++) {
                mbar_wait(barE + 8 * st, ph);
                const uint32_t dst = sb + st * G2_STAGE;
                const int k0 = ks * 896 + it * 64;
                mbar_expect_tx(barF + 8 * st, 32768);
                tma_load_2d(dst, &mapHH, barF + 8 * st, k0, rb * 128);
                tma_load_3d(dst + 16384, &mapWd, barF + 8 * st, 0, k0, nb * 2);
                if (++st == G2_STAGES) { st = 0; ph ^= 1; }
            }
        }
        __syncwarp();
        cluster_wait();
    } else {
        const int cw = wgi - 1;
        const int g = lane >> 2, t = lane & 3, wl = warp & 3;
        const int tl = tid & 127;
        int st = 0, ph = 0;
        float acc[64];
#pragma unroll 1
        for (int it = 0; it < G2_KSTEPS; it++) {
            mbar_wait(barF + 8 * st, ph);
            if (it == 0) TM(3, 1);
            wgmma_fence();
            const uint32_t aaddr = sb + st * G2_STAGE + cw * 8192;
            const uint32_t baddr = sb + st * G2_STAGE + 16384;
#pragma unroll
            for (int kk = 0; kk < 4; kk++)
                wgmma_m64n128k16_ss(acc, make_desc(aaddr + kk * 32, 16, 1024, 1), make_desc(baddr + kk * 2048, 8192, 1024, 1), (it | kk) != 0);
            wgmma_commit();
            wgmma_wait<0>();
            if (tl == 0) mbar_arrive(barE + 8 * st);
            if (++st == G2_STAGES) { st = 0; ph ^= 1; }
        }
        TM(3, 2);
        cluster_wait();
        if (cw != ks) {
            const uint32_t dst = mapa(sb + G2_OFF_X + tl * 16, (uint32_t)(ks ^ 1));
            const uint32_t rbar = mapa(barX, (uint32_t)(ks ^ 1));
#pragma unroll
            for (int i = 0; i < 16; i++) st_async_v4f(dst + i * 2048, acc[4 * i], acc[4 * i + 1], acc[4 * i + 2], acc[4 * i + 3], rbar);
        } else {
            const float4* xb = reinterpret_cast<const float4*>(smem_raw + G2_OFF_X) + tl;
            const int row0 = rb * 128 + cw * 64 + wl * 16 + g;
            const bf16* h0 = g_h + (size_t)row0 * D_ + nb * 128;
            bf16* o0 = out + (size_t)row0 * D_ + nb * 128;
            uint32_t ha[16], hb[16];
#pragma unroll
            for (int j = 0; j < 16; j++) {
                ha[j] = __ldcg(reinterpret_cast<const uint32_t*>(h0 + 8 * j + 2 * t));
                hb[j] = __ldcg(reinterpret_cast<const uint32_t*>(h0 + 8 * D_ + 8 * j + 2 * t));
            }
            mbar_wait_cluster(barX, 0);
            TM(3, 4);
#pragma unroll
            for (int j0 = 0; j0 < 16; j0 += 4) {
                uint32_t P0[4], P1[4];
#pragma unroll
                for (int jj = 0; jj < 4; jj++) {
                    const int j = j0 + jj;
                    const float4 x = xb[j * 128];
                    P0[jj] = pack_bf16(bf_lo(ha[j]) + bf16r(acc[4 * j] + x.x), bf_hi(ha[j]) + bf16r(acc[4 * j + 1] + x.y));
                    P1[jj] = pack_bf16(bf_lo(hb[j]) + bf16r(acc[4 * j + 2] + x.z), bf_hi(hb[j]) + bf16r(acc[4 * j + 3] + x.w));
                }
                quad_transpose(P0[0], P0[1], P0[2], P0[3], t);
                quad_transpose(P1[0], P1[1], P1[2], P1[3], t);
                *reinterpret_cast<uint4*>(o0 + 8 * (j0 + t)) = make_uint4(P0[0], P0[1], P0[2], P0[3]);
                *reinterpret_cast<uint4*>(o0 + 8 * D_ + 8 * (j0 + t)) = make_uint4(P1[0], P1[1], P1[2], P1[3]);
            }
        }
        TM(3, 5);
    }
#undef TMT
}

typedef CUresult (*EncodeFn)(CUtensorMap*, CUtensorMapDataType, cuuint32_t, void*, const cuuint64_t*, const cuuint64_t*,
                             const cuuint32_t*, const cuuint32_t*, CUtensorMapInterleave, CUtensorMapSwizzle,
                             CUtensorMapL2promotion, CUtensorMapFloatOOBfill);

static void enc2d(EncodeFn enc, CUtensorMap* m, const void* p, int rows, int cols, int brows, int bcols) {
    cuuint64_t dims[2] = {(cuuint64_t)cols, (cuuint64_t)rows};
    cuuint64_t strides[1] = {(cuuint64_t)cols * 2};
    cuuint32_t box[2] = {(cuuint32_t)bcols, (cuuint32_t)brows};
    cuuint32_t es[2] = {1, 1};
    enc(m, CU_TENSOR_MAP_DATA_TYPE_BFLOAT16, 2, const_cast<void*>(p), dims, strides, box, es, CU_TENSOR_MAP_INTERLEAVE_NONE,
        bcols == 32 ? CU_TENSOR_MAP_SWIZZLE_64B : CU_TENSOR_MAP_SWIZZLE_128B, CU_TENSOR_MAP_L2_PROMOTION_L2_128B, CU_TENSOR_MAP_FLOAT_OOB_FILL_NONE);
}
static void enc3d(EncodeFn enc, CUtensorMap* m, const void* p, int rows, int cols, int atom, int brows, int natoms) {
    cuuint64_t dims[3] = {(cuuint64_t)atom, (cuuint64_t)rows, (cuuint64_t)(cols / atom)};
    cuuint64_t strides[2] = {(cuuint64_t)cols * 2, (cuuint64_t)atom * 2};
    cuuint32_t box[3] = {(cuuint32_t)atom, (cuuint32_t)brows, (cuuint32_t)natoms};
    cuuint32_t es[3] = {1, 1, 1};
    enc(m, CU_TENSOR_MAP_DATA_TYPE_BFLOAT16, 3, const_cast<void*>(p), dims, strides, box, es, CU_TENSOR_MAP_INTERLEAVE_NONE,
        atom == 32 ? CU_TENSOR_MAP_SWIZZLE_64B : CU_TENSOR_MAP_SWIZZLE_128B, CU_TENSOR_MAP_L2_PROMOTION_L2_128B, CU_TENSOR_MAP_FLOAT_OOB_FILL_NONE);
}

extern "C" void kernel_launch(void* const* d_in, const int* in_sizes, int n_in, void* d_out, int out_size) {
    const bf16* q = (const bf16*)d_in[0];
    const bf16* k = (const bf16*)d_in[1];
    const bf16* v = (const bf16*)d_in[2];
    const bf16* shift_k = (const bf16*)d_in[3];
    const bf16* ssm_k = (const bf16*)d_in[4];
    const bf16* ssm_D = (const bf16*)d_in[5];
    const bf16* wg = (const bf16*)d_in[7];
    const bf16* wu = (const bf16*)d_in[8];
    const bf16* wd = (const bf16*)d_in[9];
    bf16* out = (bf16*)d_out;

    static EncodeFn enc = nullptr;
    static void *p_hn = nullptr, *p_hh = nullptr;
    if (!enc) {
        void* fn = nullptr; cudaDriverEntryPointQueryResult qr;
        cudaGetDriverEntryPoint("cuTensorMapEncodeTiled", &fn, cudaEnableDefault, &qr);
        enc = (EncodeFn)fn;
        cudaGetSymbolAddress(&p_hn, g_hn);
        cudaGetSymbolAddress(&p_hh, g_hh);
        cudaFuncSetAttribute(conv_kernel, cudaFuncAttributeMaxDynamicSharedMemorySize, (int)sizeof(K1Smem));
        cudaFuncSetAttribute(gemm1_kernel, cudaFuncAttributeMaxDynamicSharedMemorySize, G1_SMEM);
        cudaFuncSetAttribute(gemm2_kernel, cudaFuncAttributeMaxDynamicSharedMemorySize, G2_SMEM);
    }
    CUtensorMap mA, mG64, mU64, mG32, mU32, mHH, mWd;
    enc2d(enc, &mA, p_hn, S_, D_, 128, 64);
    enc2d(enc, &mG64, wg, D_, F_, 64, 64);
    enc2d(enc, &mU64, wu, D_, F_, 64, 64);
    enc2d(enc, &mG32, wg, D_, F_, 64, 32);
    enc2d(enc, &mU32, wu, D_, F_, 64, 32);
    enc2d(enc, &mHH, p_hh, S_, F_, 128, 64);
    enc3d(enc, &mWd, wd, F_, D_, 64, 64, 2);

    cudaStream_t st = cudaStreamPerThread;
#define CHK(n)
    conv_kernel<<<128, K1_THREADS, sizeof(K1Smem), st>>>(k, v, shift_k, ssm_k);
    CHK("conv");
    row_kernel<<<S_ / R_ROWS, R_THREADS, 0, st>>>(q, k, v, shift_k, ssm_D);
    CHK("row");
    gemm1_kernel<<<128, G1_THREADS, G1_SMEM, st>>>(mA, mG64, mU64, mG32, mU32);
    CHK("gemm1");
    gemm2_kernel<<<128, G2_THREADS, G2_SMEM, st>>>(mHH, mWd, out);
    CHK("gemm2");
}
```

```cpp
#include <cuda_runtime.h>
#include <cuda_bf16.h>
#include <cuda.h>
#include <stdint.h>

typedef __nv_bfloat16 bf16;
constexpr int S_ = 2048, D_ = 512, F_ = 1792;

__device__ bf16 g_yT[D_ * S_];
__device__ bf16 g_h[S_ * D_];
__device__ bf16 g_hn[S_ * D_];
__device__ bf16 g_hh[S_ * F_];

#define TM(k, i)
#define TR(k, i)
__device__ __forceinline__ uint32_t smem_u32(const void* p) { return (uint32_t)__cvta_generic_to_shared(p); }
__device__ __forceinline__ float bf16r(float x) { return __bfloat162float(__float2bfloat16_rn(x)); }
__device__ __forceinline__ float bf_lo(uint32_t w) { return __uint_as_float(w << 16); }
__device__ __forceinline__ float bf_hi(uint32_t w) { return __uint_as_float(w & 0xffff0000u); }
__device__ __forceinline__ uint32_t pack_bf16(float lo, float hi) {
    __nv_bfloat162 v = __floats2bfloat162_rn(lo, hi);
    return *reinterpret_cast<uint32_t*>(&v);
}
__device__ __forceinline__ uint32_t hmul2(uint32_t a, uint32_t b) {
    __nv_bfloat162 r = __hmul2_rn(*reinterpret_cast<__nv_bfloat162*>(&a), *reinterpret_cast<__nv_bfloat162*>(&b));
    return *reinterpret_cast<uint32_t*>(&r);
}
__device__ __forceinline__ uint32_t hadd2(uint32_t a, uint32_t b) {
    __nv_bfloat162 r = __hadd2_rn(*reinterpret_cast<__nv_bfloat162*>(&a), *reinterpret_cast<__nv_bfloat162*>(&b));
    return *reinterpret_cast<uint32_t*>(&r);
}
__device__ __forceinline__ uint4 ldg128(const void* p) {
    uint4 r; asm volatile("ld.global.nc.v4.u32 {%0,%1,%2,%3}, [%4];" : "=r"(r.x), "=r"(r.y), "=r"(r.z), "=r"(r.w) : "l"(p)); return r;
}
__device__ __forceinline__ uint4 ldcg128(const void* p) {
    uint4 r; asm volatile("ld.global.cg.v4.u32 {%0,%1,%2,%3}, [%4];" : "=r"(r.x), "=r"(r.y), "=r"(r.z), "=r"(r.w) : "l"(p)); return r;
}
__device__ __forceinline__ uint32_t ldg16(const void* p) {
    unsigned short r; asm volatile("ld.global.nc.u16 %0, [%1];" : "=h"(r) : "l"(p)); return (uint32_t)r;
}
__device__ __forceinline__ void mbar_init(uint32_t bar, int cnt) { asm volatile("mbarrier.init.shared::cta.b64 [%0], %1;" :: "r"(bar), "r"(cnt)); }
__device__ __forceinline__ void mbar_expect_tx(uint32_t bar, uint32_t bytes) { asm volatile("mbarrier.arrive.expect_tx.shared::cta.b64 _, [%0], %1;" :: "r"(bar), "r"(bytes) : "memory"); }
__device__ __forceinline__ void mbar_arrive(uint32_t bar) { asm volatile("mbarrier.arrive.shared::cta.b64 _, [%0];" :: "r"(bar) : "memory"); }
__device__ __forceinline__ void mbar_arrive_cluster(uint32_t bar, uint32_t cta) {
    asm volatile("{\n.reg .b32 ra;\nmapa.shared::cluster.u32 ra, %0, %1;\nmbarrier.arrive.shared::cluster.b64 _, [ra];\n}" :: "r"(bar), "r"(cta) : "memory");
}
__device__ __forceinline__ void mbar_wait(uint32_t bar, uint32_t parity) {
    asm volatile("{\n.reg .pred P1;\nLAB_WAIT:\nmbarrier.try_wait.parity.shared::cta.b64 P1, [%0], %1;\n@P1 bra DONE;\nbra LAB_WAIT;\nDONE:\n}" :: "r"(bar), "r"(parity) : "memory");
}
__device__ __forceinline__ void mbar_wait_cluster(uint32_t bar, uint32_t parity) {
    asm volatile("{\n.reg .pred P1;\nLAB_WAIT:\nmbarrier.try_wait.parity.acquire.cluster.shared::cta.b64 P1, [%0], %1;\n@P1 bra DONE;\nbra LAB_WAIT;\nDONE:\n}" :: "r"(bar), "r"(parity) : "memory");
}
__device__ __forceinline__ void tma_load_2d(uint32_t dst, const CUtensorMap* map, uint32_t bar, int c0, int c1) {
    asm volatile("cp.async.bulk.tensor.2d.shared::cluster.global.mbarrier::complete_tx::bytes [%0], [%1, {%3, %4}], [%2];"
        :: "r"(dst), "l"(map), "r"(bar), "r"(c0), "r"(c1) : "memory");
}
__device__ __forceinline__ void tma_load_2d_mc(uint32_t dst, const CUtensorMap* map, uint32_t bar, int c0, int c1, uint16_t mask) {
    asm volatile("cp.async.bulk.tensor.2d.shared::cluster.global.mbarrier::complete_tx::bytes.multicast::cluster [%0], [%1, {%3, %4}], [%2], %5;"
        :: "r"(dst), "l"(map), "r"(bar), "r"(c0), "r"(c1), "h"(mask) : "memory");
}
__device__ __forceinline__ void tma_load_3d(uint32_t dst, const CUtensorMap* map, uint32_t bar, int c0, int c1, int c2) {
    asm volatile("cp.async.bulk.tensor.3d.shared::cluster.global.mbarrier::complete_tx::bytes [%0], [%1, {%3, %4, %5}], [%2];"
        :: "r"(dst), "l"(map), "r"(bar), "r"(c0), "r"(c1), "r"(c2) : "memory");
}
__device__ __forceinline__ void cluster_arrive() { asm volatile("barrier.cluster.arrive.aligned;" ::: "memory"); }
__device__ __forceinline__ void cluster_arrive_relaxed() { asm volatile("barrier.cluster.arrive.relaxed.aligned;" ::: "memory"); }
__device__ __forceinline__ void cluster_wait() { asm volatile("barrier.cluster.wait.aligned;" ::: "memory"); }
__device__ __forceinline__ uint32_t mapa(uint32_t addr, uint32_t cta) {
    uint32_t r; asm volatile("mapa.shared::cluster.u32 %0, %1, %2;" : "=r"(r) : "r"(addr), "r"(cta)); return r;
}
__device__ __forceinline__ void st_async_v2(uint32_t addr, uint32_t a, uint32_t b, uint32_t rbar) {
    asm volatile("st.async.weak.shared::cluster.mbarrier::complete_tx::bytes.v2.b32 [%0], {%1, %2}, [%3];" :: "r"(addr), "r"(a), "r"(b), "r"(rbar) : "memory");
}
__device__ __forceinline__ void st_async_v4f(uint32_t addr, float a, float b, float c, float d, uint32_t rbar) {
    asm volatile("st.async.weak.shared::cluster.mbarrier::complete_tx::bytes.v4.f32 [%0], {%1, %2, %3, %4}, [%5];" :: "r"(addr), "f"(a), "f"(b), "f"(c), "f"(d), "r"(rbar) : "memory");
}
__device__ __forceinline__ void wgmma_fence() { asm volatile("wgmma.fence.sync.aligned;" ::: "memory"); }
__device__ __forceinline__ void wgmma_commit() { asm volatile("wgmma.commit_group.sync.aligned;" ::: "memory"); }
template <int N> __device__ __forceinline__ void wgmma_wait() { asm volatile("wgmma.wait_group.sync.aligned %0;" :: "n"(N) : "memory"); }
__device__ __forceinline__ uint64_t make_desc(uint32_t addr, uint32_t lbo_bytes, uint32_t sbo_bytes, uint32_t layout) {
    return (uint64_t)((addr & 0x3FFFF) >> 4) | ((uint64_t)(lbo_bytes >> 4) << 16) | ((uint64_t)(sbo_bytes >> 4) << 32) | ((uint64_t)layout << 62);
}
template <int R> __device__ __forceinline__ void reg_alloc() { asm volatile("setmaxnreg.inc.sync.aligned.u32 %0;" :: "n"(R)); }
template <int R> __device__ __forceinline__ void reg_dealloc() { asm volatile("setmaxnreg.dec.sync.aligned.u32 %0;" :: "n"(R)); }
__device__ __forceinline__ void pdl_launch() { asm volatile("griddepcontrol.launch_dependents;" ::: "memory"); }
__device__ __forceinline__ void pdl_wait() { asm volatile("griddepcontrol.wait;" ::: "memory"); }
__device__ __forceinline__ void prefetch_map(const CUtensorMap* m) { asm volatile("prefetch.tensormap [%0];" :: "l"(m) : "memory"); }
__device__ __forceinline__ void named_bar(int id, int n) { asm volatile("bar.sync %0, %1;" :: "r"(id), "r"(n) : "memory"); }

__device__ __forceinline__ void wgmma_m64n128k16_ss(float (&d)[64], uint64_t descA, uint64_t descB, int scaleD) {
    asm volatile("{\n.reg .pred p;\nsetp.ne.b32 p, %66, 0;\n"
        "wgmma.mma_async.sync.aligned.m64n128k16.f32.bf16.bf16 {%0, %1, %2, %3, %4, %5, %6, %7, %8, %9, %10, %11, %12, %13, %14, %15, %16, %17, %18, %19, %20, %21, %22, %23, %24, %25, %26, %27, %28, %29, %30, %31, %32, %33, %34, %35, %36, %37, %38, %39, %40, %41, %42, %43, %44, %45, %46, %47, %48, %49, %50, %51, %52, %53, %54, %55, %56, %57, %58, %59, %60, %61, %62, %63}, %64, %65, p, 1, 1, 0, 1;\n}\n"
        : "+f"(d[0]), "+f"(d[1]), "+f"(d[2]), "+f"(d[3]), "+f"(d[4]), "+f"(d[5]), "+f"(d[6]), "+f"(d[7]), "+f"(d[8]), "+f"(d[9]), "+f"(d[10]), "+f"(d[11]), "+f"(d[12]), "+f"(d[13]), "+f"(d[14]), "+f"(d[15]), "+f"(d[16]), "+f"(d[17]), "+f"(d[18]), "+f"(d[19]), "+f"(d[20]), "+f"(d[21]), "+f"(d[22]), "+f"(d[23]), "+f"(d[24]), "+f"(d[25]), "+f"(d[26]), "+f"(d[27]), "+f"(d[28]), "+f"(d[29]), "+f"(d[30]), "+f"(d[31]), "+f"(d[32]), "+f"(d[33]), "+f"(d[34]), "+f"(d[35]), "+f"(d[36]), "+f"(d[37]), "+f"(d[38]), "+f"(d[39]), "+f"(d[40]), "+f"(d[41]), "+f"(d[42]), "+f"(d[43]), "+f"(d[44]), "+f"(d[45]), "+f"(d[46]), "+f"(d[47]), "+f"(d[48]), "+f"(d[49]), "+f"(d[50]), "+f"(d[51]), "+f"(d[52]), "+f"(d[53]), "+f"(d[54]), "+f"(d[55]), "+f"(d[56]), "+f"(d[57]), "+f"(d[58]), "+f"(d[59]), "+f"(d[60]), "+f"(d[61]), "+f"(d[62]), "+f"(d[63])
        : "l"(descA), "l"(descB), "r"(scaleD));
}

__device__ __forceinline__ void wgmma_m64n64k16_ss(float (&d)[32], uint64_t descA, uint64_t descB, int scaleD) {
    asm volatile("{\n.reg .pred p;\nsetp.ne.b32 p, %34, 0;\n"
        "wgmma.mma_async.sync.aligned.m64n64k16.f32.bf16.bf16 {%0, %1, %2, %3, %4, %5, %6, %7, %8, %9, %10, %11, %12, %13, %14, %15, %16, %17, %18, %19, %20, %21, %22, %23, %24, %25, %26, %27, %28, %29, %30, %31}, %32, %33, p, 1, 1, 0, 1;\n}\n"
        : "+f"(d[0]), "+f"(d[1]), "+f"(d[2]), "+f"(d[3]), "+f"(d[4]), "+f"(d[5]), "+f"(d[6]), "+f"(d[7]), "+f"(d[8]), "+f"(d[9]), "+f"(d[10]), "+f"(d[11]), "+f"(d[12]), "+f"(d[13]), "+f"(d[14]), "+f"(d[15]), "+f"(d[16]), "+f"(d[17]), "+f"(d[18]), "+f"(d[19]), "+f"(d[20]), "+f"(d[21]), "+f"(d[22]), "+f"(d[23]), "+f"(d[24]), "+f"(d[25]), "+f"(d[26]), "+f"(d[27]), "+f"(d[28]), "+f"(d[29]), "+f"(d[30]), "+f"(d[31])
        : "l"(descA), "l"(descB), "r"(scaleD));
}

__device__ __forceinline__ void quad_transpose(uint32_t& r0, uint32_t& r1, uint32_t& r2, uint32_t& r3, int t) {
    const bool o1 = t & 1, o2 = t & 2;
    uint32_t x, y;
    x = o1 ? r0 : r1; y = __shfl_xor_sync(0xffffffffu, x, 1); if (o1) r0 = y; else r1 = y;
    x = o1 ? r2 : r3; y = __shfl_xor_sync(0xffffffffu, x, 1); if (o1) r2 = y; else r3 = y;
    x = o2 ? r0 : r2; y = __shfl_xor_sync(0xffffffffu, x, 2); if (o2) r0 = y; else r2 = y;
    x = o2 ? r1 : r3; y = __shfl_xor_sync(0xffffffffu, x, 2); if (o2) r1 = y; else r3 = y;
}

constexpr int K1_THREADS = 256;
constexpr int UT_PAD = 128;
constexpr int UT_LEN = UT_PAD + S_;
constexpr int KR_LEN = 2080;
constexpr int YP_LEN = S_ + (S_ / 32) * 8;

struct __align__(128) K1Smem {
    bf16 uT[4][UT_LEN];
    bf16 kr[4][2][KR_LEN];
    float yP[4][YP_LEN];
    uint64_t bar;
    uint8_t pad[32768];
};

__device__ __forceinline__ void mma16816(float (&c)[4], uint32_t a0, uint32_t a1, uint32_t a2, uint32_t a3, uint32_t b0, uint32_t b1) {
    asm("mma.sync.aligned.m16n8k16.row.col.f32.bf16.bf16.f32 {%0,%1,%2,%3}, {%4,%5,%6,%7}, {%8,%9}, {%0,%1,%2,%3};"
        : "+f"(c[0]), "+f"(c[1]), "+f"(c[2]), "+f"(c[3])
        : "r"(a0), "r"(a1), "r"(a2), "r"(a3), "r"(b0), "r"(b1));
}
__device__ __forceinline__ void ldsm_x4(uint32_t& r0, uint32_t& r1, uint32_t& r2, uint32_t& r3, uint32_t addr) {
    asm volatile("ldmatrix.sync.aligned.m8n8.x4.shared.b16 {%0,%1,%2,%3}, [%4];" : "=r"(r0), "=r"(r1), "=r"(r2), "=r"(r3) : "r"(addr) : "memory");
}

__device__ __forceinline__ void conv_mma(const bf16* uTc, const bf16* krlane, float (&acc)[16][4], int lane, int half) {
    const int lrow = lane & 7, lk = (lane >> 3) & 1, lt = lane >> 4;
    const uint32_t ubase = smem_u32(uTc) + (UT_PAD + 16 * (8 * lt + lrow) + 8 * lk) * 2;
#pragma unroll 1
    for (int pp = 0; pp < 4; pp++) {
        const int p = half * 4 + pp;
        uint32_t U[16][2];
#pragma unroll
        for (int j = 0; j < 16; j += 2) ldsm_x4(U[j][0], U[j][1], U[j + 1][0], U[j + 1][1], ubase + (j * 128 - p * 16) * 2);
        const uint32_t* kp = reinterpret_cast<const uint32_t*>(krlane - 16 * p);
        const volatile uint32_t* kpv = kp;
        uint32_t a0 = kp[0], a1 = kp[-4], a2 = kp[4], a3 = kpv[0];
#pragma unroll
        for (int q = 0; q < 16; q++) {
            uint32_t b0 = 0, b1 = 0, b2 = 0, b3 = 0;
            if (q < 15) { b0 = kp[-64 * (q + 1)]; b1 = kp[-64 * (q + 1) - 4]; b2 = kp[-64 * (q + 1) + 4]; b3 = kpv[-64 * (q + 1)]; }
#pragma unroll
            for (int n = 15; n >= q; n--) mma16816(acc[n], a0, a1, a2, a3, U[n - q][0], U[n - q][1]);
            a0 = b0; a1 = b1; a2 = b2; a3 = b3;
        }
    }
}

__global__ void __cluster_dims__(2, 1, 1) __launch_bounds__(K1_THREADS, 1)
conv_kernel(const bf16* __restrict__ k, const bf16* __restrict__ v,
            const bf16* __restrict__ shift_k, const bf16* __restrict__ ssm_k, const bf16* __restrict__ ssm_D) {
    extern __shared__ __align__(1024) uint8_t smem_raw[];
    pdl_launch();
    K1Smem& sm = *reinterpret_cast<K1Smem*>(smem_raw);
    const int tid = threadIdx.x, lane = tid & 31, warp = tid >> 5;
    const int bid = blockIdx.x;
    const int rank = bid & 1;
    const int c0 = 8 * (bid >> 1);
    const int cown = c0 + 4 * rank;
#define TMT 0
    TM(0, 0);
    const uint32_t bar = smem_u32(&sm.bar);
    if (tid == 0) {
        mbar_init(bar, 1);
        asm volatile("fence.mbarrier_init.release.cluster;" ::: "memory");
        mbar_expect_tx(bar, 1024 * 4 * 2);
    }
    cluster_arrive_relaxed();

    const int s0 = 1024 * rank + 4 * tid;
    uint4 kk[7], vv[4], sw[4];
#pragma unroll
    for (int i = 0; i < 4; i++) kk[3 + i] = ldg128(k + (size_t)(s0 + i) * D_ + c0);
#pragma unroll
    for (int i = 0; i < 4; i++) vv[i] = ldg128(v + (size_t)(s0 + i) * D_ + c0);
    if (lane == 0) {
#pragma unroll
        for (int i = 0; i < 3; i++) {
            const int s = s0 - 3 + i;
            kk[i] = make_uint4(0, 0, 0, 0);
            if (s >= 0) kk[i] = ldg128(k + (size_t)s * D_ + c0);
        }
    }
#pragma unroll
    for (int i = 0; i < 4; i++) sw[i] = ldg128(shift_k + (size_t)c0 * 4 + 8 * i);
    uint4 kq[4]; uint32_t nx[4];
#pragma unroll
    for (int c = 0; c < 4; c++) {
        const bf16* kr = ssm_k + (size_t)(cown + c) * S_;
        kq[c] = ldg128(kr + 8 * tid);
        nx[c] = 0u;
        if (tid < 255) nx[c] = ldg16(kr + 8 * tid + 8);
    }
    const uint32_t dval = ldg16(ssm_D + cown + (warp >> 1));
    if (tid < 64) *reinterpret_cast<uint4*>(&sm.uT[tid >> 4][(tid & 15) * 8]) = make_uint4(0, 0, 0, 0);
#pragma unroll
    for (int i = 0; i < 3; i++) {
        uint4 t;
        t.x = __shfl_up_sync(0xffffffffu, kk[4 + i].x, 1); t.y = __shfl_up_sync(0xffffffffu, kk[4 + i].y, 1);
        t.z = __shfl_up_sync(0xffffffffu, kk[4 + i].z, 1); t.w = __shfl_up_sync(0xffffffffu, kk[4 + i].w, 1);
        if (lane != 0) kk[i] = t;
    }
    uint32_t kvw[4][4];
    const uint32_t* kkw = reinterpret_cast<const uint32_t*>(kk);
    const uint32_t* vvw = reinterpret_cast<const uint32_t*>(vv);
#pragma unroll
    for (int i2 = 0; i2 < 4; i2++) {
        const uint32_t t0 = __byte_perm(sw[i2].x, sw[i2].z, 0x5410), t1 = __byte_perm(sw[i2].x, sw[i2].z, 0x7632);
        const uint32_t t2 = __byte_perm(sw[i2].y, sw[i2].w, 0x5410), t3 = __byte_perm(sw[i2].y, sw[i2].w, 0x7632);
#pragma unroll
        for (int r = 0; r < 4; r++) {
            uint32_t a = hmul2(kkw[(r + 0) * 4 + i2], t3);
            a = hadd2(a, hmul2(kkw[(r + 1) * 4 + i2], t2));
            a = hadd2(a, hmul2(kkw[(r + 2) * 4 + i2], t1));
            a = hadd2(a, hmul2(kkw[(r + 3) * 4 + i2], t0));
            kvw[r][i2] = hmul2(a, vvw[r * 4 + i2]);
        }
    }
    TM(0, 1);
    cluster_wait();
    {
        const uint32_t rbar = mapa(bar, (uint32_t)(rank ^ 1));
#pragma unroll
        for (int i2 = 0; i2 < 4; i2++) {
#pragma unroll
            for (int e = 0; e < 2; e++) {
                const uint32_t sel = e ? 0x7632 : 0x5410;
                const uint32_t w0 = __byte_perm(kvw[0][i2], kvw[1][i2], sel), w1 = __byte_perm(kvw[2][i2], kvw[3][i2], sel);
                const int cc = 2 * i2 + e;
                if ((cc >> 2) == rank) {
                    *reinterpret_cast<uint2*>(&sm.uT[cc & 3][UT_PAD + s0]) = make_uint2(w0, w1);
                } else {
                    st_async_v2(mapa(smem_u32(&sm.uT[cc & 3][UT_PAD + s0]), (uint32_t)(rank ^ 1)), w0, w1, rbar);
                }
            }
        }
    }
#pragma unroll
    for (int c = 0; c < 4; c++) {
        uint4 a, b;
        a.x = __byte_perm(kq[c].w, 0, 0x1032); a.y = __byte_perm(kq[c].z, 0, 0x1032);
        a.z = __byte_perm(kq[c].y, 0, 0x1032); a.w = __byte_perm(kq[c].x, 0, 0x1032);
        b.x = __byte_perm(nx[c], kq[c].w, 0x7610); b.y = __byte_perm(kq[c].w, kq[c].z, 0x7610);
        b.z = __byte_perm(kq[c].z, kq[c].y, 0x7610); b.w = __byte_perm(kq[c].y, kq[c].x, 0x7610);
        *reinterpret_cast<uint4*>(&sm.kr[c][0][2040 - 8 * tid]) = a;
        *reinterpret_cast<uint4*>(&sm.kr[c][1][2040 - 8 * tid]) = b;
        if (tid == 0) {
            *reinterpret_cast<uint4*>(&sm.kr[c][1][2048]) = make_uint4(kq[c].x & 0xffffu, 0, 0, 0);
        } else if (tid < 8) {
            if (tid < 4) *reinterpret_cast<uint4*>(&sm.kr[c][1][2048 + 8 * tid]) = make_uint4(0, 0, 0, 0);
            else *reinterpret_cast<uint4*>(&sm.kr[c][0][2048 + 8 * (tid - 4)]) = make_uint4(0, 0, 0, 0);
        }
    }
    TM(0, 3);
    __syncthreads();
    mbar_wait_cluster(bar, 0);
    TM(0, 4);

    const int ch = warp >> 1, half = warp & 1;
    const int g = lane >> 2, t = lane & 3;
    float acc[16][4];
#pragma unroll
    for (int i = 0; i < 16; i++) { acc[i][0] = acc[i][1] = acc[i][2] = acc[i][3] = 0.f; }
    const bf16* krlane = (g & 1) ? &sm.kr[ch][0][2047 - g + 2 * t] : &sm.kr[ch][1][2048 - g + 2 * t];
    conv_mma(sm.uT[ch], krlane, acc, lane, half);
    TM(0, 5);
    float* yp = &sm.yP[ch][40 * t + g];
    if (half) {
#pragma unroll
        for (int n = 0; n < 16; n++) {
            yp[160 * n] = acc[n][0];
            yp[160 * n + 16] = acc[n][1];
            yp[160 * n + 8] = acc[n][2];
            yp[160 * n + 24] = acc[n][3];
        }
    }
    named_bar(1 + ch, 64);
    if (!half) {
#pragma unroll
        for (int n = 0; n < 16; n++) {
            yp[160 * n] += acc[n][0];
            yp[160 * n + 16] += acc[n][1];
            yp[160 * n + 8] += acc[n][2];
            yp[160 * n + 24] += acc[n][3];
        }
    }
    named_bar(1 + ch, 64);
    TM(0, 6);
    {
        const int tt = tid & 63;
        bf16* dst = g_yT + (size_t)(cown + ch) * S_;
        const uint32_t d2 = dval * 0x10001u;
#pragma unroll
        for (int j = 0; j < 4; j++) {
            const int s = (j * 64 + tt) * 8;
            const float* src = &sm.yP[ch][s + (s >> 5) * 8];
            const float4 a = *reinterpret_cast<const float4*>(src), b = *reinterpret_cast<const float4*>(src + 4);
            const uint4 kv4 = *reinterpret_cast<const uint4*>(&sm.uT[ch][UT_PAD + s]);
            *reinterpret_cast<uint4*>(dst + s) = make_uint4(hadd2(pack_bf16(a.x, a.y), hmul2(kv4.x, d2)), hadd2(pack_bf16(a.z, a.w), hmul2(kv4.y, d2)),
                                                            hadd2(pack_bf16(b.x, b.y), hmul2(kv4.z, d2)), hadd2(pack_bf16(b.z, b.w), hmul2(kv4.w, d2)));
        }
    }
    TM(0, 7);
#undef TMT
}

constexpr int R_THREADS = 512;
constexpr int R_ROWS = 16;

__device__ __forceinline__ float warp_sum(float s) {
#pragma unroll
    for (int o = 16; o > 0; o >>= 1) s += __shfl_xor_sync(0xffffffffu, s, o);
    return s;
}
__device__ __forceinline__ uint32_t hsub2(uint32_t a, uint32_t b) {
    __nv_bfloat162 r = __hsub2_rn(*reinterpret_cast<__nv_bfloat162*>(&a), *reinterpret_cast<__nv_bfloat162*>(&b));
    return *reinterpret_cast<uint32_t*>(&r);
}
__device__ __forceinline__ void ln_row(const uint32_t (&x)[8], uint32_t (&o)[8]) {
    float s0 = 0.f, s1 = 0.f;
#pragma unroll
    for (int i = 0; i < 8; i++) { s0 += bf_lo(x[i]); s1 += bf_hi(x[i]); }
    const float mean = warp_sum(s0 + s1) * (1.0f / D_);
    float ss0 = 0.f, ss1 = 0.f;
#pragma unroll
    for (int i = 0; i < 8; i++) { const float d0 = bf_lo(x[i]) - mean, d1 = bf_hi(x[i]) - mean; ss0 += d0 * d0; ss1 += d1 * d1; }
    const float var = bf16r(warp_sum(ss0 + ss1) * (1.0f / D_));
    const float rinv = 1.0f / bf16r(sqrtf(bf16r(var + 1e-5f)));
    const uint32_t m2 = pack_bf16(mean, mean);
#pragma unroll
    for (int i = 0; i < 8; i++) {
        const uint32_t d = hsub2(x[i], m2);
        o[i] = pack_bf16(bf_lo(d) * rinv, bf_hi(d) * rinv);
    }
}

__global__ void __launch_bounds__(R_THREADS, 1)
row_kernel(const bf16* __restrict__ q) {
    __shared__ __align__(16) uint32_t ys[R_ROWS][D_ / 2 + 4];
    const int tid = threadIdx.x, lane = tid & 31, warp = tid >> 5;
    const int s0 = blockIdx.x * R_ROWS;
#define TMT 0
    TM(1, 0);
    pdl_launch();
    const int r0 = s0 + warp;
    const int p = tid & 255, hs = tid >> 8;
    const uint4 qa = ldg128(q + (size_t)r0 * D_ + 8 * lane);
    const uint4 qb = ldg128(q + (size_t)r0 * D_ + 8 * (lane + 32));
    const uint32_t x[8] = {qa.x, qa.y, qa.z, qa.w, qb.x, qb.y, qb.z, qb.w};
    uint32_t qn[8];
    ln_row(x, qn);
    pdl_wait();
    {
        const bf16* y0 = g_yT + (size_t)(2 * p) * S_ + s0 + 8 * hs;
        const uint4 ya = ldcg128(y0);
        const uint4 yb = ldcg128(y0 + S_);
        const uint32_t aw[4] = {ya.x, ya.y, ya.z, ya.w};
        const uint32_t bw[4] = {yb.x, yb.y, yb.z, yb.w};
#pragma unroll
        for (int j = 0; j < 4; j++) {
            ys[8 * hs + 2 * j][p] = __byte_perm(aw[j], bw[j], 0x5410);
            ys[8 * hs + 2 * j + 1][p] = __byte_perm(aw[j], bw[j], 0x7632);
        }
    }
    __syncthreads();
    TM(1, 1);
    uint32_t h[8], hn[8];
#pragma unroll
    for (int i = 0; i < 2; i++) {
        const uint4 yw4 = *reinterpret_cast<const uint4*>(&ys[warp][4 * (lane + 32 * i)]);
        const uint32_t yw[4] = {yw4.x, yw4.y, yw4.z, yw4.w};
#pragma unroll
        for (int j = 0; j < 4; j++) h[4 * i + j] = hadd2(x[4 * i + j], hmul2(qn[4 * i + j], yw[j]));
    }
    ln_row(h, hn);
#pragma unroll
    for (int i = 0; i < 2; i++) {
        const size_t off = (size_t)r0 * D_ + 8 * (lane + 32 * i);
        *reinterpret_cast<uint4*>(g_h + off) = make_uint4(h[4 * i], h[4 * i + 1], h[4 * i + 2], h[4 * i + 3]);
        *reinterpret_cast<uint4*>(g_hn + off) = make_uint4(hn[4 * i], hn[4 * i + 1], hn[4 * i + 2], hn[4 * i + 3]);
    }
    TM(1, 2);
#undef TMT
}

constexpr int G1_THREADS = 384;
constexpr int G1_STAGES = 6;
constexpr int G1_A_BYTES = 8 * 16384;
constexpr int G1_B_STAGE = 16384;
constexpr int G1_OFF_B = G1_A_BYTES;
constexpr int G1_OFF_BAR = G1_OFF_B + G1_STAGES * G1_B_STAGE;
constexpr int G1_SMEM = G1_OFF_BAR + 256;

__device__ __forceinline__ float sigmoid_fast(float x) {
    float t; asm("tanh.approx.f32 %0, %1;" : "=f"(t) : "f"(0.5f * x));
    return fmaf(t, 0.5f, 0.5f);
}

template <int NT>
__device__ __forceinline__ void g1_epilogue(const float (&acc)[NT * 8], bf16* out0, int t) {
#pragma unroll
    for (int j0 = 0; j0 < NT; j0 += 4) {
        uint32_t P0[4], P1[4];
#pragma unroll
        for (int jj = 0; jj < 4; jj++) {
            const int j = j0 + jj;
            float r[4];
#pragma unroll
            for (int e = 0; e < 4; e++) r[e] = sigmoid_fast(acc[4 * j + e]) * acc[4 * (NT + j) + e];
            P0[jj] = pack_bf16(r[0], r[1]);
            P1[jj] = pack_bf16(r[2], r[3]);
        }
        quad_transpose(P0[0], P0[1], P0[2], P0[3], t);
        quad_transpose(P1[0], P1[1], P1[2], P1[3], t);
        *reinterpret_cast<uint4*>(out0 + 8 * (j0 + t)) = make_uint4(P0[0], P0[1], P0[2], P0[3]);
        *reinterpret_cast<uint4*>(out0 + 8 * F_ + 8 * (j0 + t)) = make_uint4(P1[0], P1[1], P1[2], P1[3]);
    }
}

__host__ __device__ constexpr int g1_parity(int it) {
    int cnt = 0;
    for (int j = 0; j < it; j++) if ((((j >> 3) ^ (it >> 3)) & 1) == 0 && (j % G1_STAGES) == (it % G1_STAGES)) cnt++;
    return cnt & 1;
}
template <int NT, int U>
__device__ __forceinline__ void g1_unit(uint32_t sb, uint32_t barA, uint32_t barF, uint32_t barE, uint32_t peer, int tl, bf16* outp, int t) {
    float acc[2][NT * 8];
#pragma unroll
    for (int kc = 0; kc < 8; kc++) {
        const int it = 8 * U + kc;
        const int st = it % G1_STAGES, ph = g1_parity(it);
        if (U < 2) mbar_wait(barA + 8 * kc, 0);
        mbar_wait(barF + 8 * st, ph);
        if (tl == 0) TR(1, it);
        wgmma_fence();
        const uint32_t aaddr = sb + kc * 16384;
        const uint32_t baddr = sb + G1_OFF_B + st * G1_B_STAGE;
#pragma unroll
        for (int kk = 0; kk < 4; kk++) {
#pragma unroll
            for (int hf = 0; hf < 2; hf++) {
                if constexpr (NT == 8)
                    wgmma_m64n128k16_ss(acc[hf], make_desc(aaddr + hf * 8192 + kk * 32, 16, 1024, 1), make_desc(baddr + kk * 2048, 8192, 1024, 1), (kc | kk) != 0);
                else
                    wgmma_m64n64k16_ss(acc[hf], make_desc(aaddr + hf * 8192 + kk * 32, 16, 1024, 1), make_desc(baddr + kk * 1024, 4096, 512, 2), (kc | kk) != 0);
            }
        }
        wgmma_commit();
        if (kc > 0) {
            wgmma_wait<1>();
            const int pst = (it - 1) % G1_STAGES;
            if (tl == 0) mbar_arrive(barE + 8 * pst);
        }
    }
    wgmma_wait<0>();
    {
        const int pst = (8 * U + 7) % G1_STAGES;
        if (tl == 0) mbar_arrive(barE + 8 * pst);
    }
    if (tl == 0) TR(2, U);
    g1_epilogue<NT>(acc[0], outp + 64 * U, t);
    g1_epilogue<NT>(acc[1], outp + 64 * U + (size_t)64 * F_, t);
    if (tl == 0) TR(2, 4 + U);
}

__global__ void __cluster_dims__(2, 1, 1) __launch_bounds__(G1_THREADS, 1)
gemm1_kernel(const __grid_constant__ CUtensorMap mapA, const __grid_constant__ CUtensorMap mapG64, const __grid_constant__ CUtensorMap mapU64,
             const __grid_constant__ CUtensorMap mapG32, const __grid_constant__ CUtensorMap mapU32) {
    extern __shared__ __align__(1024) uint8_t smem_raw[];
    const uint32_t sb = smem_u32(smem_raw);
    const int tid = threadIdx.x, lane = tid & 31, warp = tid >> 5, wgi = tid >> 7;
    const int rank = blockIdx.x & 1;
    const int cb = blockIdx.x & 7, rb = blockIdx.x >> 3;
#define TMT 128
    TM(2, 0);
    pdl_launch();
    if (tid == 32) { prefetch_map(&mapA); prefetch_map(&mapG64); prefetch_map(&mapU64); prefetch_map(&mapG32); prefetch_map(&mapU32); }
    const uint32_t barA = sb + G1_OFF_BAR;
    const uint32_t barF = barA + 64;
    const uint32_t barE = barF + 16 * G1_STAGES;
    if (tid == 0) {
        for (int i = 0; i < 8; i++) mbar_init(barA + 8 * i, 1);
        for (int i = 0; i < G1_STAGES; i++) { mbar_init(barF + 8 * i, 1); mbar_init(barF + 8 * G1_STAGES + 8 * i, 1); mbar_init(barE + 8 * i, 1); }
        for (int i = 0; i < 8; i++) mbar_expect_tx(barA + 8 * i, 16384);
        asm volatile("fence.mbarrier_init.release.cluster;" ::: "memory");
    }
    __syncthreads();
    cluster_arrive_relaxed();
    cluster_wait();

    if (wgi == 0) {
        reg_dealloc<40>();
        if (tid == 0) {
            int st = 0, ph = 1;
            for (int it = 0; it < 32; it++) {
                const int kc = it & 7, u = it >> 3;
                if (it == G1_STAGES) {
                    pdl_wait();
                    for (int i = 0; i < 4; i++) {
                        const int c = 2 * i + rank;
                        tma_load_2d_mc(sb + c * 16384, &mapA, barA + 8 * c, c * 64, rb * 128, (uint16_t)3);
                    }
                }
                mbar_wait(barE + 8 * st, ph);
                TR(0, it);
                const uint32_t dst = sb + G1_OFF_B + st * G1_B_STAGE;
                const uint32_t bf = barF + (u & 1) * 8 * G1_STAGES + 8 * st;
                if (u < 3) {
                    mbar_expect_tx(bf, 16384);
                    tma_load_2d(dst, &mapG64, bf, cb * 224 + 64 * u, kc * 64);
                    tma_load_2d(dst + 8192, &mapU64, bf, cb * 224 + 64 * u, kc * 64);
                } else {
                    mbar_expect_tx(bf, 8192);
                    tma_load_2d(dst, &mapG32, bf, cb * 224 + 192, kc * 64);
                    tma_load_2d(dst + 4096, &mapU32, bf, cb * 224 + 192, kc * 64);
                }
                if (++st == G1_STAGES) { st = 0; ph ^= 1; }
            }
        }
        __syncwarp();
    } else {
        reg_alloc<232>();
        pdl_wait();
        const int g = lane >> 2, t = lane & 3, wl = warp & 3, tl = tid & 127;
        bf16* outp = g_hh + (size_t)(rb * 128 + wl * 16 + g) * F_ + cb * 224;
        const uint32_t peer = (uint32_t)(rank ^ 1);
        if (wgi == 1) {
            g1_unit<8, 0>(sb, barA, barF, barE, peer, tl, outp, t);
            TM(2, 1);
            g1_unit<8, 2>(sb, barA, barF, barE, peer, tl, outp, t);
            TM(2, 2);
        } else {
            g1_unit<8, 1>(sb, barA, barF + 8 * G1_STAGES, barE, peer, tl, outp, t);
            g1_unit<4, 3>(sb, barA, barF + 8 * G1_STAGES, barE, peer, tl, outp, t);
        }
    }
    cluster_arrive_relaxed();
    cluster_wait();
    TM(2, 3);
}

constexpr int G2_THREADS = 384;
constexpr int G2_STAGES = 6;
constexpr int G2_STAGE = 32768;
constexpr int G2_OFF_X = G2_STAGES * G2_STAGE;
constexpr int G2_OFF_BAR = G2_OFF_X + 32768;
constexpr int G2_SMEM = G2_OFF_BAR + 128;
constexpr int G2_KSTEPS = 14;

__global__ void __cluster_dims__(2, 1, 1) __launch_bounds__(G2_THREADS, 1)
gemm2_kernel(const __grid_constant__ CUtensorMap mapHH, const __grid_constant__ CUtensorMap mapWd, bf16* __restrict__ out) {
    extern __shared__ __align__(1024) uint8_t smem_raw[];
    const uint32_t sb = smem_u32(smem_raw);
    const int tid = threadIdx.x, lane = tid & 31, warp = tid >> 5, wgi = tid >> 7;
    const int ks = blockIdx.x & 1, nb = (blockIdx.x >> 1) & 3, rb = blockIdx.x >> 3;
    TM(3, 0);
    if (tid == 32) { prefetch_map(&mapHH); prefetch_map(&mapWd); }
    const uint32_t barF = sb + G2_OFF_BAR;
    const uint32_t barE = barF + 8 * G2_STAGES;
    const uint32_t barX = barE + 8 * G2_STAGES;
    if (tid == 0) {
        for (int i = 0; i < G2_STAGES; i++) { mbar_init(barF + 8 * i, 1); mbar_init(barE + 8 * i, 2); }
        mbar_init(barX, 1);
        asm volatile("fence.mbarrier_init.release.cluster;" ::: "memory");
        mbar_expect_tx(barX, 32768);
    }
    __syncthreads();
    cluster_arrive_relaxed();

    if (wgi == 0) {
        if (tid == 0) {
            for (int it = 0; it < G2_STAGES; it++) {
                mbar_expect_tx(barF + 8 * it, 32768);
                tma_load_3d(sb + it * G2_STAGE + 16384, &mapWd, barF + 8 * it, 0, ks * 896 + it * 64, nb * 2);
            }
            pdl_wait();
            for (int it = 0; it < G2_STAGES; it++)
                tma_load_2d(sb + it * G2_STAGE, &mapHH, barF + 8 * it, ks * 896 + it * 64, rb * 128);
            int st = 0, ph = 0;
            for (int it = G2_STAGES; it < G2_KSTEPS; it++) {
                mbar_wait(barE + 8 * st, ph);
                const uint32_t dst = sb + st * G2_STAGE;
                const int k0 = ks * 896 + it * 64;
                mbar_expect_tx(barF + 8 * st, 32768);
                tma_load_2d(dst, &mapHH, barF + 8 * st, k0, rb * 128);
                tma_load_3d(dst + 16384, &mapWd, barF + 8 * st, 0, k0, nb * 2);
                if (++st == G2_STAGES) { st = 0; ph ^= 1; }
            }
        }
        __syncwarp();
        cluster_wait();
    } else {
        const int cw = wgi - 1;
        const int g = lane >> 2, t = lane & 3, wl = warp & 3;
        const int tl = tid & 127;
        int st = 0, ph = 0;
        float acc[64];
        pdl_wait();
#pragma unroll 1
        for (int it = 0; it < G2_KSTEPS; it++) {
            mbar_wait(barF + 8 * st, ph);
            if (it == 0) TM(3, 1);
            wgmma_fence();
            const uint32_t aaddr = sb + st * G2_STAGE + cw * 8192;
            const uint32_t baddr = sb + st * G2_STAGE + 16384;
#pragma unroll
            for (int kk = 0; kk < 4; kk++)
                wgmma_m64n128k16_ss(acc, make_desc(aaddr + kk * 32, 16, 1024, 1), make_desc(baddr + kk * 2048, 8192, 1024, 1), (it | kk) != 0);
            wgmma_commit();
            wgmma_wait<0>();
            if (tl == 0) mbar_arrive(barE + 8 * st);
            if (++st == G2_STAGES) { st = 0; ph ^= 1; }
        }
        TM(3, 2);
        cluster_wait();
        if (cw != ks) {
            const uint32_t dst = mapa(sb + G2_OFF_X + tl * 16, (uint32_t)(ks ^ 1));
            const uint32_t rbar = mapa(barX, (uint32_t)(ks ^ 1));
#pragma unroll
            for (int i = 0; i < 16; i++) st_async_v4f(dst + i * 2048, acc[4 * i], acc[4 * i + 1], acc[4 * i + 2], acc[4 * i + 3], rbar);
        } else {
            const float4* xb = reinterpret_cast<const float4*>(smem_raw + G2_OFF_X) + tl;
            const int row0 = rb * 128 + cw * 64 + wl * 16 + g;
            const bf16* h0 = g_h + (size_t)row0 * D_ + nb * 128;
            bf16* o0 = out + (size_t)row0 * D_ + nb * 128;
            uint32_t ha[16], hb[16];
#pragma unroll
            for (int j = 0; j < 16; j++) {
                ha[j] = __ldcg(reinterpret_cast<const uint32_t*>(h0 + 8 * j + 2 * t));
                hb[j] = __ldcg(reinterpret_cast<const uint32_t*>(h0 + 8 * D_ + 8 * j + 2 * t));
            }
            mbar_wait_cluster(barX, 0);
            TM(3, 4);
#pragma unroll
            for (int j0 = 0; j0 < 16; j0 += 4) {
                uint32_t P0[4], P1[4];
#pragma unroll
                for (int jj = 0; jj < 4; jj++) {
                    const int j = j0 + jj;
                    const float4 x = xb[j * 128];
                    P0[jj] = pack_bf16(bf_lo(ha[j]) + bf16r(acc[4 * j] + x.x), bf_hi(ha[j]) + bf16r(acc[4 * j + 1] + x.y));
                    P1[jj] = pack_bf16(bf_lo(hb[j]) + bf16r(acc[4 * j + 2] + x.z), bf_hi(hb[j]) + bf16r(acc[4 * j + 3] + x.w));
                }
                quad_transpose(P0[0], P0[1], P0[2], P0[3], t);
                quad_transpose(P1[0], P1[1], P1[2], P1[3], t);
                *reinterpret_cast<uint4*>(o0 + 8 * (j0 + t)) = make_uint4(P0[0], P0[1], P0[2], P0[3]);
                *reinterpret_cast<uint4*>(o0 + 8 * D_ + 8 * (j0 + t)) = make_uint4(P1[0], P1[1], P1[2], P1[3]);
            }
        }
        TM(3, 5);
    }
#undef TMT
}

typedef CUresult (*EncodeFn)(CUtensorMap*, CUtensorMapDataType, cuuint32_t, void*, const cuuint64_t*, const cuuint64_t*,
                             const cuuint32_t*, const cuuint32_t*, CUtensorMapInterleave, CUtensorMapSwizzle,
                             CUtensorMapL2promotion, CUtensorMapFloatOOBfill);

static void enc2d(EncodeFn enc, CUtensorMap* m, const void* p, int rows, int cols, int brows, int bcols) {
    cuuint64_t dims[2] = {(cuuint64_t)cols, (cuuint64_t)rows};
    cuuint64_t strides[1] = {(cuuint64_t)cols * 2};
    cuuint32_t box[2] = {(cuuint32_t)bcols, (cuuint32_t)brows};
    cuuint32_t es[2] = {1, 1};
    enc(m, CU_TENSOR_MAP_DATA_TYPE_BFLOAT16, 2, const_cast<void*>(p), dims, strides, box, es, CU_TENSOR_MAP_INTERLEAVE_NONE,
        bcols == 32 ? CU_TENSOR_MAP_SWIZZLE_64B : CU_TENSOR_MAP_SWIZZLE_128B, CU_TENSOR_MAP_L2_PROMOTION_L2_128B, CU_TENSOR_MAP_FLOAT_OOB_FILL_NONE);
}
static void enc3d(EncodeFn enc, CUtensorMap* m, const void* p, int rows, int cols, int atom, int brows, int natoms) {
    cuuint64_t dims[3] = {(cuuint64_t)atom, (cuuint64_t)rows, (cuuint64_t)(cols / atom)};
    cuuint64_t strides[2] = {(cuuint64_t)cols * 2, (cuuint64_t)atom * 2};
    cuuint32_t box[3] = {(cuuint32_t)atom, (cuuint32_t)brows, (cuuint32_t)natoms};
    cuuint32_t es[3] = {1, 1, 1};
    enc(m, CU_TENSOR_MAP_DATA_TYPE_BFLOAT16, 3, const_cast<void*>(p), dims, strides, box, es, CU_TENSOR_MAP_INTERLEAVE_NONE,
        atom == 32 ? CU_TENSOR_MAP_SWIZZLE_64B : CU_TENSOR_MAP_SWIZZLE_128B, CU_TENSOR_MAP_L2_PROMOTION_L2_128B, CU_TENSOR_MAP_FLOAT_OOB_FILL_NONE);
}

extern "C" void kernel_launch(void* const* d_in, const int* in_sizes, int n_in, void* d_out, int out_size) {
    const bf16* q = (const bf16*)d_in[0];
    const bf16* k = (const bf16*)d_in[1];
    const bf16* v = (const bf16*)d_in[2];
    const bf16* shift_k = (const bf16*)d_in[3];
    const bf16* ssm_k = (const bf16*)d_in[4];
    const bf16* ssm_D = (const bf16*)d_in[5];
    const bf16* wg = (const bf16*)d_in[7];
    const bf16* wu = (const bf16*)d_in[8];
    const bf16* wd = (const bf16*)d_in[9];
    bf16* out = (bf16*)d_out;

    static EncodeFn enc = nullptr;
    static void *p_hn = nullptr, *p_hh = nullptr;
    if (!enc) {
        void* fn = nullptr; cudaDriverEntryPointQueryResult qr;
        cudaGetDriverEntryPoint("cuTensorMapEncodeTiled", &fn, cudaEnableDefault, &qr);
        enc = (EncodeFn)fn;
        cudaGetSymbolAddress(&p_hn, g_hn);
        cudaGetSymbolAddress(&p_hh, g_hh);
        cudaFuncSetAttribute(conv_kernel, cudaFuncAttributeMaxDynamicSharedMemorySize, (int)sizeof(K1Smem));
        cudaFuncSetAttribute(gemm1_kernel, cudaFuncAttributeMaxDynamicSharedMemorySize, G1_SMEM);
        cudaFuncSetAttribute(gemm2_kernel, cudaFuncAttributeMaxDynamicSharedMemorySize, G2_SMEM);
    }
    CUtensorMap mA, mG64, mU64, mG32, mU32, mHH, mWd;
    enc2d(enc, &mA, p_hn, S_, D_, 128, 64);
    enc2d(enc, &mG64, wg, D_, F_, 64, 64);
    enc2d(enc, &mU64, wu, D_, F_, 64, 64);
    enc2d(enc, &mG32, wg, D_, F_, 64, 32);
    enc2d(enc, &mU32, wu, D_, F_, 64, 32);
    enc2d(enc, &mHH, p_hh, S_, F_, 128, 64);
    enc3d(enc, &mWd, wd, F_, D_, 64, 64, 2);

    cudaStream_t st = cudaStreamPerThread;
    cudaLaunchAttribute at[1];
    at[0].id = cudaLaunchAttributeProgrammaticStreamSerialization;
    at[0].val.programmaticStreamSerializationAllowed = 1;
    cudaLaunchConfig_t cfg = {};
    cfg.stream = st; cfg.attrs = at; cfg.numAttrs = 1;
    conv_kernel<<<128, K1_THREADS, sizeof(K1Smem), st>>>(k, v, shift_k, ssm_k, ssm_D);
    cfg.gridDim = dim3(S_ / R_ROWS); cfg.blockDim = dim3(R_THREADS); cfg.dynamicSmemBytes = 0;
    cudaLaunchKernelEx(&cfg, row_kernel, q);
    cfg.gridDim = dim3(128); cfg.blockDim = dim3(G1_THREADS); cfg.dynamicSmemBytes = G1_SMEM;
    cudaLaunchKernelEx(&cfg, gemm1_kernel, mA, mG64, mU64, mG32, mU32);
    cfg.gridDim = dim3(128); cfg.blockDim = dim3(G2_THREADS); cfg.dynamicSmemBytes = G2_SMEM;
    cudaLaunchKernelEx(&cfg, gemm2_kernel, mHH, mWd, out);
}
```

```cpp
#include <cuda_runtime.h>
#include <cuda_bf16.h>
#include <cuda.h>
#include <stdint.h>

typedef __nv_bfloat16 bf16;
constexpr int S_ = 2048, D_ = 512, F_ = 1792;

__device__ bf16 g_yT[D_ * S_];
__device__ bf16 g_h[S_ * D_];
__device__ bf16 g_hn[S_ * D_];
__device__ bf16 g_hh[S_ * F_];

#define TM(k, i)
#define TR(k, i)
__device__ __forceinline__ uint32_t smem_u32(const void* p) { return (uint32_t)__cvta_generic_to_shared(p); }
__device__ __forceinline__ float bf16r(float x) { return __bfloat162float(__float2bfloat16_rn(x)); }
__device__ __forceinline__ float bf_lo(uint32_t w) { return __uint_as_float(w << 16); }
__device__ __forceinline__ float bf_hi(uint32_t w) { return __uint_as_float(w & 0xffff0000u); }
__device__ __forceinline__ uint32_t pack_bf16(float lo, float hi) {
    __nv_bfloat162 v = __floats2bfloat162_rn(lo, hi);
    return *reinterpret_cast<uint32_t*>(&v);
}
__device__ __forceinline__ uint32_t hmul2(uint32_t a, uint32_t b) {
    __nv_bfloat162 r = __hmul2_rn(*reinterpret_cast<__nv_bfloat162*>(&a), *reinterpret_cast<__nv_bfloat162*>(&b));
    return *reinterpret_cast<uint32_t*>(&r);
}
__device__ __forceinline__ uint32_t hadd2(uint32_t a, uint32_t b) {
    __nv_bfloat162 r = __hadd2_rn(*reinterpret_cast<__nv_bfloat162*>(&a), *reinterpret_cast<__nv_bfloat162*>(&b));
    return *reinterpret_cast<uint32_t*>(&r);
}
__device__ __forceinline__ uint4 ldg128(const void* p) {
    uint4 r; asm volatile("ld.global.nc.v4.u32 {%0,%1,%2,%3}, [%4];" : "=r"(r.x), "=r"(r.y), "=r"(r.z), "=r"(r.w) : "l"(p)); return r;
}
__device__ __forceinline__ uint4 ldcg128(const void* p) {
    uint4 r; asm volatile("ld.global.cg.v4.u32 {%0,%1,%2,%3}, [%4];" : "=r"(r.x), "=r"(r.y), "=r"(r.z), "=r"(r.w) : "l"(p)); return r;
}
__device__ __forceinline__ uint32_t ldg16(const void* p) {
    unsigned short r; asm volatile("ld.global.nc.u16 %0, [%1];" : "=h"(r) : "l"(p)); return (uint32_t)r;
}
__device__ __forceinline__ void mbar_init(uint32_t bar, int cnt) { asm volatile("mbarrier.init.shared::cta.b64 [%0], %1;" :: "r"(bar), "r"(cnt)); }
__device__ __forceinline__ void mbar_expect_tx(uint32_t bar, uint32_t bytes) { asm volatile("mbarrier.arrive.expect_tx.shared::cta.b64 _, [%0], %1;" :: "r"(bar), "r"(bytes) : "memory"); }
__device__ __forceinline__ void mbar_arrive(uint32_t bar) { asm volatile("mbarrier.arrive.shared::cta.b64 _, [%0];" :: "r"(bar) : "memory"); }
__device__ __forceinline__ void mbar_arrive_cluster(uint32_t bar, uint32_t cta) {
    asm volatile("{\n.reg .b32 ra;\nmapa.shared::cluster.u32 ra, %0, %1;\nmbarrier.arrive.shared::cluster.b64 _, [ra];\n}" :: "r"(bar), "r"(cta) : "memory");
}
__device__ __forceinline__ void mbar_wait(uint32_t bar, uint32_t parity) {
    asm volatile("{\n.reg .pred P1;\nLAB_WAIT:\nmbarrier.try_wait.parity.shared::cta.b64 P1, [%0], %1;\n@P1 bra DONE;\nbra LAB_WAIT;\nDONE:\n}" :: "r"(bar), "r"(parity) : "memory");
}
__device__ __forceinline__ void mbar_wait_cluster(uint32_t bar, uint32_t parity) {
    asm volatile("{\n.reg .pred P1;\nLAB_WAIT:\nmbarrier.try_wait.parity.acquire.cluster.shared::cta.b64 P1, [%0], %1;\n@P1 bra DONE;\nbra LAB_WAIT;\nDONE:\n}" :: "r"(bar), "r"(parity) : "memory");
}
__device__ __forceinline__ void tma_load_2d(uint32_t dst, const CUtensorMap* map, uint32_t bar, int c0, int c1) {
    asm volatile("cp.async.bulk.tensor.2d.shared::cluster.global.mbarrier::complete_tx::bytes [%0], [%1, {%3, %4}], [%2];"
        :: "r"(dst), "l"(map), "r"(bar), "r"(c0), "r"(c1) : "memory");
}
__device__ __forceinline__ void tma_load_2d_mc(uint32_t dst, const CUtensorMap* map, uint32_t bar, int c0, int c1, uint16_t mask) {
    asm volatile("cp.async.bulk.tensor.2d.shared::cluster.global.mbarrier::complete_tx::bytes.multicast::cluster [%0], [%1, {%3, %4}], [%2], %5;"
        :: "r"(dst), "l"(map), "r"(bar), "r"(c0), "r"(c1), "h"(mask) : "memory");
}
__device__ __forceinline__ void tma_load_3d(uint32_t dst, const CUtensorMap* map, uint32_t bar, int c0, int c1, int c2) {
    asm volatile("cp.async.bulk.tensor.3d.shared::cluster.global.mbarrier::complete_tx::bytes [%0], [%1, {%3, %4, %5}], [%2];"
        :: "r"(dst), "l"(map), "r"(bar), "r"(c0), "r"(c1), "r"(c2) : "memory");
}
__device__ __forceinline__ void cluster_arrive() { asm volatile("barrier.cluster.arrive.aligned;" ::: "memory"); }
__device__ __forceinline__ void cluster_arrive_relaxed() { asm volatile("barrier.cluster.arrive.relaxed.aligned;" ::: "memory"); }
__device__ __forceinline__ void cluster_wait() { asm volatile("barrier.cluster.wait.aligned;" ::: "memory"); }
__device__ __forceinline__ uint32_t mapa(uint32_t addr, uint32_t cta) {
    uint32_t r; asm volatile("mapa.shared::cluster.u32 %0, %1, %2;" : "=r"(r) : "r"(addr), "r"(cta)); return r;
}
__device__ __forceinline__ void st_async_v2(uint32_t addr, uint32_t a, uint32_t b, uint32_t rbar) {
    asm volatile("st.async.weak.shared::cluster.mbarrier::complete_tx::bytes.v2.b32 [%0], {%1, %2}, [%3];" :: "r"(addr), "r"(a), "r"(b), "r"(rbar) : "memory");
}
__device__ __forceinline__ void st_async_v4f(uint32_t addr, float a, float b, float c, float d, uint32_t rbar) {
    asm volatile("st.async.weak.shared::cluster.mbarrier::complete_tx::bytes.v4.f32 [%0], {%1, %2, %3, %4}, [%5];" :: "r"(addr), "f"(a), "f"(b), "f"(c), "f"(d), "r"(rbar) : "memory");
}
__device__ __forceinline__ void wgmma_fence() { asm volatile("wgmma.fence.sync.aligned;" ::: "memory"); }
__device__ __forceinline__ void wgmma_commit() { asm volatile("wgmma.commit_group.sync.aligned;" ::: "memory"); }
template <int N> __device__ __forceinline__ void wgmma_wait() { asm volatile("wgmma.wait_group.sync.aligned %0;" :: "n"(N) : "memory"); }
__device__ __forceinline__ uint64_t make_desc(uint32_t addr, uint32_t lbo_bytes, uint32_t sbo_bytes, uint32_t layout) {
    return (uint64_t)((addr & 0x3FFFF) >> 4) | ((uint64_t)(lbo_bytes >> 4) << 16) | ((uint64_t)(sbo_bytes >> 4) << 32) | ((uint64_t)layout << 62);
}
template <int R> __device__ __forceinline__ void reg_alloc() { asm volatile("setmaxnreg.inc.sync.aligned.u32 %0;" :: "n"(R)); }
template <int R> __device__ __forceinline__ void reg_dealloc() { asm volatile("setmaxnreg.dec.sync.aligned.u32 %0;" :: "n"(R)); }
__device__ __forceinline__ void pdl_launch() { asm volatile("griddepcontrol.launch_dependents;" ::: "memory"); }
__device__ __forceinline__ void pdl_wait() { asm volatile("griddepcontrol.wait;" ::: "memory"); }
__device__ __forceinline__ void prefetch_map(const CUtensorMap* m) { asm volatile("prefetch.tensormap [%0];" :: "l"(m) : "memory"); }
__device__ __forceinline__ void named_bar(int id, int n) { asm volatile("bar.sync %0, %1;" :: "r"(id), "r"(n) : "memory"); }

__device__ __forceinline__ void wgmma_m64n128k16_ss(float (&d)[64], uint64_t descA, uint64_t descB, int scaleD) {
    asm volatile("{\n.reg .pred p;\nsetp.ne.b32 p, %66, 0;\n"
        "wgmma.mma_async.sync.aligned.m64n128k16.f32.bf16.bf16 {%0, %1, %2, %3, %4, %5, %6, %7, %8, %9, %10, %11, %12, %13, %14, %15, %16, %17, %18, %19, %20, %21, %22, %23, %24, %25, %26, %27, %28, %29, %30, %31, %32, %33, %34, %35, %36, %37, %38, %39, %40, %41, %42, %43, %44, %45, %46, %47, %48, %49, %50, %51, %52, %53, %54, %55, %56, %57, %58, %59, %60, %61, %62, %63}, %64, %65, p, 1, 1, 0, 1;\n}\n"
        : "+f"(d[0]), "+f"(d[1]), "+f"(d[2]), "+f"(d[3]), "+f"(d[4]), "+f"(d[5]), "+f"(d[6]), "+f"(d[7]), "+f"(d[8]), "+f"(d[9]), "+f"(d[10]), "+f"(d[11]), "+f"(d[12]), "+f"(d[13]), "+f"(d[14]), "+f"(d[15]), "+f"(d[16]), "+f"(d[17]), "+f"(d[18]), "+f"(d[19]), "+f"(d[20]), "+f"(d[21]), "+f"(d[22]), "+f"(d[23]), "+f"(d[24]), "+f"(d[25]), "+f"(d[26]), "+f"(d[27]), "+f"(d[28]), "+f"(d[29]), "+f"(d[30]), "+f"(d[31]), "+f"(d[32]), "+f"(d[33]), "+f"(d[34]), "+f"(d[35]), "+f"(d[36]), "+f"(d[37]), "+f"(d[38]), "+f"(d[39]), "+f"(d[40]), "+f"(d[41]), "+f"(d[42]), "+f"(d[43]), "+f"(d[44]), "+f"(d[45]), "+f"(d[46]), "+f"(d[47]), "+f"(d[48]), "+f"(d[49]), "+f"(d[50]), "+f"(d[51]), "+f"(d[52]), "+f"(d[53]), "+f"(d[54]), "+f"(d[55]), "+f"(d[56]), "+f"(d[57]), "+f"(d[58]), "+f"(d[59]), "+f"(d[60]), "+f"(d[61]), "+f"(d[62]), "+f"(d[63])
        : "l"(descA), "l"(descB), "r"(scaleD));
}

__device__ __forceinline__ void wgmma_m64n64k16_ss(float (&d)[32], uint64_t descA, uint64_t descB, int scaleD) {
    asm volatile("{\n.reg .pred p;\nsetp.ne.b32 p, %34, 0;\n"
        "wgmma.mma_async.sync.aligned.m64n64k16.f32.bf16.bf16 {%0, %1, %2, %3, %4, %5, %6, %7, %8, %9, %10, %11, %12, %13, %14, %15, %16, %17, %18, %19, %20, %21, %22, %23, %24, %25, %26, %27, %28, %29, %30, %31}, %32, %33, p, 1, 1, 0, 1;\n}\n"
        : "+f"(d[0]), "+f"(d[1]), "+f"(d[2]), "+f"(d[3]), "+f"(d[4]), "+f"(d[5]), "+f"(d[6]), "+f"(d[7]), "+f"(d[8]), "+f"(d[9]), "+f"(d[10]), "+f"(d[11]), "+f"(d[12]), "+f"(d[13]), "+f"(d[14]), "+f"(d[15]), "+f"(d[16]), "+f"(d[17]), "+f"(d[18]), "+f"(d[19]), "+f"(d[20]), "+f"(d[21]), "+f"(d[22]), "+f"(d[23]), "+f"(d[24]), "+f"(d[25]), "+f"(d[26]), "+f"(d[27]), "+f"(d[28]), "+f"(d[29]), "+f"(d[30]), "+f"(d[31])
        : "l"(descA), "l"(descB), "r"(scaleD));
}

__device__ __forceinline__ void quad_transpose(uint32_t& r0, uint32_t& r1, uint32_t& r2, uint32_t& r3, int t) {
    const bool o1 = t & 1, o2 = t & 2;
    uint32_t x, y;
    x = o1 ? r0 : r1; y = __shfl_xor_sync(0xffffffffu, x, 1); if (o1) r0 = y; else r1 = y;
    x = o1 ? r2 : r3; y = __shfl_xor_sync(0xffffffffu, x, 1); if (o1) r2 = y; else r3 = y;
    x = o2 ? r0 : r2; y = __shfl_xor_sync(0xffffffffu, x, 2); if (o2) r0 = y; else r2 = y;
    x = o2 ? r1 : r3; y = __shfl_xor_sync(0xffffffffu, x, 2); if (o2) r1 = y; else r3 = y;
}

constexpr int K1_THREADS = 256;
constexpr int UT_PAD = 128;
constexpr int UT_LEN = UT_PAD + S_;
constexpr int KR_LEN = 2080;
constexpr int YP_LEN = S_ + (S_ / 32) * 8;

struct __align__(128) K1Smem {
    bf16 uT[4][UT_LEN];
    bf16 kr[4][2][KR_LEN];
    float yP[4][YP_LEN];
    uint64_t bar;
    uint8_t pad[32768];
};

__device__ __forceinline__ void mma16816(float (&c)[4], uint32_t a0, uint32_t a1, uint32_t a2, uint32_t a3, uint32_t b0, uint32_t b1) {
    asm("mma.sync.aligned.m16n8k16.row.col.f32.bf16.bf16.f32 {%0,%1,%2,%3}, {%4,%5,%6,%7}, {%8,%9}, {%0,%1,%2,%3};"
        : "+f"(c[0]), "+f"(c[1]), "+f"(c[2]), "+f"(c[3])
        : "r"(a0), "r"(a1), "r"(a2), "r"(a3), "r"(b0), "r"(b1));
}
__device__ __forceinline__ void ldsm_x4(uint32_t& r0, uint32_t& r1, uint32_t& r2, uint32_t& r3, uint32_t addr) {
    asm volatile("ldmatrix.sync.aligned.m8n8.x4.shared.b16 {%0,%1,%2,%3}, [%4];" : "=r"(r0), "=r"(r1), "=r"(r2), "=r"(r3) : "r"(addr) : "memory");
}

__device__ __forceinline__ void conv_mma(const bf16* uTc, const bf16* krlane, float (&acc)[16][4], int lane, int half) {
    const int lrow = lane & 7, lk = (lane >> 3) & 1, lt = lane >> 4;
    const uint32_t ubase = smem_u32(uTc) + (UT_PAD + 16 * (8 * lt + lrow) + 8 * lk) * 2;
#pragma unroll 1
    for (int pp = 0; pp < 4; pp++) {
        const int p = half * 4 + pp;
        uint32_t U[16][2];
#pragma unroll
        for (int j = 0; j < 16; j += 2) ldsm_x4(U[j][0], U[j][1], U[j + 1][0], U[j + 1][1], ubase + (j * 128 - p * 16) * 2);
        const uint32_t* kp = reinterpret_cast<const uint32_t*>(krlane - 16 * p);
        const volatile uint32_t* kpv = kp;
        uint32_t a0 = kp[0], a1 = kp[-4], a2 = kp[4], a3 = kpv[0];
#pragma unroll
        for (int q = 0; q < 16; q++) {
            uint32_t b0 = 0, b1 = 0, b2 = 0, b3 = 0;
            if (q < 15) { b0 = kp[-64 * (q + 1)]; b1 = kp[-64 * (q + 1) - 4]; b2 = kp[-64 * (q + 1) + 4]; b3 = kpv[-64 * (q + 1)]; }
#pragma unroll
            for (int n = 15; n >= q; n--) mma16816(acc[n], a0, a1, a2, a3, U[n - q][0], U[n - q][1]);
            a0 = b0; a1 = b1; a2 = b2; a3 = b3;
        }
    }
}

__global__ void __cluster_dims__(2, 1, 1) __launch_bounds__(K1_THREADS, 1)
conv_kernel(const bf16* __restrict__ k, const bf16* __restrict__ v,
            const bf16* __restrict__ shift_k, const bf16* __restrict__ ssm_k, const bf16* __restrict__ ssm_D) {
    extern __shared__ __align__(1024) uint8_t smem_raw[];
    pdl_launch();
    K1Smem& sm = *reinterpret_cast<K1Smem*>(smem_raw);
    const int tid = threadIdx.x, lane = tid & 31, warp = tid >> 5;
    const int bid = blockIdx.x;
    const int rank = bid & 1;
    const int c0 = 8 * (bid >> 1);
    const int cown = c0 + 4 * rank;
#define TMT 0
    TM(0, 0);
    const uint32_t bar = smem_u32(&sm.bar);
    if (tid == 0) {
        mbar_init(bar, 1);
        asm volatile("fence.mbarrier_init.release.cluster;" ::: "memory");
        mbar_expect_tx(bar, 1024 * 4 * 2);
    }
    cluster_arrive_relaxed();

    const int s0 = 1024 * rank + 4 * tid;
    uint4 kk[7], vv[4], sw[4];
#pragma unroll
    for (int i = 0; i < 4; i++) kk[3 + i] = ldg128(k + (size_t)(s0 + i) * D_ + c0);
#pragma unroll
    for (int i = 0; i < 4; i++) vv[i] = ldg128(v + (size_t)(s0 + i) * D_ + c0);
    if (lane == 0) {
#pragma unroll
        for (int i = 0; i < 3; i++) {
            const int s = s0 - 3 + i;
            kk[i] = make_uint4(0, 0, 0, 0);
            if (s >= 0) kk[i] = ldg128(k + (size_t)s * D_ + c0);
        }
    }
#pragma unroll
    for (int i = 0; i < 4; i++) sw[i] = ldg128(shift_k + (size_t)c0 * 4 + 8 * i);
    uint4 kq[4]; uint32_t nx[4];
#pragma unroll
    for (int c = 0; c < 4; c++) {
        const bf16* kr = ssm_k + (size_t)(cown + c) * S_;
        kq[c] = ldg128(kr + 8 * tid);
        nx[c] = 0u;
        if (tid < 255) nx[c] = ldg16(kr + 8 * tid + 8);
    }
    const uint32_t dval = ldg16(ssm_D + cown + (warp >> 1));
    if (tid < 64) *reinterpret_cast<uint4*>(&sm.uT[tid >> 4][(tid & 15) * 8]) = make_uint4(0, 0, 0, 0);
#pragma unroll
    for (int i = 0; i < 3; i++) {
        uint4 t;
        t.x = __shfl_up_sync(0xffffffffu, kk[4 + i].x, 1); t.y = __shfl_up_sync(0xffffffffu, kk[4 + i].y, 1);
        t.z = __shfl_up_sync(0xffffffffu, kk[4 + i].z, 1); t.w = __shfl_up_sync(0xffffffffu, kk[4 + i].w, 1);
        if (lane != 0) kk[i] = t;
    }
    uint32_t kvw[4][4];
    const uint32_t* kkw = reinterpret_cast<const uint32_t*>(kk);
    const uint32_t* vvw = reinterpret_cast<const uint32_t*>(vv);
#pragma unroll
    for (int i2 = 0; i2 < 4; i2++) {
        const uint32_t t0 = __byte_perm(sw[i2].x, sw[i2].z, 0x5410), t1 = __byte_perm(sw[i2].x, sw[i2].z, 0x7632);
        const uint32_t t2 = __byte_perm(sw[i2].y, sw[i2].w, 0x5410), t3 = __byte_perm(sw[i2].y, sw[i2].w, 0x7632);
#pragma unroll
        for (int r = 0; r < 4; r++) {
            uint32_t a = hmul2(kkw[(r + 0) * 4 + i2], t3);
            a = hadd2(a, hmul2(kkw[(r + 1) * 4 + i2], t2));
            a = hadd2(a, hmul2(kkw[(r + 2) * 4 + i2], t1));
            a = hadd2(a, hmul2(kkw[(r + 3) * 4 + i2], t0));
            kvw[r][i2] = hmul2(a, vvw[r * 4 + i2]);
        }
    }
    TM(0, 1);
    cluster_wait();
    {
        const uint32_t rbar = mapa(bar, (uint32_t)(rank ^ 1));
#pragma unroll
        for (int i2 = 0; i2 < 4; i2++) {
#pragma unroll
            for (int e = 0; e < 2; e++) {
                const uint32_t sel = e ? 0x7632 : 0x5410;
                const uint32_t w0 = __byte_perm(kvw[0][i2], kvw[1][i2], sel), w1 = __byte_perm(kvw[2][i2], kvw[3][i2], sel);
                const int cc = 2 * i2 + e;
                if ((cc >> 2) == rank) {
                    *reinterpret_cast<uint2*>(&sm.uT[cc & 3][UT_PAD + s0]) = make_uint2(w0, w1);
                } else {
                    st_async_v2(mapa(smem_u32(&sm.uT[cc & 3][UT_PAD + s0]), (uint32_t)(rank ^ 1)), w0, w1, rbar);
                }
            }
        }
    }
#pragma unroll
    for (int c = 0; c < 4; c++) {
        uint4 a, b;
        a.x = __byte_perm(kq[c].w, 0, 0x1032); a.y = __byte_perm(kq[c].z, 0, 0x1032);
        a.z = __byte_perm(kq[c].y, 0, 0x1032); a.w = __byte_perm(kq[c].x, 0, 0x1032);
        b.x = __byte_perm(nx[c], kq[c].w, 0x7610); b.y = __byte_perm(kq[c].w, kq[c].z, 0x7610);
        b.z = __byte_perm(kq[c].z, kq[c].y, 0x7610); b.w = __byte_perm(kq[c].y, kq[c].x, 0x7610);
        *reinterpret_cast<uint4*>(&sm.kr[c][0][2040 - 8 * tid]) = a;
        *reinterpret_cast<uint4*>(&sm.kr[c][1][2040 - 8 * tid]) = b;
        if (tid == 0) {
            *reinterpret_cast<uint4*>(&sm.kr[c][1][2048]) = make_uint4(kq[c].x & 0xffffu, 0, 0, 0);
        } else if (tid < 8) {
            if (tid < 4) *reinterpret_cast<uint4*>(&sm.kr[c][1][2048 + 8 * tid]) = make_uint4(0, 0, 0, 0);
            else *reinterpret_cast<uint4*>(&sm.kr[c][0][2048 + 8 * (tid - 4)]) = make_uint4(0, 0, 0, 0);
        }
    }
    TM(0, 3);
    __syncthreads();
    mbar_wait_cluster(bar, 0);
    TM(0, 4);

    const int ch = warp >> 1, half = warp & 1;
    const int g = lane >> 2, t = lane & 3;
    float acc[16][4];
#pragma unroll
    for (int i = 0; i < 16; i++) { acc[i][0] = acc[i][1] = acc[i][2] = acc[i][3] = 0.f; }
    const bf16* krlane = (g & 1) ? &sm.kr[ch][0][2047 - g + 2 * t] : &sm.kr[ch][1][2048 - g + 2 * t];
    conv_mma(sm.uT[ch], krlane, acc, lane, half);
    TM(0, 5);
    float* yp = &sm.yP[ch][40 * t + g];
    if (half) {
#pragma unroll
        for (int n = 0; n < 16; n++) {
            yp[160 * n] = acc[n][0];
            yp[160 * n + 16] = acc[n][1];
            yp[160 * n + 8] = acc[n][2];
            yp[160 * n + 24] = acc[n][3];
        }
    }
    named_bar(1 + ch, 64);
    if (!half) {
#pragma unroll
        for (int n = 0; n < 16; n++) {
            yp[160 * n] += acc[n][0];
            yp[160 * n + 16] += acc[n][1];
            yp[160 * n + 8] += acc[n][2];
            yp[160 * n + 24] += acc[n][3];
        }
    }
    named_bar(1 + ch, 64);
    TM(0, 6);
    {
        const int tt = tid & 63;
        bf16* dst = g_yT + (size_t)(cown + ch) * S_;
        const uint32_t d2 = dval * 0x10001u;
#pragma unroll
        for (int j = 0; j < 4; j++) {
            const int s = (j * 64 + tt) * 8;
            const float* src = &sm.yP[ch][s + (s >> 5) * 8];
            const float4 a = *reinterpret_cast<const float4*>(src), b = *reinterpret_cast<const float4*>(src + 4);
            const uint4 kv4 = *reinterpret_cast<const uint4*>(&sm.uT[ch][UT_PAD + s]);
            *reinterpret_cast<uint4*>(dst + s) = make_uint4(hadd2(pack_bf16(a.x, a.y), hmul2(kv4.x, d2)), hadd2(pack_bf16(a.z, a.w), hmul2(kv4.y, d2)),
                                                            hadd2(pack_bf16(b.x, b.y), hmul2(kv4.z, d2)), hadd2(pack_bf16(b.z, b.w), hmul2(kv4.w, d2)));
        }
    }
    TM(0, 7);
#undef TMT
}

constexpr int R_THREADS = 512;
constexpr int R_ROWS = 16;

__device__ __forceinline__ float warp_sum(float s) {
#pragma unroll
    for (int o = 16; o > 0; o >>= 1) s += __shfl_xor_sync(0xffffffffu, s, o);
    return s;
}
__device__ __forceinline__ uint32_t hsub2(uint32_t a, uint32_t b) {
    __nv_bfloat162 r = __hsub2_rn(*reinterpret_cast<__nv_bfloat162*>(&a), *reinterpret_cast<__nv_bfloat162*>(&b));
    return *reinterpret_cast<uint32_t*>(&r);
}
__device__ __forceinline__ void ln_row(const uint32_t (&x)[8], uint32_t (&o)[8]) {
    float s0 = 0.f, s1 = 0.f;
#pragma unroll
    for (int i = 0; i < 8; i++) { s0 += bf_lo(x[i]); s1 += bf_hi(x[i]); }
    const float mean = warp_sum(s0 + s1) * (1.0f / D_);
    float ss0 = 0.f, ss1 = 0.f;
#pragma unroll
    for (int i = 0; i < 8; i++) { const float d0 = bf_lo(x[i]) - mean, d1 = bf_hi(x[i]) - mean; ss0 += d0 * d0; ss1 += d1 * d1; }
    const float var = bf16r(warp_sum(ss0 + ss1) * (1.0f / D_));
    const float rinv = 1.0f / bf16r(sqrtf(bf16r(var + 1e-5f)));
    const uint32_t m2 = pack_bf16(mean, mean);
#pragma unroll
    for (int i = 0; i < 8; i++) {
        const uint32_t d = hsub2(x[i], m2);
        o[i] = pack_bf16(bf_lo(d) * rinv, bf_hi(d) * rinv);
    }
}

__global__ void __launch_bounds__(R_THREADS, 1)
row_kernel(const bf16* __restrict__ q) {
    __shared__ __align__(16) uint32_t ys[R_ROWS][D_ / 2 + 4];
    const int tid = threadIdx.x, lane = tid & 31, warp = tid >> 5;
    const int s0 = blockIdx.x * R_ROWS;
#define TMT 0
    TM(1, 0);
    pdl_launch();
    const int r0 = s0 + warp;
    const int p = tid & 255, hs = tid >> 8;
    const uint4 qa = ldg128(q + (size_t)r0 * D_ + 8 * lane);
    const uint4 qb = ldg128(q + (size_t)r0 * D_ + 8 * (lane + 32));
    const uint32_t x[8] = {qa.x, qa.y, qa.z, qa.w, qb.x, qb.y, qb.z, qb.w};
    uint32_t qn[8];
    ln_row(x, qn);
    pdl_wait();
    {
        const bf16* y0 = g_yT + (size_t)(2 * p) * S_ + s0 + 8 * hs;
        const uint4 ya = ldcg128(y0);
        const uint4 yb = ldcg128(y0 + S_);
        const uint32_t aw[4] = {ya.x, ya.y, ya.z, ya.w};
        const uint32_t bw[4] = {yb.x, yb.y, yb.z, yb.w};
#pragma unroll
        for (int j = 0; j < 4; j++) {
            ys[8 * hs + 2 * j][p] = __byte_perm(aw[j], bw[j], 0x5410);
            ys[8 * hs + 2 * j + 1][p] = __byte_perm(aw[j], bw[j], 0x7632);
        }
    }
    __syncthreads();
    TM(1, 1);
    uint32_t h[8], hn[8];
#pragma unroll
    for (int i = 0; i < 2; i++) {
        const uint4 yw4 = *reinterpret_cast<const uint4*>(&ys[warp][4 * (lane + 32 * i)]);
        const uint32_t yw[4] = {yw4.x, yw4.y, yw4.z, yw4.w};
#pragma unroll
        for (int j = 0; j < 4; j++) h[4 * i + j] = hadd2(x[4 * i + j], hmul2(qn[4 * i + j], yw[j]));
    }
    ln_row(h, hn);
#pragma unroll
    for (int i = 0; i < 2; i++) {
        const size_t off = (size_t)r0 * D_ + 8 * (lane + 32 * i);
        *reinterpret_cast<uint4*>(g_h + off) = make_uint4(h[4 * i], h[4 * i + 1], h[4 * i + 2], h[4 * i + 3]);
        *reinterpret_cast<uint4*>(g_hn + off) = make_uint4(hn[4 * i], hn[4 * i + 1], hn[4 * i + 2], hn[4 * i + 3]);
    }
    TM(1, 2);
#undef TMT
}

constexpr int G1_THREADS = 384;
constexpr int G1_STAGES = 6;
constexpr int G1_A_BYTES = 8 * 16384;
constexpr int G1_B_STAGE = 16384;
constexpr int G1_OFF_B = G1_A_BYTES;
constexpr int G1_OFF_BAR = G1_OFF_B + G1_STAGES * G1_B_STAGE;
constexpr int G1_SMEM = G1_OFF_BAR + 256;

__device__ __forceinline__ float sigmoid_fast(float x) {
    float t; asm("tanh.approx.f32 %0, %1;" : "=f"(t) : "f"(0.5f * x));
    return fmaf(t, 0.5f, 0.5f);
}

template <int NT>
__device__ __forceinline__ void g1_epilogue(const float (&acc)[NT * 8], bf16* out0, int t) {
#pragma unroll
    for (int j0 = 0; j0 < NT; j0 += 4) {
        uint32_t P0[4], P1[4];
#pragma unroll
        for (int jj = 0; jj < 4; jj++) {
            const int j = j0 + jj;
            float r[4];
#pragma unroll
            for (int e = 0; e < 4; e++) r[e] = sigmoid_fast(acc[4 * j + e]) * acc[4 * (NT + j) + e];
            P0[jj] = pack_bf16(r[0], r[1]);
            P1[jj] = pack_bf16(r[2], r[3]);
        }
        quad_transpose(P0[0], P0[1], P0[2], P0[3], t);
        quad_transpose(P1[0], P1[1], P1[2], P1[3], t);
        *reinterpret_cast<uint4*>(out0 + 8 * (j0 + t)) = make_uint4(P0[0], P0[1], P0[2], P0[3]);
        *reinterpret_cast<uint4*>(out0 + 8 * F_ + 8 * (j0 + t)) = make_uint4(P1[0], P1[1], P1[2], P1[3]);
    }
}

__host__ __device__ constexpr int g1_parity(int it) {
    int cnt = 0;
    for (int j = 0; j < it; j++) if ((((j >> 3) ^ (it >> 3)) & 1) == 0 && (j % G1_STAGES) == (it % G1_STAGES)) cnt++;
    return cnt & 1;
}
template <int NT, int U>
__device__ __forceinline__ void g1_unit(uint32_t sb, uint32_t barA, uint32_t barF, uint32_t barE, uint32_t peer, int tl, bf16* outp, int t) {
    float acc[2][NT * 8];
#pragma unroll
    for (int kc = 0; kc < 8; kc++) {
        const int it = 8 * U + kc;
        const int st = it % G1_STAGES, ph = g1_parity(it);
        if (U < 2) mbar_wait(barA + 8 * kc, 0);
        mbar_wait(barF + 8 * st, ph);
        if (tl == 0) TR(1, it);
        wgmma_fence();
        const uint32_t aaddr = sb + kc * 16384;
        const uint32_t baddr = sb + G1_OFF_B + st * G1_B_STAGE;
#pragma unroll
        for (int kk = 0; kk < 4; kk++) {
#pragma unroll
            for (int hf = 0; hf < 2; hf++) {
                if constexpr (NT == 8)
                    wgmma_m64n128k16_ss(acc[hf], make_desc(aaddr + hf * 8192 + kk * 32, 16, 1024, 1), make_desc(baddr + kk * 2048, 8192, 1024, 1), (kc | kk) != 0);
                else
                    wgmma_m64n64k16_ss(acc[hf], make_desc(aaddr + hf * 8192 + kk * 32, 16, 1024, 1), make_desc(baddr + kk * 1024, 4096, 512, 2), (kc | kk) != 0);
            }
        }
        wgmma_commit();
        if (kc > 0) {
            wgmma_wait<1>();
            const int pst = (it - 1) % G1_STAGES;
            if (tl == 0) mbar_arrive(barE + 8 * pst);
        }
    }
    wgmma_wait<0>();
    {
        const int pst = (8 * U + 7) % G1_STAGES;
        if (tl == 0) mbar_arrive(barE + 8 * pst);
    }
    if (tl == 0) TR(2, U);
    g1_epilogue<NT>(acc[0], outp + 64 * U, t);
    g1_epilogue<NT>(acc[1], outp + 64 * U + (size_t)64 * F_, t);
    if (tl == 0) TR(2, 4 + U);
}

__global__ void __cluster_dims__(2, 1, 1) __launch_bounds__(G1_THREADS, 1)
gemm1_kernel(const __grid_constant__ CUtensorMap mapA, const __grid_constant__ CUtensorMap mapG64, const __grid_constant__ CUtensorMap mapU64,
             const __grid_constant__ CUtensorMap mapG32, const __grid_constant__ CUtensorMap mapU32) {
    extern __shared__ __align__(1024) uint8_t smem_raw[];
    const uint32_t sb = smem_u32(smem_raw);
    const int tid = threadIdx.x, lane = tid & 31, warp = tid >> 5, wgi = tid >> 7;
    const int rank = blockIdx.x & 1;
    const int cb = blockIdx.x & 7, rb = blockIdx.x >> 3;
#define TMT 128
    TM(2, 0);
    pdl_launch();
    if (tid == 32) { prefetch_map(&mapA); prefetch_map(&mapG64); prefetch_map(&mapU64); prefetch_map(&mapG32); prefetch_map(&mapU32); }
    const uint32_t barA = sb + G1_OFF_BAR;
    const uint32_t barF = barA + 64;
    const uint32_t barE = barF + 16 * G1_STAGES;
    if (tid == 0) {
        for (int i = 0; i < 8; i++) mbar_init(barA + 8 * i, 1);
        for (int i = 0; i < G1_STAGES; i++) { mbar_init(barF + 8 * i, 1); mbar_init(barF + 8 * G1_STAGES + 8 * i, 1); mbar_init(barE + 8 * i, 1); }
        for (int i = 0; i < 8; i++) mbar_expect_tx(barA + 8 * i, 16384);
        asm volatile("fence.mbarrier_init.release.cluster;" ::: "memory");
    }
    __syncthreads();
    cluster_arrive_relaxed();
    cluster_wait();

    if (wgi == 0) {
        reg_dealloc<40>();
        if (lane == 0 && warp < 2) {
            const CUtensorMap* m64 = warp ? &mapU64 : &mapG64;
            const CUtensorMap* m32 = warp ? &mapU32 : &mapG32;
            int st = 0, ph = 1;
            for (int it = 0; it < 32; it++) {
                const int kc = it & 7, u = it >> 3;
                mbar_wait(barE + 8 * st, ph);
                const uint32_t dst = sb + G1_OFF_B + st * G1_B_STAGE;
                const uint32_t bf = barF + (u & 1) * 8 * G1_STAGES + 8 * st;
                if (u < 3) {
                    if (warp == 0) mbar_expect_tx(bf, 16384);
                    tma_load_2d(dst + warp * 8192, m64, bf, cb * 224 + 64 * u, kc * 64);
                } else {
                    if (warp == 0) mbar_expect_tx(bf, 8192);
                    tma_load_2d(dst + warp * 4096, m32, bf, cb * 224 + 192, kc * 64);
                }
                if (++st == G1_STAGES) { st = 0; ph ^= 1; }
            }
        } else if (lane == 0 && warp == 2) {
            pdl_wait();
            for (int i = 0; i < 4; i++) {
                const int c = 2 * i + rank;
                tma_load_2d_mc(sb + c * 16384, &mapA, barA + 8 * c, c * 64, rb * 128, (uint16_t)3);
            }
        }
        __syncwarp();
    } else {
        reg_alloc<232>();
        pdl_wait();
        const int g = lane >> 2, t = lane & 3, wl = warp & 3, tl = tid & 127;
        bf16* outp = g_hh + (size_t)(rb * 128 + wl * 16 + g) * F_ + cb * 224;
        const uint32_t peer = (uint32_t)(rank ^ 1);
        if (wgi == 1) {
            g1_unit<8, 0>(sb, barA, barF, barE, peer, tl, outp, t);
            TM(2, 1);
            g1_unit<8, 2>(sb, barA, barF, barE, peer, tl, outp, t);
            TM(2, 2);
        } else {
            g1_unit<8, 1>(sb, barA, barF + 8 * G1_STAGES, barE, peer, tl, outp, t);
            g1_unit<4, 3>(sb, barA, barF + 8 * G1_STAGES, barE, peer, tl, outp, t);
        }
    }
    cluster_arrive_relaxed();
    cluster_wait();
    TM(2, 3);
}

constexpr int G2_THREADS = 384;
constexpr int G2_STAGES = 6;
constexpr int G2_STAGE = 32768;
constexpr int G2_OFF_X = G2_STAGES * G2_STAGE;
constexpr int G2_OFF_BAR = G2_OFF_X + 32768;
constexpr int G2_SMEM = G2_OFF_BAR + 128;
constexpr int G2_KSTEPS = 14;

__global__ void __cluster_dims__(2, 1, 1) __launch_bounds__(G2_THREADS, 1)
gemm2_kernel(const __grid_constant__ CUtensorMap mapHH, const __grid_constant__ CUtensorMap mapWd, bf16* __restrict__ out) {
    extern __shared__ __align__(1024) uint8_t smem_raw[];
    const uint32_t sb = smem_u32(smem_raw);
    const int tid = threadIdx.x, lane = tid & 31, warp = tid >> 5, wgi = tid >> 7;
    const int ks = blockIdx.x & 1, nb = (blockIdx.x >> 1) & 3, rb = blockIdx.x >> 3;
    TM(3, 0);
    if (tid == 32) { prefetch_map(&mapHH); prefetch_map(&mapWd); }
    const uint32_t barF = sb + G2_OFF_BAR;
    const uint32_t barE = barF + 8 * G2_STAGES;
    const uint32_t barX = barE + 8 * G2_STAGES;
    if (tid == 0) {
        for (int i = 0; i < G2_STAGES; i++) { mbar_init(barF + 8 * i, 1); mbar_init(barE + 8 * i, 2); }
        mbar_init(barX, 1);
        asm volatile("fence.mbarrier_init.release.cluster;" ::: "memory");
        mbar_expect_tx(barX, 32768);
    }
    __syncthreads();
    cluster_arrive_relaxed();

    if (wgi == 0) {
        if (tid == 0) {
            for (int it = 0; it < G2_STAGES; it++) {
                mbar_expect_tx(barF + 8 * it, 32768);
                tma_load_3d(sb + it * G2_STAGE + 16384, &mapWd, barF + 8 * it, 0, ks * 896 + it * 64, nb * 2);
            }
            pdl_wait();
            for (int it = 0; it < G2_STAGES; it++)
                tma_load_2d(sb + it * G2_STAGE, &mapHH, barF + 8 * it, ks * 896 + it * 64, rb * 128);
            int st = 0, ph = 0;
            for (int it = G2_STAGES; it < G2_KSTEPS; it++) {
                mbar_wait(barE + 8 * st, ph);
                const uint32_t dst = sb + st * G2_STAGE;
                const int k0 = ks * 896 + it * 64;
                mbar_expect_tx(barF + 8 * st, 32768);
                tma_load_2d(dst, &mapHH, barF + 8 * st, k0, rb * 128);
                tma_load_3d(dst + 16384, &mapWd, barF + 8 * st, 0, k0, nb * 2);
                if (++st == G2_STAGES) { st = 0; ph ^= 1; }
            }
        }
        __syncwarp();
        cluster_wait();
    } else {
        const int cw = wgi - 1;
        const int g = lane >> 2, t = lane & 3, wl = warp & 3;
        const int tl = tid & 127;
        int st = 0, ph = 0;
        float acc[64];
        pdl_wait();
#pragma unroll 1
        for (int it = 0; it < G2_KSTEPS; it++) {
            mbar_wait(barF + 8 * st, ph);
            if (it == 0) TM(3, 1);
            wgmma_fence();
            const uint32_t aaddr = sb + st * G2_STAGE + cw * 8192;
            const uint32_t baddr = sb + st * G2_STAGE + 16384;
#pragma unroll
            for (int kk = 0; kk < 4; kk++)
                wgmma_m64n128k16_ss(acc, make_desc(aaddr + kk * 32, 16, 1024, 1), make_desc(baddr + kk * 2048, 8192, 1024, 1), (it | kk) != 0);
            wgmma_commit();
            wgmma_wait<0>();
            if (tl == 0) mbar_arrive(barE + 8 * st);
            if (++st == G2_STAGES) { st = 0; ph ^= 1; }
        }
        TM(3, 2);
        cluster_wait();
        if (cw != ks) {
            const uint32_t dst = mapa(sb + G2_OFF_X + tl * 16, (uint32_t)(ks ^ 1));
            const uint32_t rbar = mapa(barX, (uint32_t)(ks ^ 1));
#pragma unroll
            for (int i = 0; i < 16; i++) st_async_v4f(dst + i * 2048, acc[4 * i], acc[4 * i + 1], acc[4 * i + 2], acc[4 * i + 3], rbar);
        } else {
            const float4* xb = reinterpret_cast<const float4*>(smem_raw + G2_OFF_X) + tl;
            const int row0 = rb * 128 + cw * 64 + wl * 16 + g;
            const bf16* h0 = g_h + (size_t)row0 * D_ + nb * 128;
            bf16* o0 = out + (size_t)row0 * D_ + nb * 128;
            uint32_t ha[16], hb[16];
#pragma unroll
            for (int j = 0; j < 16; j++) {
                ha[j] = __ldcg(reinterpret_cast<const uint32_t*>(h0 + 8 * j + 2 * t));
                hb[j] = __ldcg(reinterpret_cast<const uint32_t*>(h0 + 8 * D_ + 8 * j + 2 * t));
            }
            mbar_wait_cluster(barX, 0);
            TM(3, 4);
#pragma unroll
            for (int j0 = 0; j0 < 16; j0 += 4) {
                uint32_t P0[4], P1[4];
#pragma unroll
                for (int jj = 0; jj < 4; jj++) {
                    const int j = j0 + jj;
                    const float4 x = xb[j * 128];
                    P0[jj] = pack_bf16(bf_lo(ha[j]) + bf16r(acc[4 * j] + x.x), bf_hi(ha[j]) + bf16r(acc[4 * j + 1] + x.y));
                    P1[jj] = pack_bf16(bf_lo(hb[j]) + bf16r(acc[4 * j + 2] + x.z), bf_hi(hb[j]) + bf16r(acc[4 * j + 3] + x.w));
                }
                quad_transpose(P0[0], P0[1], P0[2], P0[3], t);
                quad_transpose(P1[0], P1[1], P1[2], P1[3], t);
                *reinterpret_cast<uint4*>(o0 + 8 * (j0 + t)) = make_uint4(P0[0], P0[1], P0[2], P0[3]);
                *reinterpret_cast<uint4*>(o0 + 8 * D_ + 8 * (j0 + t)) = make_uint4(P1[0], P1[1], P1[2], P1[3]);
            }
        }
        TM(3, 5);
    }
#undef TMT
}

typedef CUresult (*EncodeFn)(CUtensorMap*, CUtensorMapDataType, cuuint32_t, void*, const cuuint64_t*, const cuuint64_t*,
                             const cuuint32_t*, const cuuint32_t*, CUtensorMapInterleave, CUtensorMapSwizzle,
                             CUtensorMapL2promotion, CUtensorMapFloatOOBfill);

static void enc2d(EncodeFn enc, CUtensorMap* m, const void* p, int rows, int cols, int brows, int bcols) {
    cuuint64_t dims[2] = {(cuuint64_t)cols, (cuuint64_t)rows};
    cuuint64_t strides[1] = {(cuuint64_t)cols * 2};
    cuuint32_t box[2] = {(cuuint32_t)bcols, (cuuint32_t)brows};
    cuuint32_t es[2] = {1, 1};
    enc(m, CU_TENSOR_MAP_DATA_TYPE_BFLOAT16, 2, const_cast<void*>(p), dims, strides, box, es, CU_TENSOR_MAP_INTERLEAVE_NONE,
        bcols == 32 ? CU_TENSOR_MAP_SWIZZLE_64B : CU_TENSOR_MAP_SWIZZLE_128B, CU_TENSOR_MAP_L2_PROMOTION_L2_128B, CU_TENSOR_MAP_FLOAT_OOB_FILL_NONE);
}
static void enc3d(EncodeFn enc, CUtensorMap* m, const void* p, int rows, int cols, int atom, int brows, int natoms) {
    cuuint64_t dims[3] = {(cuuint64_t)atom, (cuuint64_t)rows, (cuuint64_t)(cols / atom)};
    cuuint64_t strides[2] = {(cuuint64_t)cols * 2, (cuuint64_t)atom * 2};
    cuuint32_t box[3] = {(cuuint32_t)atom, (cuuint32_t)brows, (cuuint32_t)natoms};
    cuuint32_t es[3] = {1, 1, 1};
    enc(m, CU_TENSOR_MAP_DATA_TYPE_BFLOAT16, 3, const_cast<void*>(p), dims, strides, box, es, CU_TENSOR_MAP_INTERLEAVE_NONE,
        atom == 32 ? CU_TENSOR_MAP_SWIZZLE_64B : CU_TENSOR_MAP_SWIZZLE_128B, CU_TENSOR_MAP_L2_PROMOTION_L2_128B, CU_TENSOR_MAP_FLOAT_OOB_FILL_NONE);
}

extern "C" void kernel_launch(void* const* d_in, const int* in_sizes, int n_in, void* d_out, int out_size) {
    const bf16* q = (const bf16*)d_in[0];
    const bf16* k = (const bf16*)d_in[1];
    const bf16* v = (const bf16*)d_in[2];
    const bf16* shift_k = (const bf16*)d_in[3];
    const bf16* ssm_k = (const bf16*)d_in[4];
    const bf16* ssm_D = (const bf16*)d_in[5];
    const bf16* wg = (const bf16*)d_in[7];
    const bf16* wu = (const bf16*)d_in[8];
    const bf16* wd = (const bf16*)d_in[9];
    bf16* out = (bf16*)d_out;

    static EncodeFn enc = nullptr;
    static void *p_hn = nullptr, *p_hh = nullptr;
    if (!enc) {
        void* fn = nullptr; cudaDriverEntryPointQueryResult qr;
        cudaGetDriverEntryPoint("cuTensorMapEncodeTiled", &fn, cudaEnableDefault, &qr);
        enc = (EncodeFn)fn;
        cudaGetSymbolAddress(&p_hn, g_hn);
        cudaGetSymbolAddress(&p_hh, g_hh);
        cudaFuncSetAttribute(conv_kernel, cudaFuncAttributeMaxDynamicSharedMemorySize, (int)sizeof(K1Smem));
        cudaFuncSetAttribute(gemm1_kernel, cudaFuncAttributeMaxDynamicSharedMemorySize, G1_SMEM);
        cudaFuncSetAttribute(gemm2_kernel, cudaFuncAttributeMaxDynamicSharedMemorySize, G2_SMEM);
    }
    CUtensorMap mA, mG64, mU64, mG32, mU32, mHH, mWd;
    enc2d(enc, &mA, p_hn, S_, D_, 128, 64);
    enc2d(enc, &mG64, wg, D_, F_, 64, 64);
    enc2d(enc, &mU64, wu, D_, F_, 64, 64);
    enc2d(enc, &mG32, wg, D_, F_, 64, 32);
    enc2d(enc, &mU32, wu, D_, F_, 64, 32);
    enc2d(enc, &mHH, p_hh, S_, F_, 128, 64);
    enc3d(enc, &mWd, wd, F_, D_, 64, 64, 2);

    cudaStream_t st = cudaStreamPerThread;
    cudaLaunchAttribute at[1];
    at[0].id = cudaLaunchAttributeProgrammaticStreamSerialization;
    at[0].val.programmaticStreamSerializationAllowed = 1;
    cudaLaunchConfig_t cfg = {};
    cfg.stream = st; cfg.attrs = at; cfg.numAttrs = 1;
    conv_kernel<<<128, K1_THREADS, sizeof(K1Smem), st>>>(k, v, shift_k, ssm_k, ssm_D);
    cfg.gridDim = dim3(S_ / R_ROWS); cfg.blockDim = dim3(R_THREADS); cfg.dynamicSmemBytes = 0;
    cudaLaunchKernelEx(&cfg, row_kernel, q);
    cfg.gridDim = dim3(128); cfg.blockDim = dim3(G1_THREADS); cfg.dynamicSmemBytes = G1_SMEM;
    cudaLaunchKernelEx(&cfg, gemm1_kernel, mA, mG64, mU64, mG32, mU32);
    cfg.gridDim = dim3(128); cfg.blockDim = dim3(G2_THREADS); cfg.dynamicSmemBytes = G2_SMEM;
    cudaLaunchKernelEx(&cfg, gemm2_kernel, mHH, mWd, out);
}
```

```cpp
#include <cuda_runtime.h>
#include <cuda_bf16.h>
#include <cuda.h>
#include <stdint.h>

typedef __nv_bfloat16 bf16;
constexpr int S_ = 2048, D_ = 512, F_ = 1792;

__device__ bf16 g_yT[D_ * S_];
__device__ bf16 g_h[S_ * D_];
__device__ bf16 g_hn[S_ * D_];
__device__ bf16 g_hh[S_ * F_];

#define TM(k, i)
#define TR(k, i)
__device__ __forceinline__ uint32_t smem_u32(const void* p) { return (uint32_t)__cvta_generic_to_shared(p); }
__device__ __forceinline__ float bf16r(float x) { return __bfloat162float(__float2bfloat16_rn(x)); }
__device__ __forceinline__ float bf_lo(uint32_t w) { return __uint_as_float(w << 16); }
__device__ __forceinline__ float bf_hi(uint32_t w) { return __uint_as_float(w & 0xffff0000u); }
__device__ __forceinline__ uint32_t pack_bf16(float lo, float hi) {
    __nv_bfloat162 v = __floats2bfloat162_rn(lo, hi);
    return *reinterpret_cast<uint32_t*>(&v);
}
__device__ __forceinline__ uint32_t hmul2(uint32_t a, uint32_t b) {
    __nv_bfloat162 r = __hmul2_rn(*reinterpret_cast<__nv_bfloat162*>(&a), *reinterpret_cast<__nv_bfloat162*>(&b));
    return *reinterpret_cast<uint32_t*>(&r);
}
__device__ __forceinline__ uint32_t hadd2(uint32_t a, uint32_t b) {
    __nv_bfloat162 r = __hadd2_rn(*reinterpret_cast<__nv_bfloat162*>(&a), *reinterpret_cast<__nv_bfloat162*>(&b));
    return *reinterpret_cast<uint32_t*>(&r);
}
__device__ __forceinline__ uint4 ldg128(const void* p) {
    uint4 r; asm volatile("ld.global.nc.v4.u32 {%0,%1,%2,%3}, [%4];" : "=r"(r.x), "=r"(r.y), "=r"(r.z), "=r"(r.w) : "l"(p)); return r;
}
__device__ __forceinline__ uint4 ldcg128(const void* p) {
    uint4 r; asm volatile("ld.global.cg.v4.u32 {%0,%1,%2,%3}, [%4];" : "=r"(r.x), "=r"(r.y), "=r"(r.z), "=r"(r.w) : "l"(p)); return r;
}
__device__ __forceinline__ uint32_t ldg16(const void* p) {
    unsigned short r; asm volatile("ld.global.nc.u16 %0, [%1];" : "=h"(r) : "l"(p)); return (uint32_t)r;
}
__device__ __forceinline__ void mbar_init(uint32_t bar, int cnt) { asm volatile("mbarrier.init.shared::cta.b64 [%0], %1;" :: "r"(bar), "r"(cnt)); }
__device__ __forceinline__ void mbar_expect_tx(uint32_t bar, uint32_t bytes) { asm volatile("mbarrier.arrive.expect_tx.shared::cta.b64 _, [%0], %1;" :: "r"(bar), "r"(bytes) : "memory"); }
__device__ __forceinline__ void mbar_arrive(uint32_t bar) { asm volatile("mbarrier.arrive.shared::cta.b64 _, [%0];" :: "r"(bar) : "memory"); }
__device__ __forceinline__ void mbar_arrive_cluster(uint32_t bar, uint32_t cta) {
    asm volatile("{\n.reg .b32 ra;\nmapa.shared::cluster.u32 ra, %0, %1;\nmbarrier.arrive.shared::cluster.b64 _, [ra];\n}" :: "r"(bar), "r"(cta) : "memory");
}
__device__ __forceinline__ void mbar_wait(uint32_t bar, uint32_t parity) {
    asm volatile("{\n.reg .pred P1;\nLAB_WAIT:\nmbarrier.try_wait.parity.shared::cta.b64 P1, [%0], %1;\n@P1 bra DONE;\nbra LAB_WAIT;\nDONE:\n}" :: "r"(bar), "r"(parity) : "memory");
}
__device__ __forceinline__ void mbar_wait_cluster(uint32_t bar, uint32_t parity) {
    asm volatile("{\n.reg .pred P1;\nLAB_WAIT:\nmbarrier.try_wait.parity.acquire.cluster.shared::cta.b64 P1, [%0], %1;\n@P1 bra DONE;\nbra LAB_WAIT;\nDONE:\n}" :: "r"(bar), "r"(parity) : "memory");
}
__device__ __forceinline__ void tma_load_2d(uint32_t dst, const CUtensorMap* map, uint32_t bar, int c0, int c1) {
    asm volatile("cp.async.bulk.tensor.2d.shared::cluster.global.mbarrier::complete_tx::bytes [%0], [%1, {%3, %4}], [%2];"
        :: "r"(dst), "l"(map), "r"(bar), "r"(c0), "r"(c1) : "memory");
}
__device__ __forceinline__ void tma_load_2d_mc(uint32_t dst, const CUtensorMap* map, uint32_t bar, int c0, int c1, uint16_t mask) {
    asm volatile("cp.async.bulk.tensor.2d.shared::cluster.global.mbarrier::complete_tx::bytes.multicast::cluster [%0], [%1, {%3, %4}], [%2], %5;"
        :: "r"(dst), "l"(map), "r"(bar), "r"(c0), "r"(c1), "h"(mask) : "memory");
}
__device__ __forceinline__ void tma_load_3d(uint32_t dst, const CUtensorMap* map, uint32_t bar, int c0, int c1, int c2) {
    asm volatile("cp.async.bulk.tensor.3d.shared::cluster.global.mbarrier::complete_tx::bytes [%0], [%1, {%3, %4, %5}], [%2];"
        :: "r"(dst), "l"(map), "r"(bar), "r"(c0), "r"(c1), "r"(c2) : "memory");
}
__device__ __forceinline__ void cluster_arrive() { asm volatile("barrier.cluster.arrive.aligned;" ::: "memory"); }
__device__ __forceinline__ void cluster_arrive_relaxed() { asm volatile("barrier.cluster.arrive.relaxed.aligned;" ::: "memory"); }
__device__ __forceinline__ void cluster_wait() { asm volatile("barrier.cluster.wait.aligned;" ::: "memory"); }
__device__ __forceinline__ uint32_t mapa(uint32_t addr, uint32_t cta) {
    uint32_t r; asm volatile("mapa.shared::cluster.u32 %0, %1, %2;" : "=r"(r) : "r"(addr), "r"(cta)); return r;
}
__device__ __forceinline__ void st_async_v2(uint32_t addr, uint32_t a, uint32_t b, uint32_t rbar) {
    asm volatile("st.async.weak.shared::cluster.mbarrier::complete_tx::bytes.v2.b32 [%0], {%1, %2}, [%3];" :: "r"(addr), "r"(a), "r"(b), "r"(rbar) : "memory");
}
__device__ __forceinline__ void st_async_v4f(uint32_t addr, float a, float b, float c, float d, uint32_t rbar) {
    asm volatile("st.async.weak.shared::cluster.mbarrier::complete_tx::bytes.v4.f32 [%0], {%1, %2, %3, %4}, [%5];" :: "r"(addr), "f"(a), "f"(b), "f"(c), "f"(d), "r"(rbar) : "memory");
}
__device__ __forceinline__ void wgmma_fence() { asm volatile("wgmma.fence.sync.aligned;" ::: "memory"); }
__device__ __forceinline__ void wgmma_commit() { asm volatile("wgmma.commit_group.sync.aligned;" ::: "memory"); }
template <int N> __device__ __forceinline__ void wgmma_wait() { asm volatile("wgmma.wait_group.sync.aligned %0;" :: "n"(N) : "memory"); }
__device__ __forceinline__ uint64_t make_desc(uint32_t addr, uint32_t lbo_bytes, uint32_t sbo_bytes, uint32_t layout) {
    return (uint64_t)((addr & 0x3FFFF) >> 4) | ((uint64_t)(lbo_bytes >> 4) << 16) | ((uint64_t)(sbo_bytes >> 4) << 32) | ((uint64_t)layout << 62);
}
template <int R> __device__ __forceinline__ void reg_alloc() { asm volatile("setmaxnreg.inc.sync.aligned.u32 %0;" :: "n"(R)); }
template <int R> __device__ __forceinline__ void reg_dealloc() { asm volatile("setmaxnreg.dec.sync.aligned.u32 %0;" :: "n"(R)); }
__device__ __forceinline__ void pdl_launch() { asm volatile("griddepcontrol.launch_dependents;" ::: "memory"); }
__device__ __forceinline__ void pdl_wait() { asm volatile("griddepcontrol.wait;" ::: "memory"); }
__device__ __forceinline__ void prefetch_map(const CUtensorMap* m) { asm volatile("prefetch.tensormap [%0];" :: "l"(m) : "memory"); }
__device__ __forceinline__ void named_bar(int id, int n) { asm volatile("bar.sync %0, %1;" :: "r"(id), "r"(n) : "memory"); }

__device__ __forceinline__ void wgmma_m64n256k16_ss(float (&d)[128], uint64_t descA, uint64_t descB, int scaleD) {
    asm volatile("{\n.reg .pred p;\nsetp.ne.b32 p, %130, 0;\n"
        "wgmma.mma_async.sync.aligned.m64n256k16.f32.bf16.bf16 {%0, %1, %2, %3, %4, %5, %6, %7, %8, %9, %10, %11, %12, %13, %14, %15, %16, %17, %18, %19, %20, %21, %22, %23, %24, %25, %26, %27, %28, %29, %30, %31, %32, %33, %34, %35, %36, %37, %38, %39, %40, %41, %42, %43, %44, %45, %46, %47, %48, %49, %50, %51, %52, %53, %54, %55, %56, %57, %58, %59, %60, %61, %62, %63, %64, %65, %66, %67, %68, %69, %70, %71, %72, %73, %74, %75, %76, %77, %78, %79, %80, %81, %82, %83, %84, %85, %86, %87, %88, %89, %90, %91, %92, %93, %94, %95, %96, %97, %98, %99, %100, %101, %102, %103, %104, %105, %106, %107, %108, %109, %110, %111, %112, %113, %114, %115, %116, %117, %118, %119, %120, %121, %122, %123, %124, %125, %126, %127}, %128, %129, p, 1, 1, 0, 1;\n}\n"
        : "+f"(d[0]), "+f"(d[1]), "+f"(d[2]), "+f"(d[3]), "+f"(d[4]), "+f"(d[5]), "+f"(d[6]), "+f"(d[7]), "+f"(d[8]), "+f"(d[9]), "+f"(d[10]), "+f"(d[11]), "+f"(d[12]), "+f"(d[13]), "+f"(d[14]), "+f"(d[15]), "+f"(d[16]), "+f"(d[17]), "+f"(d[18]), "+f"(d[19]), "+f"(d[20]), "+f"(d[21]), "+f"(d[22]), "+f"(d[23]), "+f"(d[24]), "+f"(d[25]), "+f"(d[26]), "+f"(d[27]), "+f"(d[28]), "+f"(d[29]), "+f"(d[30]), "+f"(d[31]), "+f"(d[32]), "+f"(d[33]), "+f"(d[34]), "+f"(d[35]), "+f"(d[36]), "+f"(d[37]), "+f"(d[38]), "+f"(d[39]), "+f"(d[40]), "+f"(d[41]), "+f"(d[42]), "+f"(d[43]), "+f"(d[44]), "+f"(d[45]), "+f"(d[46]), "+f"(d[47]), "+f"(d[48]), "+f"(d[49]), "+f"(d[50]), "+f"(d[51]), "+f"(d[52]), "+f"(d[53]), "+f"(d[54]), "+f"(d[55]), "+f"(d[56]), "+f"(d[57]), "+f"(d[58]), "+f"(d[59]), "+f"(d[60]), "+f"(d[61]), "+f"(d[62]), "+f"(d[63]), "+f"(d[64]), "+f"(d[65]), "+f"(d[66]), "+f"(d[67]), "+f"(d[68]), "+f"(d[69]), "+f"(d[70]), "+f"(d[71]), "+f"(d[72]), "+f"(d[73]), "+f"(d[74]), "+f"(d[75]), "+f"(d[76]), "+f"(d[77]), "+f"(d[78]), "+f"(d[79]), "+f"(d[80]), "+f"(d[81]), "+f"(d[82]), "+f"(d[83]), "+f"(d[84]), "+f"(d[85]), "+f"(d[86]), "+f"(d[87]), "+f"(d[88]), "+f"(d[89]), "+f"(d[90]), "+f"(d[91]), "+f"(d[92]), "+f"(d[93]), "+f"(d[94]), "+f"(d[95]), "+f"(d[96]), "+f"(d[97]), "+f"(d[98]), "+f"(d[99]), "+f"(d[100]), "+f"(d[101]), "+f"(d[102]), "+f"(d[103]), "+f"(d[104]), "+f"(d[105]), "+f"(d[106]), "+f"(d[107]), "+f"(d[108]), "+f"(d[109]), "+f"(d[110]), "+f"(d[111]), "+f"(d[112]), "+f"(d[113]), "+f"(d[114]), "+f"(d[115]), "+f"(d[116]), "+f"(d[117]), "+f"(d[118]), "+f"(d[119]), "+f"(d[120]), "+f"(d[121]), "+f"(d[122]), "+f"(d[123]), "+f"(d[124]), "+f"(d[125]), "+f"(d[126]), "+f"(d[127])
        : "l"(descA), "l"(descB), "r"(scaleD));
}

__device__ __forceinline__ void wgmma_m64n192k16_ss(float (&d)[96], uint64_t descA, uint64_t descB, int scaleD) {
    asm volatile("{\n.reg .pred p;\nsetp.ne.b32 p, %98, 0;\n"
        "wgmma.mma_async.sync.aligned.m64n192k16.f32.bf16.bf16 {%0, %1, %2, %3, %4, %5, %6, %7, %8, %9, %10, %11, %12, %13, %14, %15, %16, %17, %18, %19, %20, %21, %22, %23, %24, %25, %26, %27, %28, %29, %30, %31, %32, %33, %34, %35, %36, %37, %38, %39, %40, %41, %42, %43, %44, %45, %46, %47, %48, %49, %50, %51, %52, %53, %54, %55, %56, %57, %58, %59, %60, %61, %62, %63, %64, %65, %66, %67, %68, %69, %70, %71, %72, %73, %74, %75, %76, %77, %78, %79, %80, %81, %82, %83, %84, %85, %86, %87, %88, %89, %90, %91, %92, %93, %94, %95}, %96, %97, p, 1, 1, 0, 1;\n}\n"
        : "+f"(d[0]), "+f"(d[1]), "+f"(d[2]), "+f"(d[3]), "+f"(d[4]), "+f"(d[5]), "+f"(d[6]), "+f"(d[7]), "+f"(d[8]), "+f"(d[9]), "+f"(d[10]), "+f"(d[11]), "+f"(d[12]), "+f"(d[13]), "+f"(d[14]), "+f"(d[15]), "+f"(d[16]), "+f"(d[17]), "+f"(d[18]), "+f"(d[19]), "+f"(d[20]), "+f"(d[21]), "+f"(d[22]), "+f"(d[23]), "+f"(d[24]), "+f"(d[25]), "+f"(d[26]), "+f"(d[27]), "+f"(d[28]), "+f"(d[29]), "+f"(d[30]), "+f"(d[31]), "+f"(d[32]), "+f"(d[33]), "+f"(d[34]), "+f"(d[35]), "+f"(d[36]), "+f"(d[37]), "+f"(d[38]), "+f"(d[39]), "+f"(d[40]), "+f"(d[41]), "+f"(d[42]), "+f"(d[43]), "+f"(d[44]), "+f"(d[45]), "+f"(d[46]), "+f"(d[47]), "+f"(d[48]), "+f"(d[49]), "+f"(d[50]), "+f"(d[51]), "+f"(d[52]), "+f"(d[53]), "+f"(d[54]), "+f"(d[55]), "+f"(d[56]), "+f"(d[57]), "+f"(d[58]), "+f"(d[59]), "+f"(d[60]), "+f"(d[61]), "+f"(d[62]), "+f"(d[63]), "+f"(d[64]), "+f"(d[65]), "+f"(d[66]), "+f"(d[67]), "+f"(d[68]), "+f"(d[69]), "+f"(d[70]), "+f"(d[71]), "+f"(d[72]), "+f"(d[73]), "+f"(d[74]), "+f"(d[75]), "+f"(d[76]), "+f"(d[77]), "+f"(d[78]), "+f"(d[79]), "+f"(d[80]), "+f"(d[81]), "+f"(d[82]), "+f"(d[83]), "+f"(d[84]), "+f"(d[85]), "+f"(d[86]), "+f"(d[87]), "+f"(d[88]), "+f"(d[89]), "+f"(d[90]), "+f"(d[91]), "+f"(d[92]), "+f"(d[93]), "+f"(d[94]), "+f"(d[95])
        : "l"(descA), "l"(descB), "r"(scaleD));
}

__device__ __forceinline__ void wgmma_m64n128k16_ss(float (&d)[64], uint64_t descA, uint64_t descB, int scaleD) {
    asm volatile("{\n.reg .pred p;\nsetp.ne.b32 p, %66, 0;\n"
        "wgmma.mma_async.sync.aligned.m64n128k16.f32.bf16.bf16 {%0, %1, %2, %3, %4, %5, %6, %7, %8, %9, %10, %11, %12, %13, %14, %15, %16, %17, %18, %19, %20, %21, %22, %23, %24, %25, %26, %27, %28, %29, %30, %31, %32, %33, %34, %35, %36, %37, %38, %39, %40, %41, %42, %43, %44, %45, %46, %47, %48, %49, %50, %51, %52, %53, %54, %55, %56, %57, %58, %59, %60, %61, %62, %63}, %64, %65, p, 1, 1, 0, 1;\n}\n"
        : "+f"(d[0]), "+f"(d[1]), "+f"(d[2]), "+f"(d[3]), "+f"(d[4]), "+f"(d[5]), "+f"(d[6]), "+f"(d[7]), "+f"(d[8]), "+f"(d[9]), "+f"(d[10]), "+f"(d[11]), "+f"(d[12]), "+f"(d[13]), "+f"(d[14]), "+f"(d[15]), "+f"(d[16]), "+f"(d[17]), "+f"(d[18]), "+f"(d[19]), "+f"(d[20]), "+f"(d[21]), "+f"(d[22]), "+f"(d[23]), "+f"(d[24]), "+f"(d[25]), "+f"(d[26]), "+f"(d[27]), "+f"(d[28]), "+f"(d[29]), "+f"(d[30]), "+f"(d[31]), "+f"(d[32]), "+f"(d[33]), "+f"(d[34]), "+f"(d[35]), "+f"(d[36]), "+f"(d[37]), "+f"(d[38]), "+f"(d[39]), "+f"(d[40]), "+f"(d[41]), "+f"(d[42]), "+f"(d[43]), "+f"(d[44]), "+f"(d[45]), "+f"(d[46]), "+f"(d[47]), "+f"(d[48]), "+f"(d[49]), "+f"(d[50]), "+f"(d[51]), "+f"(d[52]), "+f"(d[53]), "+f"(d[54]), "+f"(d[55]), "+f"(d[56]), "+f"(d[57]), "+f"(d[58]), "+f"(d[59]), "+f"(d[60]), "+f"(d[61]), "+f"(d[62]), "+f"(d[63])
        : "l"(descA), "l"(descB), "r"(scaleD));
}

__device__ __forceinline__ void quad_transpose(uint32_t& r0, uint32_t& r1, uint32_t& r2, uint32_t& r3, int t) {
    const bool o1 = t & 1, o2 = t & 2;
    uint32_t x, y;
    x = o1 ? r0 : r1; y = __shfl_xor_sync(0xffffffffu, x, 1); if (o1) r0 = y; else r1 = y;
    x = o1 ? r2 : r3; y = __shfl_xor_sync(0xffffffffu, x, 1); if (o1) r2 = y; else r3 = y;
    x = o2 ? r0 : r2; y = __shfl_xor_sync(0xffffffffu, x, 2); if (o2) r0 = y; else r2 = y;
    x = o2 ? r1 : r3; y = __shfl_xor_sync(0xffffffffu, x, 2); if (o2) r1 = y; else r3 = y;
}

constexpr int K1_THREADS = 256;
constexpr int UT_PAD = 128;
constexpr int UT_LEN = UT_PAD + S_;
constexpr int KR_LEN = 2080;
constexpr int YP_LEN = S_ + (S_ / 32) * 8;

struct __align__(128) K1Smem {
    bf16 uT[4][UT_LEN];
    bf16 kr[4][2][KR_LEN];
    float yP[4][YP_LEN];
    uint64_t bar;
    uint8_t pad[32768];
};

__device__ __forceinline__ void mma16816(float (&c)[4], uint32_t a0, uint32_t a1, uint32_t a2, uint32_t a3, uint32_t b0, uint32_t b1) {
    asm("mma.sync.aligned.m16n8k16.row.col.f32.bf16.bf16.f32 {%0,%1,%2,%3}, {%4,%5,%6,%7}, {%8,%9}, {%0,%1,%2,%3};"
        : "+f"(c[0]), "+f"(c[1]), "+f"(c[2]), "+f"(c[3])
        : "r"(a0), "r"(a1), "r"(a2), "r"(a3), "r"(b0), "r"(b1));
}
__device__ __forceinline__ void ldsm_x4(uint32_t& r0, uint32_t& r1, uint32_t& r2, uint32_t& r3, uint32_t addr) {
    asm volatile("ldmatrix.sync.aligned.m8n8.x4.shared.b16 {%0,%1,%2,%3}, [%4];" : "=r"(r0), "=r"(r1), "=r"(r2), "=r"(r3) : "r"(addr) : "memory");
}

__device__ __forceinline__ void conv_mma(const bf16* uTc, const bf16* krlane, float (&acc)[16][4], int lane, int half) {
    const int lrow = lane & 7, lk = (lane >> 3) & 1, lt = lane >> 4;
    const uint32_t ubase = smem_u32(uTc) + (UT_PAD + 16 * (8 * lt + lrow) + 8 * lk) * 2;
#pragma unroll 1
    for (int pp = 0; pp < 4; pp++) {
        const int p = half * 4 + pp;
        uint32_t U[16][2];
#pragma unroll
        for (int j = 0; j < 16; j += 2) ldsm_x4(U[j][0], U[j][1], U[j + 1][0], U[j + 1][1], ubase + (j * 128 - p * 16) * 2);
        const uint32_t* kp = reinterpret_cast<const uint32_t*>(krlane - 16 * p);
        const volatile uint32_t* kpv = kp;
        uint32_t a0 = kp[0], a1 = kp[-4], a2 = kp[4], a3 = kpv[0];
#pragma unroll
        for (int q = 0; q < 16; q++) {
            uint32_t b0 = 0, b1 = 0, b2 = 0, b3 = 0;
            if (q < 15) { b0 = kp[-64 * (q + 1)]; b1 = kp[-64 * (q + 1) - 4]; b2 = kp[-64 * (q + 1) + 4]; b3 = kpv[-64 * (q + 1)]; }
#pragma unroll
            for (int n = 15; n >= q; n--) mma16816(acc[n], a0, a1, a2, a3, U[n - q][0], U[n - q][1]);
            a0 = b0; a1 = b1; a2 = b2; a3 = b3;
        }
    }
}

__global__ void __cluster_dims__(2, 1, 1) __launch_bounds__(K1_THREADS, 1)
conv_kernel(const bf16* __restrict__ k, const bf16* __restrict__ v,
            const bf16* __restrict__ shift_k, const bf16* __restrict__ ssm_k, const bf16* __restrict__ ssm_D) {
    extern __shared__ __align__(1024) uint8_t smem_raw[];
    pdl_launch();
    K1Smem& sm = *reinterpret_cast<K1Smem*>(smem_raw);
    const int tid = threadIdx.x, lane = tid & 31, warp = tid >> 5;
    const int bid = blockIdx.x;
    const int rank = bid & 1;
    const int c0 = 8 * (bid >> 1);
    const int cown = c0 + 4 * rank;
#define TMT 0
    TM(0, 0);
    const uint32_t bar = smem_u32(&sm.bar);
    if (tid == 0) {
        mbar_init(bar, 1);
        asm volatile("fence.mbarrier_init.release.cluster;" ::: "memory");
        mbar_expect_tx(bar, 1024 * 4 * 2);
    }
    cluster_arrive_relaxed();

    const int s0 = 1024 * rank + 4 * tid;
    uint4 kk[7], vv[4], sw[4];
#pragma unroll
    for (int i = 0; i < 4; i++) kk[3 + i] = ldg128(k + (size_t)(s0 + i) * D_ + c0);
#pragma unroll
    for (int i = 0; i < 4; i++) vv[i] = ldg128(v + (size_t)(s0 + i) * D_ + c0);
    if (lane == 0) {
#pragma unroll
        for (int i = 0; i < 3; i++) {
            const int s = s0 - 3 + i;
            kk[i] = make_uint4(0, 0, 0, 0);
            if (s >= 0) kk[i] = ldg128(k + (size_t)s * D_ + c0);
        }
    }
#pragma unroll
    for (int i = 0; i < 4; i++) sw[i] = ldg128(shift_k + (size_t)c0 * 4 + 8 * i);
    uint4 kq[4]; uint32_t nx[4];
#pragma unroll
    for (int c = 0; c < 4; c++) {
        const bf16* kr = ssm_k + (size_t)(cown + c) * S_;
        kq[c] = ldg128(kr + 8 * tid);
        nx[c] = 0u;
        if (tid < 255) nx[c] = ldg16(kr + 8 * tid + 8);
    }
    const uint32_t dval = ldg16(ssm_D + cown + (warp >> 1));
    if (tid < 64) *reinterpret_cast<uint4*>(&sm.uT[tid >> 4][(tid & 15) * 8]) = make_uint4(0, 0, 0, 0);
#pragma unroll
    for (int i = 0; i < 3; i++) {
        uint4 t;
        t.x = __shfl_up_sync(0xffffffffu, kk[4 + i].x, 1); t.y = __shfl_up_sync(0xffffffffu, kk[4 + i].y, 1);
        t.z = __shfl_up_sync(0xffffffffu, kk[4 + i].z, 1); t.w = __shfl_up_sync(0xffffffffu, kk[4 + i].w, 1);
        if (lane != 0) kk[i] = t;
    }
    uint32_t kvw[4][4];
    const uint32_t* kkw = reinterpret_cast<const uint32_t*>(kk);
    const uint32_t* vvw = reinterpret_cast<const uint32_t*>(vv);
#pragma unroll
    for (int i2 = 0; i2 < 4; i2++) {
        const uint32_t t0 = __byte_perm(sw[i2].x, sw[i2].z, 0x5410), t1 = __byte_perm(sw[i2].x, sw[i2].z, 0x7632);
        const uint32_t t2 = __byte_perm(sw[i2].y, sw[i2].w, 0x5410), t3 = __byte_perm(sw[i2].y, sw[i2].w, 0x7632);
#pragma unroll
        for (int r = 0; r < 4; r++) {
            uint32_t a = hmul2(kkw[(r + 0) * 4 + i2], t3);
            a = hadd2(a, hmul2(kkw[(r + 1) * 4 + i2], t2));
            a = hadd2(a, hmul2(kkw[(r + 2) * 4 + i2], t1));
            a = hadd2(a, hmul2(kkw[(r + 3) * 4 + i2], t0));
            kvw[r][i2] = hmul2(a, vvw[r * 4 + i2]);
        }
    }
    TM(0, 1);
    cluster_wait();
    {
        const uint32_t rbar = mapa(bar, (uint32_t)(rank ^ 1));
#pragma unroll
        for (int i2 = 0; i2 < 4; i2++) {
#pragma unroll
            for (int e = 0; e < 2; e++) {
                const uint32_t sel = e ? 0x7632 : 0x5410;
                const uint32_t w0 = __byte_perm(kvw[0][i2], kvw[1][i2], sel), w1 = __byte_perm(kvw[2][i2], kvw[3][i2], sel);
                const int cc = 2 * i2 + e;
                if ((cc >> 2) == rank) {
                    *reinterpret_cast<uint2*>(&sm.uT[cc & 3][UT_PAD + s0]) = make_uint2(w0, w1);
                } else {
                    st_async_v2(mapa(smem_u32(&sm.uT[cc & 3][UT_PAD + s0]), (uint32_t)(rank ^ 1)), w0, w1, rbar);
                }
            }
        }
    }
#pragma unroll
    for (int c = 0; c < 4; c++) {
        uint4 a, b;
        a.x = __byte_perm(kq[c].w, 0, 0x1032); a.y = __byte_perm(kq[c].z, 0, 0x1032);
        a.z = __byte_perm(kq[c].y, 0, 0x1032); a.w = __byte_perm(kq[c].x, 0, 0x1032);
        b.x = __byte_perm(nx[c], kq[c].w, 0x7610); b.y = __byte_perm(kq[c].w, kq[c].z, 0x7610);
        b.z = __byte_perm(kq[c].z, kq[c].y, 0x7610); b.w = __byte_perm(kq[c].y, kq[c].x, 0x7610);
        *reinterpret_cast<uint4*>(&sm.kr[c][0][2040 - 8 * tid]) = a;
        *reinterpret_cast<uint4*>(&sm.kr[c][1][2040 - 8 * tid]) = b;
        if (tid == 0) {
            *reinterpret_cast<uint4*>(&sm.kr[c][1][2048]) = make_uint4(kq[c].x & 0xffffu, 0, 0, 0);
        } else if (tid < 8) {
            if (tid < 4) *reinterpret_cast<uint4*>(&sm.kr[c][1][2048 + 8 * tid]) = make_uint4(0, 0, 0, 0);
            else *reinterpret_cast<uint4*>(&sm.kr[c][0][2048 + 8 * (tid - 4)]) = make_uint4(0, 0, 0, 0);
        }
    }
    TM(0, 3);
    __syncthreads();
    mbar_wait_cluster(bar, 0);
    TM(0, 4);

    const int ch = warp >> 1, half = warp & 1;
    const int g = lane >> 2, t = lane & 3;
    float acc[16][4];
#pragma unroll
    for (int i = 0; i < 16; i++) { acc[i][0] = acc[i][1] = acc[i][2] = acc[i][3] = 0.f; }
    const bf16* krlane = (g & 1) ? &sm.kr[ch][0][2047 - g + 2 * t] : &sm.kr[ch][1][2048 - g + 2 * t];
    conv_mma(sm.uT[ch], krlane, acc, lane, half);
    TM(0, 5);
    float* yp = &sm.yP[ch][40 * t + g];
    if (half) {
#pragma unroll
        for (int n = 0; n < 16; n++) {
            yp[160 * n] = acc[n][0];
            yp[160 * n + 16] = acc[n][1];
            yp[160 * n + 8] = acc[n][2];
            yp[160 * n + 24] = acc[n][3];
        }
    }
    named_bar(1 + ch, 64);
    if (!half) {
#pragma unroll
        for (int n = 0; n < 16; n++) {
            yp[160 * n] += acc[n][0];
            yp[160 * n + 16] += acc[n][1];
            yp[160 * n + 8] += acc[n][2];
            yp[160 * n + 24] += acc[n][3];
        }
    }
    named_bar(1 + ch, 64);
    TM(0, 6);
    {
        const int tt = tid & 63;
        bf16* dst = g_yT + (size_t)(cown + ch) * S_;
        const uint32_t d2 = dval * 0x10001u;
#pragma unroll
        for (int j = 0; j < 4; j++) {
            const int s = (j * 64 + tt) * 8;
            const float* src = &sm.yP[ch][s + (s >> 5) * 8];
            const float4 a = *reinterpret_cast<const float4*>(src), b = *reinterpret_cast<const float4*>(src + 4);
            const uint4 kv4 = *reinterpret_cast<const uint4*>(&sm.uT[ch][UT_PAD + s]);
            *reinterpret_cast<uint4*>(dst + s) = make_uint4(hadd2(pack_bf16(a.x, a.y), hmul2(kv4.x, d2)), hadd2(pack_bf16(a.z, a.w), hmul2(kv4.y, d2)),
                                                            hadd2(pack_bf16(b.x, b.y), hmul2(kv4.z, d2)), hadd2(pack_bf16(b.z, b.w), hmul2(kv4.w, d2)));
        }
    }
    TM(0, 7);
#undef TMT
}

constexpr int R_THREADS = 512;
constexpr int R_ROWS = 16;

__device__ __forceinline__ float warp_sum(float s) {
#pragma unroll
    for (int o = 16; o > 0; o >>= 1) s += __shfl_xor_sync(0xffffffffu, s, o);
    return s;
}
__device__ __forceinline__ uint32_t hsub2(uint32_t a, uint32_t b) {
    __nv_bfloat162 r = __hsub2_rn(*reinterpret_cast<__nv_bfloat162*>(&a), *reinterpret_cast<__nv_bfloat162*>(&b));
    return *reinterpret_cast<uint32_t*>(&r);
}
__device__ __forceinline__ void ln_row(const uint32_t (&x)[8], uint32_t (&o)[8]) {
    float s0 = 0.f, s1 = 0.f;
#pragma unroll
    for (int i = 0; i < 8; i++) { s0 += bf_lo(x[i]); s1 += bf_hi(x[i]); }
    const float mean = warp_sum(s0 + s1) * (1.0f / D_);
    float ss0 = 0.f, ss1 = 0.f;
#pragma unroll
    for (int i = 0; i < 8; i++) { const float d0 = bf_lo(x[i]) - mean, d1 = bf_hi(x[i]) - mean; ss0 += d0 * d0; ss1 += d1 * d1; }
    const float var = bf16r(warp_sum(ss0 + ss1) * (1.0f / D_));
    const float rinv = 1.0f / bf16r(sqrtf(bf16r(var + 1e-5f)));
    const uint32_t m2 = pack_bf16(mean, mean);
#pragma unroll
    for (int i = 0; i < 8; i++) {
        const uint32_t d = hsub2(x[i], m2);
        o[i] = pack_bf16(bf_lo(d) * rinv, bf_hi(d) * rinv);
    }
}

__global__ void __launch_bounds__(R_THREADS, 1)
row_kernel(const bf16* __restrict__ q) {
    __shared__ __align__(16) uint32_t ys[R_ROWS][D_ / 2 + 4];
    const int tid = threadIdx.x, lane = tid & 31, warp = tid >> 5;
    const int s0 = blockIdx.x * R_ROWS;
#define TMT 0
    TM(1, 0);
    pdl_launch();
    const int r0 = s0 + warp;
    const int p = tid & 255, hs = tid >> 8;
    const uint4 qa = ldg128(q + (size_t)r0 * D_ + 8 * lane);
    const uint4 qb = ldg128(q + (size_t)r0 * D_ + 8 * (lane + 32));
    const uint32_t x[8] = {qa.x, qa.y, qa.z, qa.w, qb.x, qb.y, qb.z, qb.w};
    uint32_t qn[8];
    ln_row(x, qn);
    pdl_wait();
    {
        const bf16* y0 = g_yT + (size_t)(2 * p) * S_ + s0 + 8 * hs;
        const uint4 ya = ldcg128(y0);
        const uint4 yb = ldcg128(y0 + S_);
        const uint32_t aw[4] = {ya.x, ya.y, ya.z, ya.w};
        const uint32_t bw[4] = {yb.x, yb.y, yb.z, yb.w};
#pragma unroll
        for (int j = 0; j < 4; j++) {
            ys[8 * hs + 2 * j][p] = __byte_perm(aw[j], bw[j], 0x5410);
            ys[8 * hs + 2 * j + 1][p] = __byte_perm(aw[j], bw[j], 0x7632);
        }
    }
    __syncthreads();
    TM(1, 1);
    uint32_t h[8], hn[8];
#pragma unroll
    for (int i = 0; i < 2; i++) {
        const uint4 yw4 = *reinterpret_cast<const uint4*>(&ys[warp][4 * (lane + 32 * i)]);
        const uint32_t yw[4] = {yw4.x, yw4.y, yw4.z, yw4.w};
#pragma unroll
        for (int j = 0; j < 4; j++) h[4 * i + j] = hadd2(x[4 * i + j], hmul2(qn[4 * i + j], yw[j]));
    }
    ln_row(h, hn);
#pragma unroll
    for (int i = 0; i < 2; i++) {
        const size_t off = (size_t)r0 * D_ + 8 * (lane + 32 * i);
        *reinterpret_cast<uint4*>(g_h + off) = make_uint4(h[4 * i], h[4 * i + 1], h[4 * i + 2], h[4 * i + 3]);
        *reinterpret_cast<uint4*>(g_hn + off) = make_uint4(hn[4 * i], hn[4 * i + 1], hn[4 * i + 2], hn[4 * i + 3]);
    }
    TM(1, 2);
#undef TMT
}

constexpr int G1_THREADS = 384;
constexpr int G1_STAGES = 3;
constexpr int G1_A_BYTES = 8 * 16384;
constexpr int G1_B_STAGE = 32768;
constexpr int G1_OFF_B = G1_A_BYTES;
constexpr int G1_OFF_BAR = G1_OFF_B + G1_STAGES * G1_B_STAGE;
constexpr int G1_SMEM = G1_OFF_BAR + 256;

__device__ __forceinline__ float sigmoid_fast(float x) {
    float t; asm("tanh.approx.f32 %0, %1;" : "=f"(t) : "f"(0.5f * x));
    return fmaf(t, 0.5f, 0.5f);
}

template <int NT>
__device__ __forceinline__ void g1_epilogue(const float (&acc)[NT * 8], bf16* out0, int t) {
#pragma unroll
    for (int j0 = 0; j0 < NT; j0 += 4) {
        uint32_t P0[4], P1[4];
#pragma unroll
        for (int jj = 0; jj < 4; jj++) {
            const int j = j0 + jj;
            float r[4];
#pragma unroll
            for (int e = 0; e < 4; e++) r[e] = sigmoid_fast(acc[4 * j + e]) * acc[4 * (NT + j) + e];
            P0[jj] = pack_bf16(r[0], r[1]);
            P1[jj] = pack_bf16(r[2], r[3]);
        }
        quad_transpose(P0[0], P0[1], P0[2], P0[3], t);
        quad_transpose(P1[0], P1[1], P1[2], P1[3], t);
        *reinterpret_cast<uint4*>(out0 + 8 * (j0 + t)) = make_uint4(P0[0], P0[1], P0[2], P0[3]);
        *reinterpret_cast<uint4*>(out0 + 8 * F_ + 8 * (j0 + t)) = make_uint4(P1[0], P1[1], P1[2], P1[3]);
    }
}

__global__ void __cluster_dims__(2, 1, 1) __launch_bounds__(G1_THREADS, 1)
gemm1_kernel(const __grid_constant__ CUtensorMap mapA, const __grid_constant__ CUtensorMap mapG4, const __grid_constant__ CUtensorMap mapU4,
             const __grid_constant__ CUtensorMap mapG3, const __grid_constant__ CUtensorMap mapU3) {
    extern __shared__ __align__(1024) uint8_t smem_raw[];
    const uint32_t sb = smem_u32(smem_raw);
    const int tid = threadIdx.x, lane = tid & 31, warp = tid >> 5, wgi = tid >> 7;
    const int rank = blockIdx.x & 1;
    const int cb = blockIdx.x & 7, rb = blockIdx.x >> 3;
#define TMT 128
    TM(2, 0);
    pdl_launch();
    if (tid == 32) { prefetch_map(&mapA); prefetch_map(&mapG4); prefetch_map(&mapU4); prefetch_map(&mapG3); prefetch_map(&mapU3); }
    const uint32_t barA = sb + G1_OFF_BAR;
    const uint32_t barF = barA + 64;
    const uint32_t barE = barF + 8 * G1_STAGES;
    if (tid == 0) {
        for (int i = 0; i < 8; i++) mbar_init(barA + 8 * i, 1);
        for (int i = 0; i < G1_STAGES; i++) { mbar_init(barF + 8 * i, 1); mbar_init(barE + 8 * i, 2); }
        for (int i = 0; i < 8; i++) mbar_expect_tx(barA + 8 * i, 16384);
        asm volatile("fence.mbarrier_init.release.cluster;" ::: "memory");
    }
    __syncthreads();
    cluster_arrive_relaxed();
    cluster_wait();

    if (wgi == 0) {
        reg_dealloc<40>();
        if (lane == 0 && warp == 0) {
            int st = 0, ph = 1;
            for (int it = 0; it < 16; it++) {
                const int kc = it & 7;
                mbar_wait(barE + 8 * st, ph);
                const uint32_t dst = sb + G1_OFF_B + st * G1_B_STAGE;
                if (it < 8) {
                    mbar_expect_tx(barF + 8 * st, 32768);
                    tma_load_3d(dst, &mapG4, barF + 8 * st, 0, kc * 64, cb * 7);
                    tma_load_3d(dst + 16384, &mapU4, barF + 8 * st, 0, kc * 64, cb * 7);
                } else {
                    mbar_expect_tx(barF + 8 * st, 24576);
                    tma_load_3d(dst, &mapG3, barF + 8 * st, 0, kc * 64, cb * 7 + 4);
                    tma_load_3d(dst + 12288, &mapU3, barF + 8 * st, 0, kc * 64, cb * 7 + 4);
                }
                if (++st == G1_STAGES) { st = 0; ph ^= 1; }
            }
        } else if (lane == 0 && warp == 1) {
            pdl_wait();
            for (int i = 0; i < 4; i++) {
                const int c = 2 * i + rank;
                tma_load_2d_mc(sb + c * 16384, &mapA, barA + 8 * c, c * 64, rb * 128, (uint16_t)3);
            }
        }
        __syncwarp();
    } else {
        reg_alloc<232>();
        pdl_wait();
        const int cw = wgi - 1;
        const int g = lane >> 2, t = lane & 3, wl = warp & 3, tl = tid & 127;
        bf16* outp = g_hh + (size_t)(rb * 128 + cw * 64 + wl * 16 + g) * F_ + cb * 224;
        int st = 0, ph = 0;
        {
            float acc[128];
#pragma unroll 1
            for (int kc = 0; kc < 8; kc++) {
                mbar_wait(barA + 8 * kc, 0);
                mbar_wait(barF + 8 * st, ph);
                if (tl == 0 && cw == 0) TR(1, kc);
                wgmma_fence();
                const uint32_t aaddr = sb + kc * 16384 + cw * 8192;
                const uint32_t baddr = sb + G1_OFF_B + st * G1_B_STAGE;
#pragma unroll
                for (int kk = 0; kk < 4; kk++)
                    wgmma_m64n256k16_ss(acc, make_desc(aaddr + kk * 32, 16, 1024, 1), make_desc(baddr + kk * 1024, 4096, 512, 2), (kc | kk) != 0);
                wgmma_commit();
                wgmma_wait<0>();
                if (tl == 0) mbar_arrive(barE + 8 * st);
                if (++st == G1_STAGES) { st = 0; ph ^= 1; }
            }
            TM(2, 1);
            g1_epilogue<16>(acc, outp, t);
            TM(2, 2);
        }
        {
            float acc[96];
#pragma unroll 1
            for (int kc = 0; kc < 8; kc++) {
                mbar_wait(barF + 8 * st, ph);
                if (tl == 0 && cw == 0) TR(1, 8 + kc);
                wgmma_fence();
                const uint32_t aaddr = sb + kc * 16384 + cw * 8192;
                const uint32_t baddr = sb + G1_OFF_B + st * G1_B_STAGE;
#pragma unroll
                for (int kk = 0; kk < 4; kk++)
                    wgmma_m64n192k16_ss(acc, make_desc(aaddr + kk * 32, 16, 1024, 1), make_desc(baddr + kk * 1024, 4096, 512, 2), (kc | kk) != 0);
                wgmma_commit();
                wgmma_wait<0>();
                if (tl == 0) mbar_arrive(barE + 8 * st);
                if (++st == G1_STAGES) { st = 0; ph ^= 1; }
            }
            TM(2, 3);
            g1_epilogue<12>(acc, outp + 128, t);
            TM(2, 4);
        }
    }
}

constexpr int G2_THREADS = 384;
constexpr int G2_STAGES = 6;
constexpr int G2_STAGE = 32768;
constexpr int G2_OFF_X = G2_STAGES * G2_STAGE;
constexpr int G2_OFF_BAR = G2_OFF_X + 32768;
constexpr int G2_SMEM = G2_OFF_BAR + 128;
constexpr int G2_KSTEPS = 14;

__global__ void __cluster_dims__(2, 1, 1) __launch_bounds__(G2_THREADS, 1)
gemm2_kernel(const __grid_constant__ CUtensorMap mapHH, const __grid_constant__ CUtensorMap mapWd, bf16* __restrict__ out) {
    extern __shared__ __align__(1024) uint8_t smem_raw[];
    const uint32_t sb = smem_u32(smem_raw);
    const int tid = threadIdx.x, lane = tid & 31, warp = tid >> 5, wgi = tid >> 7;
    const int ks = blockIdx.x & 1, nb = (blockIdx.x >> 1) & 3, rb = blockIdx.x >> 3;
    TM(3, 0);
    if (tid == 32) { prefetch_map(&mapHH); prefetch_map(&mapWd); }
    const uint32_t barF = sb + G2_OFF_BAR;
    const uint32_t barE = barF + 8 * G2_STAGES;
    const uint32_t barX = barE + 8 * G2_STAGES;
    if (tid == 0) {
        for (int i = 0; i < G2_STAGES; i++) { mbar_init(barF + 8 * i, 1); mbar_init(barE + 8 * i, 2); }
        mbar_init(barX, 1);
        asm volatile("fence.mbarrier_init.release.cluster;" ::: "memory");
        mbar_expect_tx(barX, 32768);
    }
    __syncthreads();
    cluster_arrive_relaxed();

    if (wgi == 0) {
        if (tid == 0) {
            for (int it = 0; it < G2_STAGES; it++) {
                mbar_expect_tx(barF + 8 * it, 32768);
                tma_load_3d(sb + it * G2_STAGE + 16384, &mapWd, barF + 8 * it, 0, ks * 896 + it * 64, nb * 2);
            }
            pdl_wait();
            for (int it = 0; it < G2_STAGES; it++)
                tma_load_2d(sb + it * G2_STAGE, &mapHH, barF + 8 * it, ks * 896 + it * 64, rb * 128);
            int st = 0, ph = 0;
            for (int it = G2_STAGES; it < G2_KSTEPS; it++) {
                mbar_wait(barE + 8 * st, ph);
                const uint32_t dst = sb + st * G2_STAGE;
                const int k0 = ks * 896 + it * 64;
                mbar_expect_tx(barF + 8 * st, 32768);
                tma_load_2d(dst, &mapHH, barF + 8 * st, k0, rb * 128);
                tma_load_3d(dst + 16384, &mapWd, barF + 8 * st, 0, k0, nb * 2);
                if (++st == G2_STAGES) { st = 0; ph ^= 1; }
            }
        }
        __syncwarp();
        cluster_wait();
    } else {
        const int cw = wgi - 1;
        const int g = lane >> 2, t = lane & 3, wl = warp & 3;
        const int tl = tid & 127;
        int st = 0, ph = 0;
        float acc[64];
        pdl_wait();
#pragma unroll 1
        for (int it = 0; it < G2_KSTEPS; it++) {
            mbar_wait(barF + 8 * st, ph);
            if (it == 0) TM(3, 1);
            wgmma_fence();
            const uint32_t aaddr = sb + st * G2_STAGE + cw * 8192;
            const uint32_t baddr = sb + st * G2_STAGE + 16384;
#pragma unroll
            for (int kk = 0; kk < 4; kk++)
                wgmma_m64n128k16_ss(acc, make_desc(aaddr + kk * 32, 16, 1024, 1), make_desc(baddr + kk * 2048, 8192, 1024, 1), (it | kk) != 0);
            wgmma_commit();
            wgmma_wait<0>();
            if (tl == 0) mbar_arrive(barE + 8 * st);
            if (++st == G2_STAGES) { st = 0; ph ^= 1; }
        }
        TM(3, 2);
        cluster_wait();
        if (cw != ks) {
            const uint32_t dst = mapa(sb + G2_OFF_X + tl * 16, (uint32_t)(ks ^ 1));
            const uint32_t rbar = mapa(barX, (uint32_t)(ks ^ 1));
#pragma unroll
            for (int i = 0; i < 16; i++) st_async_v4f(dst + i * 2048, acc[4 * i], acc[4 * i + 1], acc[4 * i + 2], acc[4 * i + 3], rbar);
        } else {
            const float4* xb = reinterpret_cast<const float4*>(smem_raw + G2_OFF_X) + tl;
            const int row0 = rb * 128 + cw * 64 + wl * 16 + g;
            const bf16* h0 = g_h + (size_t)row0 * D_ + nb * 128;
            bf16* o0 = out + (size_t)row0 * D_ + nb * 128;
            uint32_t ha[16], hb[16];
#pragma unroll
            for (int j = 0; j < 16; j++) {
                ha[j] = __ldcg(reinterpret_cast<const uint32_t*>(h0 + 8 * j + 2 * t));
                hb[j] = __ldcg(reinterpret_cast<const uint32_t*>(h0 + 8 * D_ + 8 * j + 2 * t));
            }
            mbar_wait_cluster(barX, 0);
            TM(3, 4);
#pragma unroll
            for (int j0 = 0; j0 < 16; j0 += 4) {
                uint32_t P0[4], P1[4];
#pragma unroll
                for (int jj = 0; jj < 4; jj++) {
                    const int j = j0 + jj;
                    const float4 x = xb[j * 128];
                    P0[jj] = pack_bf16(bf_lo(ha[j]) + bf16r(acc[4 * j] + x.x), bf_hi(ha[j]) + bf16r(acc[4 * j + 1] + x.y));
                    P1[jj] = pack_bf16(bf_lo(hb[j]) + bf16r(acc[4 * j + 2] + x.z), bf_hi(hb[j]) + bf16r(acc[4 * j + 3] + x.w));
                }
                quad_transpose(P0[0], P0[1], P0[2], P0[3], t);
                quad_transpose(P1[0], P1[1], P1[2], P1[3], t);
                *reinterpret_cast<uint4*>(o0 + 8 * (j0 + t)) = make_uint4(P0[0], P0[1], P0[2], P0[3]);
                *reinterpret_cast<uint4*>(o0 + 8 * D_ + 8 * (j0 + t)) = make_uint4(P1[0], P1[1], P1[2], P1[3]);
            }
        }
        TM(3, 5);
    }
#undef TMT
}

typedef CUresult (*EncodeFn)(CUtensorMap*, CUtensorMapDataType, cuuint32_t, void*, const cuuint64_t*, const cuuint64_t*,
                             const cuuint32_t*, const cuuint32_t*, CUtensorMapInterleave, CUtensorMapSwizzle,
                             CUtensorMapL2promotion, CUtensorMapFloatOOBfill);

static void enc2d(EncodeFn enc, CUtensorMap* m, const void* p, int rows, int cols, int brows, int bcols) {
    cuuint64_t dims[2] = {(cuuint64_t)cols, (cuuint64_t)rows};
    cuuint64_t strides[1] = {(cuuint64_t)cols * 2};
    cuuint32_t box[2] = {(cuuint32_t)bcols, (cuuint32_t)brows};
    cuuint32_t es[2] = {1, 1};
    enc(m, CU_TENSOR_MAP_DATA_TYPE_BFLOAT16, 2, const_cast<void*>(p), dims, strides, box, es, CU_TENSOR_MAP_INTERLEAVE_NONE,
        bcols == 32 ? CU_TENSOR_MAP_SWIZZLE_64B : CU_TENSOR_MAP_SWIZZLE_128B, CU_TENSOR_MAP_L2_PROMOTION_L2_128B, CU_TENSOR_MAP_FLOAT_OOB_FILL_NONE);
}
static void enc3d(EncodeFn enc, CUtensorMap* m, const void* p, int rows, int cols, int atom, int brows, int natoms) {
    cuuint64_t dims[3] = {(cuuint64_t)atom, (cuuint64_t)rows, (cuuint64_t)(cols / atom)};
    cuuint64_t strides[2] = {(cuuint64_t)cols * 2, (cuuint64_t)atom * 2};
    cuuint32_t box[3] = {(cuuint32_t)atom, (cuuint32_t)brows, (cuuint32_t)natoms};
    cuuint32_t es[3] = {1, 1, 1};
    enc(m, CU_TENSOR_MAP_DATA_TYPE_BFLOAT16, 3, const_cast<void*>(p), dims, strides, box, es, CU_TENSOR_MAP_INTERLEAVE_NONE,
        atom == 32 ? CU_TENSOR_MAP_SWIZZLE_64B : CU_TENSOR_MAP_SWIZZLE_128B, CU_TENSOR_MAP_L2_PROMOTION_L2_128B, CU_TENSOR_MAP_FLOAT_OOB_FILL_NONE);
}

extern "C" void kernel_launch(void* const* d_in, const int* in_sizes, int n_in, void* d_out, int out_size) {
    const bf16* q = (const bf16*)d_in[0];
    const bf16* k = (const bf16*)d_in[1];
    const bf16* v = (const bf16*)d_in[2];
    const bf16* shift_k = (const bf16*)d_in[3];
    const bf16* ssm_k = (const bf16*)d_in[4];
    const bf16* ssm_D = (const bf16*)d_in[5];
    const bf16* wg = (const bf16*)d_in[7];
    const bf16* wu = (const bf16*)d_in[8];
    const bf16* wd = (const bf16*)d_in[9];
    bf16* out = (bf16*)d_out;

    static EncodeFn enc = nullptr;
    static void *p_hn = nullptr, *p_hh = nullptr;
    if (!enc) {
        void* fn = nullptr; cudaDriverEntryPointQueryResult qr;
        cudaGetDriverEntryPoint("cuTensorMapEncodeTiled", &fn, cudaEnableDefault, &qr);
        enc = (EncodeFn)fn;
        cudaGetSymbolAddress(&p_hn, g_hn);
        cudaGetSymbolAddress(&p_hh, g_hh);
        cudaFuncSetAttribute(conv_kernel, cudaFuncAttributeMaxDynamicSharedMemorySize, (int)sizeof(K1Smem));
        cudaFuncSetAttribute(gemm1_kernel, cudaFuncAttributeMaxDynamicSharedMemorySize, G1_SMEM);
        cudaFuncSetAttribute(gemm2_kernel, cudaFuncAttributeMaxDynamicSharedMemorySize, G2_SMEM);
    }
    CUtensorMap mA, mG64, mU64, mG32, mU32, mHH, mWd;
    enc2d(enc, &mA, p_hn, S_, D_, 128, 64);
    enc3d(enc, &mG64, wg, D_, F_, 32, 64, 4);
    enc3d(enc, &mU64, wu, D_, F_, 32, 64, 4);
    enc3d(enc, &mG32, wg, D_, F_, 32, 64, 3);
    enc3d(enc, &mU32, wu, D_, F_, 32, 64, 3);
    enc2d(enc, &mHH, p_hh, S_, F_, 128, 64);
    enc3d(enc, &mWd, wd, F_, D_, 64, 64, 2);

    cudaStream_t st = cudaStreamPerThread;
    cudaLaunchAttribute at[1];
    at[0].id = cudaLaunchAttributeProgrammaticStreamSerialization;
    at[0].val.programmaticStreamSerializationAllowed = 1;
    cudaLaunchConfig_t cfg = {};
    cfg.stream = st; cfg.attrs = at; cfg.numAttrs = 1;
    conv_kernel<<<128, K1_THREADS, sizeof(K1Smem), st>>>(k, v, shift_k, ssm_k, ssm_D);
    cfg.gridDim = dim3(S_ / R_ROWS); cfg.blockDim = dim3(R_THREADS); cfg.dynamicSmemBytes = 0;
    cudaLaunchKernelEx(&cfg, row_kernel, q);
    cfg.gridDim = dim3(128); cfg.blockDim = dim3(G1_THREADS); cfg.dynamicSmemBytes = G1_SMEM;
    cudaLaunchKernelEx(&cfg, gemm1_kernel, mA, mG64, mU64, mG32, mU32);
    cfg.gridDim = dim3(128); cfg.blockDim = dim3(G2_THREADS); cfg.dynamicSmemBytes = G2_SMEM;
    cudaLaunchKernelEx(&cfg, gemm2_kernel, mHH, mWd, out);
}
```

```cpp
#include <cuda_runtime.h>
#include <cuda_bf16.h>
#include <cuda.h>
#include <stdint.h>

typedef __nv_bfloat16 bf16;
constexpr int S_ = 2048, D_ = 512, F_ = 1792;

__device__ bf16 g_yT[D_ * S_];
__device__ bf16 g_h[S_ * D_];
__device__ bf16 g_hn[S_ * D_];
__device__ bf16 g_hh[S_ * F_];

#define TM(k, i)
#define TR(k, i)
__device__ __forceinline__ uint32_t smem_u32(const void* p) { return (uint32_t)__cvta_generic_to_shared(p); }
__device__ __forceinline__ float bf16r(float x) { return __bfloat162float(__float2bfloat16_rn(x)); }
__device__ __forceinline__ float bf_lo(uint32_t w) { return __uint_as_float(w << 16); }
__device__ __forceinline__ float bf_hi(uint32_t w) { return __uint_as_float(w & 0xffff0000u); }
__device__ __forceinline__ uint32_t pack_bf16(float lo, float hi) {
    __nv_bfloat162 v = __floats2bfloat162_rn(lo, hi);
    return *reinterpret_cast<uint32_t*>(&v);
}
__device__ __forceinline__ uint32_t hmul2(uint32_t a, uint32_t b) {
    __nv_bfloat162 r = __hmul2_rn(*reinterpret_cast<__nv_bfloat162*>(&a), *reinterpret_cast<__nv_bfloat162*>(&b));
    return *reinterpret_cast<uint32_t*>(&r);
}
__device__ __forceinline__ uint32_t hadd2(uint32_t a, uint32_t b) {
    __nv_bfloat162 r = __hadd2_rn(*reinterpret_cast<__nv_bfloat162*>(&a), *reinterpret_cast<__nv_bfloat162*>(&b));
    return *reinterpret_cast<uint32_t*>(&r);
}
__device__ __forceinline__ uint4 ldg128(const void* p) {
    uint4 r; asm volatile("ld.global.nc.v4.u32 {%0,%1,%2,%3}, [%4];" : "=r"(r.x), "=r"(r.y), "=r"(r.z), "=r"(r.w) : "l"(p)); return r;
}
__device__ __forceinline__ uint4 ldcg128(const void* p) {
    uint4 r; asm volatile("ld.global.cg.v4.u32 {%0,%1,%2,%3}, [%4];" : "=r"(r.x), "=r"(r.y), "=r"(r.z), "=r"(r.w) : "l"(p)); return r;
}
__device__ __forceinline__ uint32_t ldg16(const void* p) {
    unsigned short r; asm volatile("ld.global.nc.u16 %0, [%1];" : "=h"(r) : "l"(p)); return (uint32_t)r;
}
__device__ __forceinline__ void mbar_init(uint32_t bar, int cnt) { asm volatile("mbarrier.init.shared::cta.b64 [%0], %1;" :: "r"(bar), "r"(cnt)); }
__device__ __forceinline__ void mbar_expect_tx(uint32_t bar, uint32_t bytes) { asm volatile("mbarrier.arrive.expect_tx.shared::cta.b64 _, [%0], %1;" :: "r"(bar), "r"(bytes) : "memory"); }
__device__ __forceinline__ void mbar_arrive(uint32_t bar) { asm volatile("mbarrier.arrive.shared::cta.b64 _, [%0];" :: "r"(bar) : "memory"); }
__device__ __forceinline__ void mbar_arrive_cluster(uint32_t bar, uint32_t cta) {
    asm volatile("{\n.reg .b32 ra;\nmapa.shared::cluster.u32 ra, %0, %1;\nmbarrier.arrive.shared::cluster.b64 _, [ra];\n}" :: "r"(bar), "r"(cta) : "memory");
}
__device__ __forceinline__ void mbar_wait(uint32_t bar, uint32_t parity) {
    asm volatile("{\n.reg .pred P1;\nLAB_WAIT:\nmbarrier.try_wait.parity.shared::cta.b64 P1, [%0], %1;\n@P1 bra DONE;\nbra LAB_WAIT;\nDONE:\n}" :: "r"(bar), "r"(parity) : "memory");
}
__device__ __forceinline__ void mbar_wait_cluster(uint32_t bar, uint32_t parity) {
    asm volatile("{\n.reg .pred P1;\nLAB_WAIT:\nmbarrier.try_wait.parity.acquire.cluster.shared::cta.b64 P1, [%0], %1;\n@P1 bra DONE;\nbra LAB_WAIT;\nDONE:\n}" :: "r"(bar), "r"(parity) : "memory");
}
__device__ __forceinline__ void tma_load_2d(uint32_t dst, const CUtensorMap* map, uint32_t bar, int c0, int c1) {
    asm volatile("cp.async.bulk.tensor.2d.shared::cluster.global.mbarrier::complete_tx::bytes [%0], [%1, {%3, %4}], [%2];"
        :: "r"(dst), "l"(map), "r"(bar), "r"(c0), "r"(c1) : "memory");
}
__device__ __forceinline__ void tma_load_2d_mc(uint32_t dst, const CUtensorMap* map, uint32_t bar, int c0, int c1, uint16_t mask) {
    asm volatile("cp.async.bulk.tensor.2d.shared::cluster.global.mbarrier::complete_tx::bytes.multicast::cluster [%0], [%1, {%3, %4}], [%2], %5;"
        :: "r"(dst), "l"(map), "r"(bar), "r"(c0), "r"(c1), "h"(mask) : "memory");
}
__device__ __forceinline__ void tma_load_3d(uint32_t dst, const CUtensorMap* map, uint32_t bar, int c0, int c1, int c2) {
    asm volatile("cp.async.bulk.tensor.3d.shared::cluster.global.mbarrier::complete_tx::bytes [%0], [%1, {%3, %4, %5}], [%2];"
        :: "r"(dst), "l"(map), "r"(bar), "r"(c0), "r"(c1), "r"(c2) : "memory");
}
__device__ __forceinline__ void cluster_arrive() { asm volatile("barrier.cluster.arrive.aligned;" ::: "memory"); }
__device__ __forceinline__ void cluster_arrive_relaxed() { asm volatile("barrier.cluster.arrive.relaxed.aligned;" ::: "memory"); }
__device__ __forceinline__ void cluster_wait() { asm volatile("barrier.cluster.wait.aligned;" ::: "memory"); }
__device__ __forceinline__ uint32_t mapa(uint32_t addr, uint32_t cta) {
    uint32_t r; asm volatile("mapa.shared::cluster.u32 %0, %1, %2;" : "=r"(r) : "r"(addr), "r"(cta)); return r;
}
__device__ __forceinline__ void st_async_v2(uint32_t addr, uint32_t a, uint32_t b, uint32_t rbar) {
    asm volatile("st.async.weak.shared::cluster.mbarrier::complete_tx::bytes.v2.b32 [%0], {%1, %2}, [%3];" :: "r"(addr), "r"(a), "r"(b), "r"(rbar) : "memory");
}
__device__ __forceinline__ void st_async_v4f(uint32_t addr, float a, float b, float c, float d, uint32_t rbar) {
    asm volatile("st.async.weak.shared::cluster.mbarrier::complete_tx::bytes.v4.f32 [%0], {%1, %2, %3, %4}, [%5];" :: "r"(addr), "f"(a), "f"(b), "f"(c), "f"(d), "r"(rbar) : "memory");
}
__device__ __forceinline__ void wgmma_fence() { asm volatile("wgmma.fence.sync.aligned;" ::: "memory"); }
__device__ __forceinline__ void wgmma_commit() { asm volatile("wgmma.commit_group.sync.aligned;" ::: "memory"); }
template <int N> __device__ __forceinline__ void wgmma_wait() { asm volatile("wgmma.wait_group.sync.aligned %0;" :: "n"(N) : "memory"); }
__device__ __forceinline__ uint64_t make_desc(uint32_t addr, uint32_t lbo_bytes, uint32_t sbo_bytes, uint32_t layout) {
    return (uint64_t)((addr & 0x3FFFF) >> 4) | ((uint64_t)(lbo_bytes >> 4) << 16) | ((uint64_t)(sbo_bytes >> 4) << 32) | ((uint64_t)layout << 62);
}
template <int R> __device__ __forceinline__ void reg_alloc() { asm volatile("setmaxnreg.inc.sync.aligned.u32 %0;" :: "n"(R)); }
template <int R> __device__ __forceinline__ void reg_dealloc() { asm volatile("setmaxnreg.dec.sync.aligned.u32 %0;" :: "n"(R)); }
__device__ __forceinline__ void pdl_launch() { asm volatile("griddepcontrol.launch_dependents;" ::: "memory"); }
__device__ __forceinline__ void pdl_wait() { asm volatile("griddepcontrol.wait;" ::: "memory"); }
__device__ __forceinline__ void prefetch_map(const CUtensorMap* m) { asm volatile("prefetch.tensormap [%0];" :: "l"(m) : "memory"); }
__device__ __forceinline__ void named_bar(int id, int n) { asm volatile("bar.sync %0, %1;" :: "r"(id), "r"(n) : "memory"); }

__device__ __forceinline__ void wgmma_m64n256k16_ss(float (&d)[128], uint64_t descA, uint64_t descB, int scaleD) {
    asm volatile("{\n.reg .pred p;\nsetp.ne.b32 p, %130, 0;\n"
        "wgmma.mma_async.sync.aligned.m64n256k16.f32.bf16.bf16 {%0, %1, %2, %3, %4, %5, %6, %7, %8, %9, %10, %11, %12, %13, %14, %15, %16, %17, %18, %19, %20, %21, %22, %23, %24, %25, %26, %27, %28, %29, %30, %31, %32, %33, %34, %35, %36, %37, %38, %39, %40, %41, %42, %43, %44, %45, %46, %47, %48, %49, %50, %51, %52, %53, %54, %55, %56, %57, %58, %59, %60, %61, %62, %63, %64, %65, %66, %67, %68, %69, %70, %71, %72, %73, %74, %75, %76, %77, %78, %79, %80, %81, %82, %83, %84, %85, %86, %87, %88, %89, %90, %91, %92, %93, %94, %95, %96, %97, %98, %99, %100, %101, %102, %103, %104, %105, %106, %107, %108, %109, %110, %111, %112, %113, %114, %115, %116, %117, %118, %119, %120, %121, %122, %123, %124, %125, %126, %127}, %128, %129, p, 1, 1, 0, 1;\n}\n"
        : "+f"(d[0]), "+f"(d[1]), "+f"(d[2]), "+f"(d[3]), "+f"(d[4]), "+f"(d[5]), "+f"(d[6]), "+f"(d[7]), "+f"(d[8]), "+f"(d[9]), "+f"(d[10]), "+f"(d[11]), "+f"(d[12]), "+f"(d[13]), "+f"(d[14]), "+f"(d[15]), "+f"(d[16]), "+f"(d[17]), "+f"(d[18]), "+f"(d[19]), "+f"(d[20]), "+f"(d[21]), "+f"(d[22]), "+f"(d[23]), "+f"(d[24]), "+f"(d[25]), "+f"(d[26]), "+f"(d[27]), "+f"(d[28]), "+f"(d[29]), "+f"(d[30]), "+f"(d[31]), "+f"(d[32]), "+f"(d[33]), "+f"(d[34]), "+f"(d[35]), "+f"(d[36]), "+f"(d[37]), "+f"(d[38]), "+f"(d[39]), "+f"(d[40]), "+f"(d[41]), "+f"(d[42]), "+f"(d[43]), "+f"(d[44]), "+f"(d[45]), "+f"(d[46]), "+f"(d[47]), "+f"(d[48]), "+f"(d[49]), "+f"(d[50]), "+f"(d[51]), "+f"(d[52]), "+f"(d[53]), "+f"(d[54]), "+f"(d[55]), "+f"(d[56]), "+f"(d[57]), "+f"(d[58]), "+f"(d[59]), "+f"(d[60]), "+f"(d[61]), "+f"(d[62]), "+f"(d[63]), "+f"(d[64]), "+f"(d[65]), "+f"(d[66]), "+f"(d[67]), "+f"(d[68]), "+f"(d[69]), "+f"(d[70]), "+f"(d[71]), "+f"(d[72]), "+f"(d[73]), "+f"(d[74]), "+f"(d[75]), "+f"(d[76]), "+f"(d[77]), "+f"(d[78]), "+f"(d[79]), "+f"(d[80]), "+f"(d[81]), "+f"(d[82]), "+f"(d[83]), "+f"(d[84]), "+f"(d[85]), "+f"(d[86]), "+f"(d[87]), "+f"(d[88]), "+f"(d[89]), "+f"(d[90]), "+f"(d[91]), "+f"(d[92]), "+f"(d[93]), "+f"(d[94]), "+f"(d[95]), "+f"(d[96]), "+f"(d[97]), "+f"(d[98]), "+f"(d[99]), "+f"(d[100]), "+f"(d[101]), "+f"(d[102]), "+f"(d[103]), "+f"(d[104]), "+f"(d[105]), "+f"(d[106]), "+f"(d[107]), "+f"(d[108]), "+f"(d[109]), "+f"(d[110]), "+f"(d[111]), "+f"(d[112]), "+f"(d[113]), "+f"(d[114]), "+f"(d[115]), "+f"(d[116]), "+f"(d[117]), "+f"(d[118]), "+f"(d[119]), "+f"(d[120]), "+f"(d[121]), "+f"(d[122]), "+f"(d[123]), "+f"(d[124]), "+f"(d[125]), "+f"(d[126]), "+f"(d[127])
        : "l"(descA), "l"(descB), "r"(scaleD));
}

__device__ __forceinline__ void wgmma_m64n192k16_ss(float (&d)[96], uint64_t descA, uint64_t descB, int scaleD) {
    asm volatile("{\n.reg .pred p;\nsetp.ne.b32 p, %98, 0;\n"
        "wgmma.mma_async.sync.aligned.m64n192k16.f32.bf16.bf16 {%0, %1, %2, %3, %4, %5, %6, %7, %8, %9, %10, %11, %12, %13, %14, %15, %16, %17, %18, %19, %20, %21, %22, %23, %24, %25, %26, %27, %28, %29, %30, %31, %32, %33, %34, %35, %36, %37, %38, %39, %40, %41, %42, %43, %44, %45, %46, %47, %48, %49, %50, %51, %52, %53, %54, %55, %56, %57, %58, %59, %60, %61, %62, %63, %64, %65, %66, %67, %68, %69, %70, %71, %72, %73, %74, %75, %76, %77, %78, %79, %80, %81, %82, %83, %84, %85, %86, %87, %88, %89, %90, %91, %92, %93, %94, %95}, %96, %97, p, 1, 1, 0, 1;\n}\n"
        : "+f"(d[0]), "+f"(d[1]), "+f"(d[2]), "+f"(d[3]), "+f"(d[4]), "+f"(d[5]), "+f"(d[6]), "+f"(d[7]), "+f"(d[8]), "+f"(d[9]), "+f"(d[10]), "+f"(d[11]), "+f"(d[12]), "+f"(d[13]), "+f"(d[14]), "+f"(d[15]), "+f"(d[16]), "+f"(d[17]), "+f"(d[18]), "+f"(d[19]), "+f"(d[20]), "+f"(d[21]), "+f"(d[22]), "+f"(d[23]), "+f"(d[24]), "+f"(d[25]), "+f"(d[26]), "+f"(d[27]), "+f"(d[28]), "+f"(d[29]), "+f"(d[30]), "+f"(d[31]), "+f"(d[32]), "+f"(d[33]), "+f"(d[34]), "+f"(d[35]), "+f"(d[36]), "+f"(d[37]), "+f"(d[38]), "+f"(d[39]), "+f"(d[40]), "+f"(d[41]), "+f"(d[42]), "+f"(d[43]), "+f"(d[44]), "+f"(d[45]), "+f"(d[46]), "+f"(d[47]), "+f"(d[48]), "+f"(d[49]), "+f"(d[50]), "+f"(d[51]), "+f"(d[52]), "+f"(d[53]), "+f"(d[54]), "+f"(d[55]), "+f"(d[56]), "+f"(d[57]), "+f"(d[58]), "+f"(d[59]), "+f"(d[60]), "+f"(d[61]), "+f"(d[62]), "+f"(d[63]), "+f"(d[64]), "+f"(d[65]), "+f"(d[66]), "+f"(d[67]), "+f"(d[68]), "+f"(d[69]), "+f"(d[70]), "+f"(d[71]), "+f"(d[72]), "+f"(d[73]), "+f"(d[74]), "+f"(d[75]), "+f"(d[76]), "+f"(d[77]), "+f"(d[78]), "+f"(d[79]), "+f"(d[80]), "+f"(d[81]), "+f"(d[82]), "+f"(d[83]), "+f"(d[84]), "+f"(d[85]), "+f"(d[86]), "+f"(d[87]), "+f"(d[88]), "+f"(d[89]), "+f"(d[90]), "+f"(d[91]), "+f"(d[92]), "+f"(d[93]), "+f"(d[94]), "+f"(d[95])
        : "l"(descA), "l"(descB), "r"(scaleD));
}

__device__ __forceinline__ void wgmma_m64n128k16_ss(float (&d)[64], uint64_t descA, uint64_t descB, int scaleD) {
    asm volatile("{\n.reg .pred p;\nsetp.ne.b32 p, %66, 0;\n"
        "wgmma.mma_async.sync.aligned.m64n128k16.f32.bf16.bf16 {%0, %1, %2, %3, %4, %5, %6, %7, %8, %9, %10, %11, %12, %13, %14, %15, %16, %17, %18, %19, %20, %21, %22, %23, %24, %25, %26, %27, %28, %29, %30, %31, %32, %33, %34, %35, %36, %37, %38, %39, %40, %41, %42, %43, %44, %45, %46, %47, %48, %49, %50, %51, %52, %53, %54, %55, %56, %57, %58, %59, %60, %61, %62, %63}, %64, %65, p, 1, 1, 0, 1;\n}\n"
        : "+f"(d[0]), "+f"(d[1]), "+f"(d[2]), "+f"(d[3]), "+f"(d[4]), "+f"(d[5]), "+f"(d[6]), "+f"(d[7]), "+f"(d[8]), "+f"(d[9]), "+f"(d[10]), "+f"(d[11]), "+f"(d[12]), "+f"(d[13]), "+f"(d[14]), "+f"(d[15]), "+f"(d[16]), "+f"(d[17]), "+f"(d[18]), "+f"(d[19]), "+f"(d[20]), "+f"(d[21]), "+f"(d[22]), "+f"(d[23]), "+f"(d[24]), "+f"(d[25]), "+f"(d[26]), "+f"(d[27]), "+f"(d[28]), "+f"(d[29]), "+f"(d[30]), "+f"(d[31]), "+f"(d[32]), "+f"(d[33]), "+f"(d[34]), "+f"(d[35]), "+f"(d[36]), "+f"(d[37]), "+f"(d[38]), "+f"(d[39]), "+f"(d[40]), "+f"(d[41]), "+f"(d[42]), "+f"(d[43]), "+f"(d[44]), "+f"(d[45]), "+f"(d[46]), "+f"(d[47]), "+f"(d[48]), "+f"(d[49]), "+f"(d[50]), "+f"(d[51]), "+f"(d[52]), "+f"(d[53]), "+f"(d[54]), "+f"(d[55]), "+f"(d[56]), "+f"(d[57]), "+f"(d[58]), "+f"(d[59]), "+f"(d[60]), "+f"(d[61]), "+f"(d[62]), "+f"(d[63])
        : "l"(descA), "l"(descB), "r"(scaleD));
}

__device__ __forceinline__ void quad_transpose(uint32_t& r0, uint32_t& r1, uint32_t& r2, uint32_t& r3, int t) {
    const bool o1 = t & 1, o2 = t & 2;
    uint32_t x, y;
    x = o1 ? r0 : r1; y = __shfl_xor_sync(0xffffffffu, x, 1); if (o1) r0 = y; else r1 = y;
    x = o1 ? r2 : r3; y = __shfl_xor_sync(0xffffffffu, x, 1); if (o1) r2 = y; else r3 = y;
    x = o2 ? r0 : r2; y = __shfl_xor_sync(0xffffffffu, x, 2); if (o2) r0 = y; else r2 = y;
    x = o2 ? r1 : r3; y = __shfl_xor_sync(0xffffffffu, x, 2); if (o2) r1 = y; else r3 = y;
}

constexpr int K1_THREADS = 256;
constexpr int UT_PAD = 128;
constexpr int UT_LEN = UT_PAD + S_;
constexpr int KR_LEN = 2080;
constexpr int YP_LEN = S_ + (S_ / 32) * 8;

struct __align__(128) K1Smem {
    bf16 uT[4][UT_LEN];
    bf16 kr[4][2][KR_LEN];
    float yP[4][YP_LEN];
    uint64_t bar;
    uint8_t pad[32768];
};

__device__ __forceinline__ void mma16816(float (&c)[4], uint32_t a0, uint32_t a1, uint32_t a2, uint32_t a3, uint32_t b0, uint32_t b1) {
    asm("mma.sync.aligned.m16n8k16.row.col.f32.bf16.bf16.f32 {%0,%1,%2,%3}, {%4,%5,%6,%7}, {%8,%9}, {%0,%1,%2,%3};"
        : "+f"(c[0]), "+f"(c[1]), "+f"(c[2]), "+f"(c[3])
        : "r"(a0), "r"(a1), "r"(a2), "r"(a3), "r"(b0), "r"(b1));
}
__device__ __forceinline__ void ldsm_x4(uint32_t& r0, uint32_t& r1, uint32_t& r2, uint32_t& r3, uint32_t addr) {
    asm volatile("ldmatrix.sync.aligned.m8n8.x4.shared.b16 {%0,%1,%2,%3}, [%4];" : "=r"(r0), "=r"(r1), "=r"(r2), "=r"(r3) : "r"(addr) : "memory");
}

__device__ __forceinline__ void conv_mma(const bf16* uTc, const bf16* krlane, float (&acc)[16][4], int lane, int half) {
    const int lrow = lane & 7, lk = (lane >> 3) & 1, lt = lane >> 4;
    const uint32_t ubase = smem_u32(uTc) + (UT_PAD + 16 * (8 * lt + lrow) + 8 * lk) * 2;
#pragma unroll 1
    for (int pp = 0; pp < 4; pp++) {
        const int p = half * 4 + pp;
        uint32_t U[16][2];
#pragma unroll
        for (int j = 0; j < 16; j += 2) ldsm_x4(U[j][0], U[j][1], U[j + 1][0], U[j + 1][1], ubase + (j * 128 - p * 16) * 2);
        const uint32_t* kp = reinterpret_cast<const uint32_t*>(krlane - 16 * p);
        const volatile uint32_t* kpv = kp;
        uint32_t a0 = kp[0], a1 = kp[-4], a2 = kp[4], a3 = kpv[0];
#pragma unroll
        for (int q = 0; q < 16; q++) {
            uint32_t b0 = 0, b1 = 0, b2 = 0, b3 = 0;
            if (q < 15) { b0 = kp[-64 * (q + 1)]; b1 = kp[-64 * (q + 1) - 4]; b2 = kp[-64 * (q + 1) + 4]; b3 = kpv[-64 * (q + 1)]; }
#pragma unroll
            for (int n = 15; n >= q; n--) mma16816(acc[n], a0, a1, a2, a3, U[n - q][0], U[n - q][1]);
            a0 = b0; a1 = b1; a2 = b2; a3 = b3;
        }
    }
}

__global__ void __cluster_dims__(2, 1, 1) __launch_bounds__(K1_THREADS, 1)
conv_kernel(const bf16* __restrict__ k, const bf16* __restrict__ v,
            const bf16* __restrict__ shift_k, const bf16* __restrict__ ssm_k, const bf16* __restrict__ ssm_D) {
    extern __shared__ __align__(1024) uint8_t smem_raw[];
    pdl_launch();
    K1Smem& sm = *reinterpret_cast<K1Smem*>(smem_raw);
    const int tid = threadIdx.x, lane = tid & 31, warp = tid >> 5;
    const int bid = blockIdx.x;
    const int rank = bid & 1;
    const int c0 = 8 * (bid >> 1);
    const int cown = c0 + 4 * rank;
#define TMT 0
    TM(0, 0);
    const uint32_t bar = smem_u32(&sm.bar);
    if (tid == 0) {
        mbar_init(bar, 1);
        asm volatile("fence.mbarrier_init.release.cluster;" ::: "memory");
        mbar_expect_tx(bar, 1024 * 4 * 2);
    }
    cluster_arrive_relaxed();

    const int s0 = 1024 * rank + 4 * tid;
    uint4 kk[7], vv[4], sw[4];
#pragma unroll
    for (int i = 0; i < 4; i++) kk[3 + i] = ldg128(k + (size_t)(s0 + i) * D_ + c0);
#pragma unroll
    for (int i = 0; i < 4; i++) vv[i] = ldg128(v + (size_t)(s0 + i) * D_ + c0);
    if (lane == 0) {
#pragma unroll
        for (int i = 0; i < 3; i++) {
            const int s = s0 - 3 + i;
            kk[i] = make_uint4(0, 0, 0, 0);
            if (s >= 0) kk[i] = ldg128(k + (size_t)s * D_ + c0);
        }
    }
#pragma unroll
    for (int i = 0; i < 4; i++) sw[i] = ldg128(shift_k + (size_t)c0 * 4 + 8 * i);
    uint4 kq[4]; uint32_t nx[4];
#pragma unroll
    for (int c = 0; c < 4; c++) {
        const bf16* kr = ssm_k + (size_t)(cown + c) * S_;
        kq[c] = ldg128(kr + 8 * tid);
        nx[c] = 0u;
        if (tid < 255) nx[c] = ldg16(kr + 8 * tid + 8);
    }
    const uint32_t dval = ldg16(ssm_D + cown + (warp >> 1));
    if (tid < 64) *reinterpret_cast<uint4*>(&sm.uT[tid >> 4][(tid & 15) * 8]) = make_uint4(0, 0, 0, 0);
#pragma unroll
    for (int i = 0; i < 3; i++) {
        uint4 t;
        t.x = __shfl_up_sync(0xffffffffu, kk[4 + i].x, 1); t.y = __shfl_up_sync(0xffffffffu, kk[4 + i].y, 1);
        t.z = __shfl_up_sync(0xffffffffu, kk[4 + i].z, 1); t.w = __shfl_up_sync(0xffffffffu, kk[4 + i].w, 1);
        if (lane != 0) kk[i] = t;
    }
    uint32_t kvw[4][4];
    const uint32_t* kkw = reinterpret_cast<const uint32_t*>(kk);
    const uint32_t* vvw = reinterpret_cast<const uint32_t*>(vv);
#pragma unroll
    for (int i2 = 0; i2 < 4; i2++) {
        const uint32_t t0 = __byte_perm(sw[i2].x, sw[i2].z, 0x5410), t1 = __byte_perm(sw[i2].x, sw[i2].z, 0x7632);
        const uint32_t t2 = __byte_perm(sw[i2].y, sw[i2].w, 0x5410), t3 = __byte_perm(sw[i2].y, sw[i2].w, 0x7632);
#pragma unroll
        for (int r = 0; r < 4; r++) {
            uint32_t a = hmul2(kkw[(r + 0) * 4 + i2], t3);
            a = hadd2(a, hmul2(kkw[(r + 1) * 4 + i2], t2));
            a = hadd2(a, hmul2(kkw[(r + 2) * 4 + i2], t1));
            a = hadd2(a, hmul2(kkw[(r + 3) * 4 + i2], t0));
            kvw[r][i2] = hmul2(a, vvw[r * 4 + i2]);
        }
    }
    TM(0, 1);
    cluster_wait();
    {
        const uint32_t rbar = mapa(bar, (uint32_t)(rank ^ 1));
#pragma unroll
        for (int i2 = 0; i2 < 4; i2++) {
#pragma unroll
            for (int e = 0; e < 2; e++) {
                const uint32_t sel = e ? 0x7632 : 0x5410;
                const uint32_t w0 = __byte_perm(kvw[0][i2], kvw[1][i2], sel), w1 = __byte_perm(kvw[2][i2], kvw[3][i2], sel);
                const int cc = 2 * i2 + e;
                if ((cc >> 2) == rank) {
                    *reinterpret_cast<uint2*>(&sm.uT[cc & 3][UT_PAD + s0]) = make_uint2(w0, w1);
                } else {
                    st_async_v2(mapa(smem_u32(&sm.uT[cc & 3][UT_PAD + s0]), (uint32_t)(rank ^ 1)), w0, w1, rbar);
                }
            }
        }
    }
#pragma unroll
    for (int c = 0; c < 4; c++) {
        uint4 a, b;
        a.x = __byte_perm(kq[c].w, 0, 0x1032); a.y = __byte_perm(kq[c].z, 0, 0x1032);
        a.z = __byte_perm(kq[c].y, 0, 0x1032); a.w = __byte_perm(kq[c].x, 0, 0x1032);
        b.x = __byte_perm(nx[c], kq[c].w, 0x7610); b.y = __byte_perm(kq[c].w, kq[c].z, 0x7610);
        b.z = __byte_perm(kq[c].z, kq[c].y, 0x7610); b.w = __byte_perm(kq[c].y, kq[c].x, 0x7610);
        *reinterpret_cast<uint4*>(&sm.kr[c][0][2040 - 8 * tid]) = a;
        *reinterpret_cast<uint4*>(&sm.kr[c][1][2040 - 8 * tid]) = b;
        if (tid == 0) {
            *reinterpret_cast<uint4*>(&sm.kr[c][1][2048]) = make_uint4(kq[c].x & 0xffffu, 0, 0, 0);
        } else if (tid < 8) {
            if (tid < 4) *reinterpret_cast<uint4*>(&sm.kr[c][1][2048 + 8 * tid]) = make_uint4(0, 0, 0, 0);
            else *reinterpret_cast<uint4*>(&sm.kr[c][0][2048 + 8 * (tid - 4)]) = make_uint4(0, 0, 0, 0);
        }
    }
    TM(0, 3);
    __syncthreads();
    mbar_wait_cluster(bar, 0);
    TM(0, 4);

    const int ch = warp >> 1, half = warp & 1;
    const int g = lane >> 2, t = lane & 3;
    float acc[16][4];
#pragma unroll
    for (int i = 0; i < 16; i++) { acc[i][0] = acc[i][1] = acc[i][2] = acc[i][3] = 0.f; }
    const bf16* krlane = (g & 1) ? &sm.kr[ch][0][2047 - g + 2 * t] : &sm.kr[ch][1][2048 - g + 2 * t];
    conv_mma(sm.uT[ch], krlane, acc, lane, half);
    TM(0, 5);
    float* yp = &sm.yP[ch][40 * t + g];
    if (half) {
#pragma unroll
        for (int n = 0; n < 16; n++) {
            yp[160 * n] = acc[n][0];
            yp[160 * n + 16] = acc[n][1];
            yp[160 * n + 8] = acc[n][2];
            yp[160 * n + 24] = acc[n][3];
        }
    }
    named_bar(1 + ch, 64);
    if (!half) {
#pragma unroll
        for (int n = 0; n < 16; n++) {
            yp[160 * n] += acc[n][0];
            yp[160 * n + 16] += acc[n][1];
            yp[160 * n + 8] += acc[n][2];
            yp[160 * n + 24] += acc[n][3];
        }
    }
    named_bar(1 + ch, 64);
    TM(0, 6);
    {
        const int tt = tid & 63;
        bf16* dst = g_yT + (size_t)(cown + ch) * S_;
        const uint32_t d2 = dval * 0x10001u;
#pragma unroll
        for (int j = 0; j < 4; j++) {
            const int s = (j * 64 + tt) * 8;
            const float* src = &sm.yP[ch][s + (s >> 5) * 8];
            const float4 a = *reinterpret_cast<const float4*>(src), b = *reinterpret_cast<const float4*>(src + 4);
            const uint4 kv4 = *reinterpret_cast<const uint4*>(&sm.uT[ch][UT_PAD + s]);
            *reinterpret_cast<uint4*>(dst + s) = make_uint4(hadd2(pack_bf16(a.x, a.y), hmul2(kv4.x, d2)), hadd2(pack_bf16(a.z, a.w), hmul2(kv4.y, d2)),
                                                            hadd2(pack_bf16(b.x, b.y), hmul2(kv4.z, d2)), hadd2(pack_bf16(b.z, b.w), hmul2(kv4.w, d2)));
        }
    }
    TM(0, 7);
#undef TMT
}

constexpr int R_THREADS = 512;
constexpr int R_ROWS = 16;

__device__ __forceinline__ float warp_sum(float s) {
#pragma unroll
    for (int o = 16; o > 0; o >>= 1) s += __shfl_xor_sync(0xffffffffu, s, o);
    return s;
}
__device__ __forceinline__ uint32_t hsub2(uint32_t a, uint32_t b) {
    __nv_bfloat162 r = __hsub2_rn(*reinterpret_cast<__nv_bfloat162*>(&a), *reinterpret_cast<__nv_bfloat162*>(&b));
    return *reinterpret_cast<uint32_t*>(&r);
}
__device__ __forceinline__ void ln_row(const uint32_t (&x)[8], uint32_t (&o)[8]) {
    float s0 = 0.f, s1 = 0.f;
#pragma unroll
    for (int i = 0; i < 8; i++) { s0 += bf_lo(x[i]); s1 += bf_hi(x[i]); }
    const float mean = warp_sum(s0 + s1) * (1.0f / D_);
    float ss0 = 0.f, ss1 = 0.f;
#pragma unroll
    for (int i = 0; i < 8; i++) { const float d0 = bf_lo(x[i]) - mean, d1 = bf_hi(x[i]) - mean; ss0 += d0 * d0; ss1 += d1 * d1; }
    const float var = bf16r(warp_sum(ss0 + ss1) * (1.0f / D_));
    const float rinv = 1.0f / bf16r(sqrtf(bf16r(var + 1e-5f)));
    const uint32_t m2 = pack_bf16(mean, mean);
#pragma unroll
    for (int i = 0; i < 8; i++) {
        const uint32_t d = hsub2(x[i], m2);
        o[i] = pack_bf16(bf_lo(d) * rinv, bf_hi(d) * rinv);
    }
}

__global__ void __launch_bounds__(R_THREADS, 1)
row_kernel(const bf16* __restrict__ q) {
    __shared__ __align__(16) uint32_t ys[R_ROWS][D_ / 2 + 4];
    const int tid = threadIdx.x, lane = tid & 31, warp = tid >> 5;
    const int s0 = blockIdx.x * R_ROWS;
#define TMT 0
    TM(1, 0);
    pdl_launch();
    const int r0 = s0 + warp;
    const int p = tid & 255, hs = tid >> 8;
    const uint4 qa = ldg128(q + (size_t)r0 * D_ + 8 * lane);
    const uint4 qb = ldg128(q + (size_t)r0 * D_ + 8 * (lane + 32));
    const uint32_t x[8] = {qa.x, qa.y, qa.z, qa.w, qb.x, qb.y, qb.z, qb.w};
    uint32_t qn[8];
    ln_row(x, qn);
    pdl_wait();
    {
        const bf16* y0 = g_yT + (size_t)(2 * p) * S_ + s0 + 8 * hs;
        const uint4 ya = ldcg128(y0);
        const uint4 yb = ldcg128(y0 + S_);
        const uint32_t aw[4] = {ya.x, ya.y, ya.z, ya.w};
        const uint32_t bw[4] = {yb.x, yb.y, yb.z, yb.w};
#pragma unroll
        for (int j = 0; j < 4; j++) {
            ys[8 * hs + 2 * j][p] = __byte_perm(aw[j], bw[j], 0x5410);
            ys[8 * hs + 2 * j + 1][p] = __byte_perm(aw[j], bw[j], 0x7632);
        }
    }
    __syncthreads();
    TM(1, 1);
    uint32_t h[8], hn[8];
#pragma unroll
    for (int i = 0; i < 2; i++) {
        const uint4 yw4 = *reinterpret_cast<const uint4*>(&ys[warp][4 * (lane + 32 * i)]);
        const uint32_t yw[4] = {yw4.x, yw4.y, yw4.z, yw4.w};
#pragma unroll
        for (int j = 0; j < 4; j++) h[4 * i + j] = hadd2(x[4 * i + j], hmul2(qn[4 * i + j], yw[j]));
    }
    ln_row(h, hn);
#pragma unroll
    for (int i = 0; i < 2; i++) {
        const size_t off = (size_t)r0 * D_ + 8 * (lane + 32 * i);
        *reinterpret_cast<uint4*>(g_h + off) = make_uint4(h[4 * i], h[4 * i + 1], h[4 * i + 2], h[4 * i + 3]);
        *reinterpret_cast<uint4*>(g_hn + off) = make_uint4(hn[4 * i], hn[4 * i + 1], hn[4 * i + 2], hn[4 * i + 3]);
    }
    TM(1, 2);
#undef TMT
}

constexpr int G1_THREADS = 384;
constexpr int G1_STAGES = 3;
constexpr int G1_A_BYTES = 8 * 16384;
constexpr int G1_B_STAGE = 32768;
constexpr int G1_OFF_B = G1_A_BYTES;
constexpr int G1_OFF_BAR = G1_OFF_B + G1_STAGES * G1_B_STAGE;
constexpr int G1_SMEM = G1_OFF_BAR + 256;

__device__ __forceinline__ float sigmoid_fast(float x) {
    float t; asm("tanh.approx.f32 %0, %1;" : "=f"(t) : "f"(0.5f * x));
    return fmaf(t, 0.5f, 0.5f);
}

template <int NT>
__device__ __forceinline__ void g1_epilogue(const float (&acc)[NT * 8], bf16* out0, int t) {
#pragma unroll
    for (int j0 = 0; j0 < NT; j0 += 4) {
        uint32_t P0[4], P1[4];
#pragma unroll
        for (int jj = 0; jj < 4; jj++) {
            const int j = j0 + jj;
            float r[4];
#pragma unroll
            for (int e = 0; e < 4; e++) r[e] = sigmoid_fast(acc[4 * j + e]) * acc[4 * (NT + j) + e];
            P0[jj] = pack_bf16(r[0], r[1]);
            P1[jj] = pack_bf16(r[2], r[3]);
        }
        quad_transpose(P0[0], P0[1], P0[2], P0[3], t);
        quad_transpose(P1[0], P1[1], P1[2], P1[3], t);
        *reinterpret_cast<uint4*>(out0 + 8 * (j0 + t)) = make_uint4(P0[0], P0[1], P0[2], P0[3]);
        *reinterpret_cast<uint4*>(out0 + 8 * F_ + 8 * (j0 + t)) = make_uint4(P1[0], P1[1], P1[2], P1[3]);
    }
}

__global__ void __cluster_dims__(2, 1, 1) __launch_bounds__(G1_THREADS, 1)
gemm1_kernel(const __grid_constant__ CUtensorMap mapA, const __grid_constant__ CUtensorMap mapG4, const __grid_constant__ CUtensorMap mapU4,
             const __grid_constant__ CUtensorMap mapG3, const __grid_constant__ CUtensorMap mapU3) {
    extern __shared__ __align__(1024) uint8_t smem_raw[];
    const uint32_t sb = smem_u32(smem_raw);
    const int tid = threadIdx.x, lane = tid & 31, warp = tid >> 5, wgi = tid >> 7;
    const int rank = blockIdx.x & 1;
    const int cb = blockIdx.x & 7, rb = blockIdx.x >> 3;
#define TMT 128
    TM(2, 0);
    pdl_launch();
    if (tid == 32) { prefetch_map(&mapA); prefetch_map(&mapG3); prefetch_map(&mapU3); }
    const uint32_t barA = sb + G1_OFF_BAR;
    const uint32_t barF = barA + 64;
    const uint32_t barE = barF + 8 * G1_STAGES;
    if (tid == 0) {
        for (int i = 0; i < 8; i++) mbar_init(barA + 8 * i, 1);
        for (int i = 0; i < G1_STAGES; i++) { mbar_init(barF + 8 * i, 1); mbar_init(barE + 8 * i, 2); }
        for (int i = 0; i < 8; i++) mbar_expect_tx(barA + 8 * i, 16384);
        asm volatile("fence.mbarrier_init.release.cluster;" ::: "memory");
        for (int it = 0; it < G1_STAGES; it++) {
            const uint32_t dst = sb + G1_OFF_B + it * G1_B_STAGE;
            mbar_expect_tx(barF + 8 * it, 32768);
            tma_load_3d(dst, &mapG4, barF + 8 * it, 0, it * 64, cb * 7);
            tma_load_3d(dst + 16384, &mapU4, barF + 8 * it, 0, it * 64, cb * 7);
        }
    }
    __syncthreads();
    cluster_arrive_relaxed();
    cluster_wait();

    if (wgi == 0) {
        reg_dealloc<40>();
        if (lane == 0 && warp == 0) {
            int st = 0, ph = 0;
            for (int it = G1_STAGES; it < 16; it++) {
                const int kc = it & 7;
                mbar_wait(barE + 8 * st, ph);
                const uint32_t dst = sb + G1_OFF_B + st * G1_B_STAGE;
                if (it < 8) {
                    mbar_expect_tx(barF + 8 * st, 32768);
                    tma_load_3d(dst, &mapG4, barF + 8 * st, 0, kc * 64, cb * 7);
                    tma_load_3d(dst + 16384, &mapU4, barF + 8 * st, 0, kc * 64, cb * 7);
                } else {
                    mbar_expect_tx(barF + 8 * st, 24576);
                    tma_load_3d(dst, &mapG3, barF + 8 * st, 0, kc * 64, cb * 7 + 4);
                    tma_load_3d(dst + 12288, &mapU3, barF + 8 * st, 0, kc * 64, cb * 7 + 4);
                }
                if (++st == G1_STAGES) { st = 0; ph ^= 1; }
            }
        } else if (lane == 0 && warp == 1) {
            pdl_wait();
            for (int i = 0; i < 4; i++) {
                const int c = 2 * i + rank;
                tma_load_2d_mc(sb + c * 16384, &mapA, barA + 8 * c, c * 64, rb * 128, (uint16_t)3);
            }
        }
        __syncwarp();
    } else {
        reg_alloc<232>();
        pdl_wait();
        const int cw = wgi - 1;
        const int g = lane >> 2, t = lane & 3, wl = warp & 3, tl = tid & 127;
        bf16* outp = g_hh + (size_t)(rb * 128 + cw * 64 + wl * 16 + g) * F_ + cb * 224;
        int st = 0, ph = 0;
        {
            float acc[128];
#pragma unroll 1
            for (int kc = 0; kc < 8; kc++) {
                mbar_wait(barA + 8 * kc, 0);
                mbar_wait(barF + 8 * st, ph);
                if (tl == 0 && cw == 0) TR(1, kc);
                wgmma_fence();
                const uint32_t aaddr = sb + kc * 16384 + cw * 8192;
                const uint32_t baddr = sb + G1_OFF_B + st * G1_B_STAGE;
#pragma unroll
                for (int kk = 0; kk < 4; kk++)
                    wgmma_m64n256k16_ss(acc, make_desc(aaddr + kk * 32, 16, 1024, 1), make_desc(baddr + kk * 1024, 4096, 512, 2), (kc | kk) != 0);
                wgmma_commit();
                wgmma_wait<0>();
                if (tl == 0) mbar_arrive(barE + 8 * st);
                if (++st == G1_STAGES) { st = 0; ph ^= 1; }
            }
            TM(2, 1);
            g1_epilogue<16>(acc, outp, t);
            TM(2, 2);
        }
        {
            float acc[96];
#pragma unroll 1
            for (int kc = 0; kc < 8; kc++) {
                mbar_wait(barF + 8 * st, ph);
                if (tl == 0 && cw == 0) TR(1, 8 + kc);
                wgmma_fence();
                const uint32_t aaddr = sb + kc * 16384 + cw * 8192;
                const uint32_t baddr = sb + G1_OFF_B + st * G1_B_STAGE;
#pragma unroll
                for (int kk = 0; kk < 4; kk++)
                    wgmma_m64n192k16_ss(acc, make_desc(aaddr + kk * 32, 16, 1024, 1), make_desc(baddr + kk * 1024, 4096, 512, 2), (kc | kk) != 0);
                wgmma_commit();
                wgmma_wait<0>();
                if (tl == 0) mbar_arrive(barE + 8 * st);
                if (++st == G1_STAGES) { st = 0; ph ^= 1; }
            }
            TM(2, 3);
            g1_epilogue<12>(acc, outp + 128, t);
            TM(2, 4);
        }
    }
}

constexpr int G2_THREADS = 384;
constexpr int G2_STAGES = 6;
constexpr int G2_STAGE = 32768;
constexpr int G2_OFF_X = G2_STAGES * G2_STAGE;
constexpr int G2_OFF_BAR = G2_OFF_X + 32768;
constexpr int G2_SMEM = G2_OFF_BAR + 128;
constexpr int G2_KSTEPS = 14;

__global__ void __cluster_dims__(2, 1, 1) __launch_bounds__(G2_THREADS, 1)
gemm2_kernel(const __grid_constant__ CUtensorMap mapHH, const __grid_constant__ CUtensorMap mapWd, bf16* __restrict__ out) {
    extern __shared__ __align__(1024) uint8_t smem_raw[];
    const uint32_t sb = smem_u32(smem_raw);
    const int tid = threadIdx.x, lane = tid & 31, warp = tid >> 5, wgi = tid >> 7;
    const int ks = blockIdx.x & 1, nb = (blockIdx.x >> 1) & 3, rb = blockIdx.x >> 3;
    TM(3, 0);
    if (tid == 32) { prefetch_map(&mapHH); }
    const uint32_t barF = sb + G2_OFF_BAR;
    const uint32_t barE = barF + 8 * G2_STAGES;
    const uint32_t barX = barE + 8 * G2_STAGES;
    if (tid == 0) {
        for (int i = 0; i < G2_STAGES; i++) { mbar_init(barF + 8 * i, 1); mbar_init(barE + 8 * i, 2); }
        mbar_init(barX, 1);
        asm volatile("fence.mbarrier_init.release.cluster;" ::: "memory");
        mbar_expect_tx(barX, 32768);
        for (int it = 0; it < G2_STAGES; it++) {
            mbar_expect_tx(barF + 8 * it, 32768);
            tma_load_3d(sb + it * G2_STAGE + 16384, &mapWd, barF + 8 * it, 0, ks * 896 + it * 64, nb * 2);
        }
    }
    __syncthreads();
    cluster_arrive_relaxed();

    if (wgi == 0) {
        if (tid == 0) {
            pdl_wait();
            for (int it = 0; it < G2_STAGES; it++)
                tma_load_2d(sb + it * G2_STAGE, &mapHH, barF + 8 * it, ks * 896 + it * 64, rb * 128);
            int st = 0, ph = 0;
            for (int it = G2_STAGES; it < G2_KSTEPS; it++) {
                mbar_wait(barE + 8 * st, ph);
                const uint32_t dst = sb + st * G2_STAGE;
                const int k0 = ks * 896 + it * 64;
                mbar_expect_tx(barF + 8 * st, 32768);
                tma_load_2d(dst, &mapHH, barF + 8 * st, k0, rb * 128);
                tma_load_3d(dst + 16384, &mapWd, barF + 8 * st, 0, k0, nb * 2);
                if (++st == G2_STAGES) { st = 0; ph ^= 1; }
            }
        }
        __syncwarp();
        cluster_wait();
    } else {
        const int cw = wgi - 1;
        const int g = lane >> 2, t = lane & 3, wl = warp & 3;
        const int tl = tid & 127;
        int st = 0, ph = 0;
        float acc[64];
        pdl_wait();
#pragma unroll 1
        for (int it = 0; it < G2_KSTEPS; it++) {
            mbar_wait(barF + 8 * st, ph);
            if (it == 0) TM(3, 1);
            wgmma_fence();
            const uint32_t aaddr = sb + st * G2_STAGE + cw * 8192;
            const uint32_t baddr = sb + st * G2_STAGE + 16384;
#pragma unroll
            for (int kk = 0; kk < 4; kk++)
                wgmma_m64n128k16_ss(acc, make_desc(aaddr + kk * 32, 16, 1024, 1), make_desc(baddr + kk * 2048, 8192, 1024, 1), (it | kk) != 0);
            wgmma_commit();
            wgmma_wait<0>();
            if (tl == 0) mbar_arrive(barE + 8 * st);
            if (++st == G2_STAGES) { st = 0; ph ^= 1; }
        }
        TM(3, 2);
        cluster_wait();
        if (cw != ks) {
            const uint32_t dst = mapa(sb + G2_OFF_X + tl * 16, (uint32_t)(ks ^ 1));
            const uint32_t rbar = mapa(barX, (uint32_t)(ks ^ 1));
#pragma unroll
            for (int i = 0; i < 16; i++) st_async_v4f(dst + i * 2048, acc[4 * i], acc[4 * i + 1], acc[4 * i + 2], acc[4 * i + 3], rbar);
        } else {
            const float4* xb = reinterpret_cast<const float4*>(smem_raw + G2_OFF_X) + tl;
            const int row0 = rb * 128 + cw * 64 + wl * 16 + g;
            const bf16* h0 = g_h + (size_t)row0 * D_ + nb * 128;
            bf16* o0 = out + (size_t)row0 * D_ + nb * 128;
            uint32_t ha[16], hb[16];
#pragma unroll
            for (int j = 0; j < 16; j++) {
                ha[j] = __ldcg(reinterpret_cast<const uint32_t*>(h0 + 8 * j + 2 * t));
                hb[j] = __ldcg(reinterpret_cast<const uint32_t*>(h0 + 8 * D_ + 8 * j + 2 * t));
            }
            mbar_wait_cluster(barX, 0);
            TM(3, 4);
#pragma unroll
            for (int j0 = 0; j0 < 16; j0 += 4) {
                uint32_t P0[4], P1[4];
#pragma unroll
                for (int jj = 0; jj < 4; jj++) {
                    const int j = j0 + jj;
                    const float4 x = xb[j * 128];
                    P0[jj] = pack_bf16(bf_lo(ha[j]) + bf16r(acc[4 * j] + x.x), bf_hi(ha[j]) + bf16r(acc[4 * j + 1] + x.y));
                    P1[jj] = pack_bf16(bf_lo(hb[j]) + bf16r(acc[4 * j + 2] + x.z), bf_hi(hb[j]) + bf16r(acc[4 * j + 3] + x.w));
                }
                quad_transpose(P0[0], P0[1], P0[2], P0[3], t);
                quad_transpose(P1[0], P1[1], P1[2], P1[3], t);
                *reinterpret_cast<uint4*>(o0 + 8 * (j0 + t)) = make_uint4(P0[0], P0[1], P0[2], P0[3]);
                *reinterpret_cast<uint4*>(o0 + 8 * D_ + 8 * (j0 + t)) = make_uint4(P1[0], P1[1], P1[2], P1[3]);
            }
        }
        TM(3, 5);
    }
#undef TMT
}

typedef CUresult (*EncodeFn)(CUtensorMap*, CUtensorMapDataType, cuuint32_t, void*, const cuuint64_t*, const cuuint64_t*,
                             const cuuint32_t*, const cuuint32_t*, CUtensorMapInterleave, CUtensorMapSwizzle,
                             CUtensorMapL2promotion, CUtensorMapFloatOOBfill);

static void enc2d(EncodeFn enc, CUtensorMap* m, const void* p, int rows, int cols, int brows, int bcols) {
    cuuint64_t dims[2] = {(cuuint64_t)cols, (cuuint64_t)rows};
    cuuint64_t strides[1] = {(cuuint64_t)cols * 2};
    cuuint32_t box[2] = {(cuuint32_t)bcols, (cuuint32_t)brows};
    cuuint32_t es[2] = {1, 1};
    enc(m, CU_TENSOR_MAP_DATA_TYPE_BFLOAT16, 2, const_cast<void*>(p), dims, strides, box, es, CU_TENSOR_MAP_INTERLEAVE_NONE,
        bcols == 32 ? CU_TENSOR_MAP_SWIZZLE_64B : CU_TENSOR_MAP_SWIZZLE_128B, CU_TENSOR_MAP_L2_PROMOTION_L2_128B, CU_TENSOR_MAP_FLOAT_OOB_FILL_NONE);
}
static void enc3d(EncodeFn enc, CUtensorMap* m, const void* p, int rows, int cols, int atom, int brows, int natoms) {
    cuuint64_t dims[3] = {(cuuint64_t)atom, (cuuint64_t)rows, (cuuint64_t)(cols / atom)};
    cuuint64_t strides[2] = {(cuuint64_t)cols * 2, (cuuint64_t)atom * 2};
    cuuint32_t box[3] = {(cuuint32_t)atom, (cuuint32_t)brows, (cuuint32_t)natoms};
    cuuint32_t es[3] = {1, 1, 1};
    enc(m, CU_TENSOR_MAP_DATA_TYPE_BFLOAT16, 3, const_cast<void*>(p), dims, strides, box, es, CU_TENSOR_MAP_INTERLEAVE_NONE,
        atom == 32 ? CU_TENSOR_MAP_SWIZZLE_64B : CU_TENSOR_MAP_SWIZZLE_128B, CU_TENSOR_MAP_L2_PROMOTION_L2_128B, CU_TENSOR_MAP_FLOAT_OOB_FILL_NONE);
}

extern "C" void kernel_launch(void* const* d_in, const int* in_sizes, int n_in, void* d_out, int out_size) {
    const bf16* q = (const bf16*)d_in[0];
    const bf16* k = (const bf16*)d_in[1];
    const bf16* v = (const bf16*)d_in[2];
    const bf16* shift_k = (const bf16*)d_in[3];
    const bf16* ssm_k = (const bf16*)d_in[4];
    const bf16* ssm_D = (const bf16*)d_in[5];
    const bf16* wg = (const bf16*)d_in[7];
    const bf16* wu = (const bf16*)d_in[8];
    const bf16* wd = (const bf16*)d_in[9];
    bf16* out = (bf16*)d_out;

    static EncodeFn enc = nullptr;
    static void *p_hn = nullptr, *p_hh = nullptr;
    if (!enc) {
        void* fn = nullptr; cudaDriverEntryPointQueryResult qr;
        cudaGetDriverEntryPoint("cuTensorMapEncodeTiled", &fn, cudaEnableDefault, &qr);
        enc = (EncodeFn)fn;
        cudaGetSymbolAddress(&p_hn, g_hn);
        cudaGetSymbolAddress(&p_hh, g_hh);
        cudaFuncSetAttribute(conv_kernel, cudaFuncAttributeMaxDynamicSharedMemorySize, (int)sizeof(K1Smem));
        cudaFuncSetAttribute(gemm1_kernel, cudaFuncAttributeMaxDynamicSharedMemorySize, G1_SMEM);
        cudaFuncSetAttribute(gemm2_kernel, cudaFuncAttributeMaxDynamicSharedMemorySize, G2_SMEM);
    }
    CUtensorMap mA, mG64, mU64, mG32, mU32, mHH, mWd;
    enc2d(enc, &mA, p_hn, S_, D_, 128, 64);
    enc3d(enc, &mG64, wg, D_, F_, 32, 64, 4);
    enc3d(enc, &mU64, wu, D_, F_, 32, 64, 4);
    enc3d(enc, &mG32, wg, D_, F_, 32, 64, 3);
    enc3d(enc, &mU32, wu, D_, F_, 32, 64, 3);
    enc2d(enc, &mHH, p_hh, S_, F_, 128, 64);
    enc3d(enc, &mWd, wd, F_, D_, 64, 64, 2);

    cudaStream_t st = cudaStreamPerThread;
    cudaLaunchAttribute at[1];
    at[0].id = cudaLaunchAttributeProgrammaticStreamSerialization;
    at[0].val.programmaticStreamSerializationAllowed = 1;
    cudaLaunchConfig_t cfg = {};
    cfg.stream = st; cfg.attrs = at; cfg.numAttrs = 1;
    conv_kernel<<<128, K1_THREADS, sizeof(K1Smem), st>>>(k, v, shift_k, ssm_k, ssm_D);
    cfg.gridDim = dim3(S_ / R_ROWS); cfg.blockDim = dim3(R_THREADS); cfg.dynamicSmemBytes = 0;
    cudaLaunchKernelEx(&cfg, row_kernel, q);
    cfg.gridDim = dim3(128); cfg.blockDim = dim3(G1_THREADS); cfg.dynamicSmemBytes = G1_SMEM;
    cudaLaunchKernelEx(&cfg, gemm1_kernel, mA, mG64, mU64, mG32, mU32);
    cfg.gridDim = dim3(128); cfg.blockDim = dim3(G2_THREADS); cfg.dynamicSmemBytes = G2_SMEM;
    cudaLaunchKernelEx(&cfg, gemm2_kernel, mHH, mWd, out);
}
```

```cpp
#include <cuda_runtime.h>
#include <cuda_bf16.h>
#include <cuda.h>
#include <stdint.h>

typedef __nv_bfloat16 bf16;
constexpr int S_ = 2048, D_ = 512, F_ = 1792;

__device__ bf16 g_yT[D_ * S_];
__device__ bf16 g_h[S_ * D_];
__device__ bf16 g_hn[S_ * D_];
__device__ bf16 g_hh[S_ * F_];
__device__ unsigned int g_cnt[16];

#define TM(k, i)
#define TR(k, i)
__device__ __forceinline__ uint32_t smem_u32(const void* p) { return (uint32_t)__cvta_generic_to_shared(p); }
__device__ __forceinline__ float bf16r(float x) { return __bfloat162float(__float2bfloat16_rn(x)); }
__device__ __forceinline__ float bf_lo(uint32_t w) { return __uint_as_float(w << 16); }
__device__ __forceinline__ float bf_hi(uint32_t w) { return __uint_as_float(w & 0xffff0000u); }
__device__ __forceinline__ uint32_t pack_bf16(float lo, float hi) {
    __nv_bfloat162 v = __floats2bfloat162_rn(lo, hi);
    return *reinterpret_cast<uint32_t*>(&v);
}
__device__ __forceinline__ uint32_t hmul2(uint32_t a, uint32_t b) {
    __nv_bfloat162 r = __hmul2_rn(*reinterpret_cast<__nv_bfloat162*>(&a), *reinterpret_cast<__nv_bfloat162*>(&b));
    return *reinterpret_cast<uint32_t*>(&r);
}
__device__ __forceinline__ uint32_t hadd2(uint32_t a, uint32_t b) {
    __nv_bfloat162 r = __hadd2_rn(*reinterpret_cast<__nv_bfloat162*>(&a), *reinterpret_cast<__nv_bfloat162*>(&b));
    return *reinterpret_cast<uint32_t*>(&r);
}
__device__ __forceinline__ uint4 ldg128(const void* p) {
    uint4 r; asm volatile("ld.global.nc.v4.u32 {%0,%1,%2,%3}, [%4];" : "=r"(r.x), "=r"(r.y), "=r"(r.z), "=r"(r.w) : "l"(p)); return r;
}
__device__ __forceinline__ uint4 ldcg128(const void* p) {
    uint4 r; asm volatile("ld.global.cg.v4.u32 {%0,%1,%2,%3}, [%4];" : "=r"(r.x), "=r"(r.y), "=r"(r.z), "=r"(r.w) : "l"(p)); return r;
}
__device__ __forceinline__ uint32_t ldg16(const void* p) {
    unsigned short r; asm volatile("ld.global.nc.u16 %0, [%1];" : "=h"(r) : "l"(p)); return (uint32_t)r;
}
__device__ __forceinline__ void mbar_init(uint32_t bar, int cnt) { asm volatile("mbarrier.init.shared::cta.b64 [%0], %1;" :: "r"(bar), "r"(cnt)); }
__device__ __forceinline__ void mbar_expect_tx(uint32_t bar, uint32_t bytes) { asm volatile("mbarrier.arrive.expect_tx.shared::cta.b64 _, [%0], %1;" :: "r"(bar), "r"(bytes) : "memory"); }
__device__ __forceinline__ void mbar_arrive(uint32_t bar) { asm volatile("mbarrier.arrive.shared::cta.b64 _, [%0];" :: "r"(bar) : "memory"); }
__device__ __forceinline__ void mbar_arrive_cluster(uint32_t bar, uint32_t cta) {
    asm volatile("{\n.reg .b32 ra;\nmapa.shared::cluster.u32 ra, %0, %1;\nmbarrier.arrive.shared::cluster.b64 _, [ra];\n}" :: "r"(bar), "r"(cta) : "memory");
}
__device__ __forceinline__ void mbar_wait(uint32_t bar, uint32_t parity) {
    asm volatile("{\n.reg .pred P1;\nLAB_WAIT:\nmbarrier.try_wait.parity.shared::cta.b64 P1, [%0], %1;\n@P1 bra DONE;\nbra LAB_WAIT;\nDONE:\n}" :: "r"(bar), "r"(parity) : "memory");
}
__device__ __forceinline__ void mbar_wait_cluster(uint32_t bar, uint32_t parity) {
    asm volatile("{\n.reg .pred P1;\nLAB_WAIT:\nmbarrier.try_wait.parity.acquire.cluster.shared::cta.b64 P1, [%0], %1;\n@P1 bra DONE;\nbra LAB_WAIT;\nDONE:\n}" :: "r"(bar), "r"(parity) : "memory");
}
__device__ __forceinline__ void tma_load_2d(uint32_t dst, const CUtensorMap* map, uint32_t bar, int c0, int c1) {
    asm volatile("cp.async.bulk.tensor.2d.shared::cluster.global.mbarrier::complete_tx::bytes [%0], [%1, {%3, %4}], [%2];"
        :: "r"(dst), "l"(map), "r"(bar), "r"(c0), "r"(c1) : "memory");
}
__device__ __forceinline__ void tma_load_2d_mc(uint32_t dst, const CUtensorMap* map, uint32_t bar, int c0, int c1, uint16_t mask) {
    asm volatile("cp.async.bulk.tensor.2d.shared::cluster.global.mbarrier::complete_tx::bytes.multicast::cluster [%0], [%1, {%3, %4}], [%2], %5;"
        :: "r"(dst), "l"(map), "r"(bar), "r"(c0), "r"(c1), "h"(mask) : "memory");
}
__device__ __forceinline__ void tma_load_3d(uint32_t dst, const CUtensorMap* map, uint32_t bar, int c0, int c1, int c2) {
    asm volatile("cp.async.bulk.tensor.3d.shared::cluster.global.mbarrier::complete_tx::bytes [%0], [%1, {%3, %4, %5}], [%2];"
        :: "r"(dst), "l"(map), "r"(bar), "r"(c0), "r"(c1), "r"(c2) : "memory");
}
__device__ __forceinline__ void cluster_arrive() { asm volatile("barrier.cluster.arrive.aligned;" ::: "memory"); }
__device__ __forceinline__ void cluster_arrive_relaxed() { asm volatile("barrier.cluster.arrive.relaxed.aligned;" ::: "memory"); }
__device__ __forceinline__ void cluster_wait() { asm volatile("barrier.cluster.wait.aligned;" ::: "memory"); }
__device__ __forceinline__ uint32_t mapa(uint32_t addr, uint32_t cta) {
    uint32_t r; asm volatile("mapa.shared::cluster.u32 %0, %1, %2;" : "=r"(r) : "r"(addr), "r"(cta)); return r;
}
__device__ __forceinline__ void st_async_v2(uint32_t addr, uint32_t a, uint32_t b, uint32_t rbar) {
    asm volatile("st.async.weak.shared::cluster.mbarrier::complete_tx::bytes.v2.b32 [%0], {%1, %2}, [%3];" :: "r"(addr), "r"(a), "r"(b), "r"(rbar) : "memory");
}
__device__ __forceinline__ void st_async_v4f(uint32_t addr, float a, float b, float c, float d, uint32_t rbar) {
    asm volatile("st.async.weak.shared::cluster.mbarrier::complete_tx::bytes.v4.f32 [%0], {%1, %2, %3, %4}, [%5];" :: "r"(addr), "f"(a), "f"(b), "f"(c), "f"(d), "r"(rbar) : "memory");
}
__device__ __forceinline__ void wgmma_fence() { asm volatile("wgmma.fence.sync.aligned;" ::: "memory"); }
__device__ __forceinline__ void wgmma_commit() { asm volatile("wgmma.commit_group.sync.aligned;" ::: "memory"); }
template <int N> __device__ __forceinline__ void wgmma_wait() { asm volatile("wgmma.wait_group.sync.aligned %0;" :: "n"(N) : "memory"); }
__device__ __forceinline__ uint64_t make_desc(uint32_t addr, uint32_t lbo_bytes, uint32_t sbo_bytes, uint32_t layout) {
    return (uint64_t)((addr & 0x3FFFF) >> 4) | ((uint64_t)(lbo_bytes >> 4) << 16) | ((uint64_t)(sbo_bytes >> 4) << 32) | ((uint64_t)layout << 62);
}
template <int R> __device__ __forceinline__ void reg_alloc() { asm volatile("setmaxnreg.inc.sync.aligned.u32 %0;" :: "n"(R)); }
template <int R> __device__ __forceinline__ void reg_dealloc() { asm volatile("setmaxnreg.dec.sync.aligned.u32 %0;" :: "n"(R)); }
__device__ __forceinline__ void pdl_launch() { asm volatile("griddepcontrol.launch_dependents;" ::: "memory"); }
__device__ __forceinline__ void pdl_wait() { asm volatile("griddepcontrol.wait;" ::: "memory"); }
__device__ __forceinline__ void prefetch_map(const CUtensorMap* m) { asm volatile("prefetch.tensormap [%0];" :: "l"(m) : "memory"); }
__device__ __forceinline__ void named_bar(int id, int n) { asm volatile("bar.sync %0, %1;" :: "r"(id), "r"(n) : "memory"); }

__device__ __forceinline__ void wgmma_m64n256k16_ss(float (&d)[128], uint64_t descA, uint64_t descB, int scaleD) {
    asm volatile("{\n.reg .pred p;\nsetp.ne.b32 p, %130, 0;\n"
        "wgmma.mma_async.sync.aligned.m64n256k16.f32.bf16.bf16 {%0, %1, %2, %3, %4, %5, %6, %7, %8, %9, %10, %11, %12, %13, %14, %15, %16, %17, %18, %19, %20, %21, %22, %23, %24, %25, %26, %27, %28, %29, %30, %31, %32, %33, %34, %35, %36, %37, %38, %39, %40, %41, %42, %43, %44, %45, %46, %47, %48, %49, %50, %51, %52, %53, %54, %55, %56, %57, %58, %59, %60, %61, %62, %63, %64, %65, %66, %67, %68, %69, %70, %71, %72, %73, %74, %75, %76, %77, %78, %79, %80, %81, %82, %83, %84, %85, %86, %87, %88, %89, %90, %91, %92, %93, %94, %95, %96, %97, %98, %99, %100, %101, %102, %103, %104, %105, %106, %107, %108, %109, %110, %111, %112, %113, %114, %115, %116, %117, %118, %119, %120, %121, %122, %123, %124, %125, %126, %127}, %128, %129, p, 1, 1, 0, 1;\n}\n"
        : "+f"(d[0]), "+f"(d[1]), "+f"(d[2]), "+f"(d[3]), "+f"(d[4]), "+f"(d[5]), "+f"(d[6]), "+f"(d[7]), "+f"(d[8]), "+f"(d[9]), "+f"(d[10]), "+f"(d[11]), "+f"(d[12]), "+f"(d[13]), "+f"(d[14]), "+f"(d[15]), "+f"(d[16]), "+f"(d[17]), "+f"(d[18]), "+f"(d[19]), "+f"(d[20]), "+f"(d[21]), "+f"(d[22]), "+f"(d[23]), "+f"(d[24]), "+f"(d[25]), "+f"(d[26]), "+f"(d[27]), "+f"(d[28]), "+f"(d[29]), "+f"(d[30]), "+f"(d[31]), "+f"(d[32]), "+f"(d[33]), "+f"(d[34]), "+f"(d[35]), "+f"(d[36]), "+f"(d[37]), "+f"(d[38]), "+f"(d[39]), "+f"(d[40]), "+f"(d[41]), "+f"(d[42]), "+f"(d[43]), "+f"(d[44]), "+f"(d[45]), "+f"(d[46]), "+f"(d[47]), "+f"(d[48]), "+f"(d[49]), "+f"(d[50]), "+f"(d[51]), "+f"(d[52]), "+f"(d[53]), "+f"(d[54]), "+f"(d[55]), "+f"(d[56]), "+f"(d[57]), "+f"(d[58]), "+f"(d[59]), "+f"(d[60]), "+f"(d[61]), "+f"(d[62]), "+f"(d[63]), "+f"(d[64]), "+f"(d[65]), "+f"(d[66]), "+f"(d[67]), "+f"(d[68]), "+f"(d[69]), "+f"(d[70]), "+f"(d[71]), "+f"(d[72]), "+f"(d[73]), "+f"(d[74]), "+f"(d[75]), "+f"(d[76]), "+f"(d[77]), "+f"(d[78]), "+f"(d[79]), "+f"(d[80]), "+f"(d[81]), "+f"(d[82]), "+f"(d[83]), "+f"(d[84]), "+f"(d[85]), "+f"(d[86]), "+f"(d[87]), "+f"(d[88]), "+f"(d[89]), "+f"(d[90]), "+f"(d[91]), "+f"(d[92]), "+f"(d[93]), "+f"(d[94]), "+f"(d[95]), "+f"(d[96]), "+f"(d[97]), "+f"(d[98]), "+f"(d[99]), "+f"(d[100]), "+f"(d[101]), "+f"(d[102]), "+f"(d[103]), "+f"(d[104]), "+f"(d[105]), "+f"(d[106]), "+f"(d[107]), "+f"(d[108]), "+f"(d[109]), "+f"(d[110]), "+f"(d[111]), "+f"(d[112]), "+f"(d[113]), "+f"(d[114]), "+f"(d[115]), "+f"(d[116]), "+f"(d[117]), "+f"(d[118]), "+f"(d[119]), "+f"(d[120]), "+f"(d[121]), "+f"(d[122]), "+f"(d[123]), "+f"(d[124]), "+f"(d[125]), "+f"(d[126]), "+f"(d[127])
        : "l"(descA), "l"(descB), "r"(scaleD));
}

__device__ __forceinline__ void wgmma_m64n192k16_ss(float (&d)[96], uint64_t descA, uint64_t descB, int scaleD) {
    asm volatile("{\n.reg .pred p;\nsetp.ne.b32 p, %98, 0;\n"
        "wgmma.mma_async.sync.aligned.m64n192k16.f32.bf16.bf16 {%0, %1, %2, %3, %4, %5, %6, %7, %8, %9, %10, %11, %12, %13, %14, %15, %16, %17, %18, %19, %20, %21, %22, %23, %24, %25, %26, %27, %28, %29, %30, %31, %32, %33, %34, %35, %36, %37, %38, %39, %40, %41, %42, %43, %44, %45, %46, %47, %48, %49, %50, %51, %52, %53, %54, %55, %56, %57, %58, %59, %60, %61, %62, %63, %64, %65, %66, %67, %68, %69, %70, %71, %72, %73, %74, %75, %76, %77, %78, %79, %80, %81, %82, %83, %84, %85, %86, %87, %88, %89, %90, %91, %92, %93, %94, %95}, %96, %97, p, 1, 1, 0, 1;\n}\n"
        : "+f"(d[0]), "+f"(d[1]), "+f"(d[2]), "+f"(d[3]), "+f"(d[4]), "+f"(d[5]), "+f"(d[6]), "+f"(d[7]), "+f"(d[8]), "+f"(d[9]), "+f"(d[10]), "+f"(d[11]), "+f"(d[12]), "+f"(d[13]), "+f"(d[14]), "+f"(d[15]), "+f"(d[16]), "+f"(d[17]), "+f"(d[18]), "+f"(d[19]), "+f"(d[20]), "+f"(d[21]), "+f"(d[22]), "+f"(d[23]), "+f"(d[24]), "+f"(d[25]), "+f"(d[26]), "+f"(d[27]), "+f"(d[28]), "+f"(d[29]), "+f"(d[30]), "+f"(d[31]), "+f"(d[32]), "+f"(d[33]), "+f"(d[34]), "+f"(d[35]), "+f"(d[36]), "+f"(d[37]), "+f"(d[38]), "+f"(d[39]), "+f"(d[40]), "+f"(d[41]), "+f"(d[42]), "+f"(d[43]), "+f"(d[44]), "+f"(d[45]), "+f"(d[46]), "+f"(d[47]), "+f"(d[48]), "+f"(d[49]), "+f"(d[50]), "+f"(d[51]), "+f"(d[52]), "+f"(d[53]), "+f"(d[54]), "+f"(d[55]), "+f"(d[56]), "+f"(d[57]), "+f"(d[58]), "+f"(d[59]), "+f"(d[60]), "+f"(d[61]), "+f"(d[62]), "+f"(d[63]), "+f"(d[64]), "+f"(d[65]), "+f"(d[66]), "+f"(d[67]), "+f"(d[68]), "+f"(d[69]), "+f"(d[70]), "+f"(d[71]), "+f"(d[72]), "+f"(d[73]), "+f"(d[74]), "+f"(d[75]), "+f"(d[76]), "+f"(d[77]), "+f"(d[78]), "+f"(d[79]), "+f"(d[80]), "+f"(d[81]), "+f"(d[82]), "+f"(d[83]), "+f"(d[84]), "+f"(d[85]), "+f"(d[86]), "+f"(d[87]), "+f"(d[88]), "+f"(d[89]), "+f"(d[90]), "+f"(d[91]), "+f"(d[92]), "+f"(d[93]), "+f"(d[94]), "+f"(d[95])
        : "l"(descA), "l"(descB), "r"(scaleD));
}

__device__ __forceinline__ void wgmma_m64n128k16_ss(float (&d)[64], uint64_t descA, uint64_t descB, int scaleD) {
    asm volatile("{\n.reg .pred p;\nsetp.ne.b32 p, %66, 0;\n"
        "wgmma.mma_async.sync.aligned.m64n128k16.f32.bf16.bf16 {%0, %1, %2, %3, %4, %5, %6, %7, %8, %9, %10, %11, %12, %13, %14, %15, %16, %17, %18, %19, %20, %21, %22, %23, %24, %25, %26, %27, %28, %29, %30, %31, %32, %33, %34, %35, %36, %37, %38, %39, %40, %41, %42, %43, %44, %45, %46, %47, %48, %49, %50, %51, %52, %53, %54, %55, %56, %57, %58, %59, %60, %61, %62, %63}, %64, %65, p, 1, 1, 0, 1;\n}\n"
        : "+f"(d[0]), "+f"(d[1]), "+f"(d[2]), "+f"(d[3]), "+f"(d[4]), "+f"(d[5]), "+f"(d[6]), "+f"(d[7]), "+f"(d[8]), "+f"(d[9]), "+f"(d[10]), "+f"(d[11]), "+f"(d[12]), "+f"(d[13]), "+f"(d[14]), "+f"(d[15]), "+f"(d[16]), "+f"(d[17]), "+f"(d[18]), "+f"(d[19]), "+f"(d[20]), "+f"(d[21]), "+f"(d[22]), "+f"(d[23]), "+f"(d[24]), "+f"(d[25]), "+f"(d[26]), "+f"(d[27]), "+f"(d[28]), "+f"(d[29]), "+f"(d[30]), "+f"(d[31]), "+f"(d[32]), "+f"(d[33]), "+f"(d[34]), "+f"(d[35]), "+f"(d[36]), "+f"(d[37]), "+f"(d[38]), "+f"(d[39]), "+f"(d[40]), "+f"(d[41]), "+f"(d[42]), "+f"(d[43]), "+f"(d[44]), "+f"(d[45]), "+f"(d[46]), "+f"(d[47]), "+f"(d[48]), "+f"(d[49]), "+f"(d[50]), "+f"(d[51]), "+f"(d[52]), "+f"(d[53]), "+f"(d[54]), "+f"(d[55]), "+f"(d[56]), "+f"(d[57]), "+f"(d[58]), "+f"(d[59]), "+f"(d[60]), "+f"(d[61]), "+f"(d[62]), "+f"(d[63])
        : "l"(descA), "l"(descB), "r"(scaleD));
}

__device__ __forceinline__ void quad_transpose(uint32_t& r0, uint32_t& r1, uint32_t& r2, uint32_t& r3, int t) {
    const bool o1 = t & 1, o2 = t & 2;
    uint32_t x, y;
    x = o1 ? r0 : r1; y = __shfl_xor_sync(0xffffffffu, x, 1); if (o1) r0 = y; else r1 = y;
    x = o1 ? r2 : r3; y = __shfl_xor_sync(0xffffffffu, x, 1); if (o1) r2 = y; else r3 = y;
    x = o2 ? r0 : r2; y = __shfl_xor_sync(0xffffffffu, x, 2); if (o2) r0 = y; else r2 = y;
    x = o2 ? r1 : r3; y = __shfl_xor_sync(0xffffffffu, x, 2); if (o2) r1 = y; else r3 = y;
}

constexpr int K1_THREADS = 256;
constexpr int UT_PAD = 128;
constexpr int UT_LEN = UT_PAD + S_;
constexpr int KR_LEN = 2080;
constexpr int YP_LEN = S_ + (S_ / 32) * 8;

struct __align__(128) K1Smem {
    bf16 uT[4][UT_LEN];
    bf16 kr[4][2][KR_LEN];
    float yP[4][YP_LEN];
    uint64_t bar;
    uint8_t pad[32768];
};

__device__ __forceinline__ void mma16816(float (&c)[4], uint32_t a0, uint32_t a1, uint32_t a2, uint32_t a3, uint32_t b0, uint32_t b1) {
    asm("mma.sync.aligned.m16n8k16.row.col.f32.bf16.bf16.f32 {%0,%1,%2,%3}, {%4,%5,%6,%7}, {%8,%9}, {%0,%1,%2,%3};"
        : "+f"(c[0]), "+f"(c[1]), "+f"(c[2]), "+f"(c[3])
        : "r"(a0), "r"(a1), "r"(a2), "r"(a3), "r"(b0), "r"(b1));
}
__device__ __forceinline__ void ldsm_x4(uint32_t& r0, uint32_t& r1, uint32_t& r2, uint32_t& r3, uint32_t addr) {
    asm volatile("ldmatrix.sync.aligned.m8n8.x4.shared.b16 {%0,%1,%2,%3}, [%4];" : "=r"(r0), "=r"(r1), "=r"(r2), "=r"(r3) : "r"(addr) : "memory");
}

__device__ __forceinline__ void conv_mma(const bf16* uTc, const bf16* krlane, float (&acc)[16][4], int lane, int half) {
    const int lrow = lane & 7, lk = (lane >> 3) & 1, lt = lane >> 4;
    const uint32_t ubase = smem_u32(uTc) + (UT_PAD + 16 * (8 * lt + lrow) + 8 * lk) * 2;
#pragma unroll 1
    for (int pp = 0; pp < 4; pp++) {
        const int p = half * 4 + pp;
        uint32_t U[16][2];
#pragma unroll
        for (int j = 0; j < 16; j += 2) ldsm_x4(U[j][0], U[j][1], U[j + 1][0], U[j + 1][1], ubase + (j * 128 - p * 16) * 2);
        const uint32_t* kp = reinterpret_cast<const uint32_t*>(krlane - 16 * p);
        const volatile uint32_t* kpv = kp;
        uint32_t a0 = kp[0], a1 = kp[-4], a2 = kp[4], a3 = kpv[0];
#pragma unroll
        for (int q = 0; q < 16; q++) {
            uint32_t b0 = 0, b1 = 0, b2 = 0, b3 = 0;
            if (q < 15) { b0 = kp[-64 * (q + 1)]; b1 = kp[-64 * (q + 1) - 4]; b2 = kp[-64 * (q + 1) + 4]; b3 = kpv[-64 * (q + 1)]; }
#pragma unroll
            for (int n = 15; n >= q; n--) mma16816(acc[n], a0, a1, a2, a3, U[n - q][0], U[n - q][1]);
            a0 = b0; a1 = b1; a2 = b2; a3 = b3;
        }
    }
}

__global__ void __cluster_dims__(2, 1, 1) __launch_bounds__(K1_THREADS, 1)
conv_kernel(const bf16* __restrict__ k, const bf16* __restrict__ v,
            const bf16* __restrict__ shift_k, const bf16* __restrict__ ssm_k, const bf16* __restrict__ ssm_D) {
    extern __shared__ __align__(1024) uint8_t smem_raw[];
    pdl_launch();
    K1Smem& sm = *reinterpret_cast<K1Smem*>(smem_raw);
    const int tid = threadIdx.x, lane = tid & 31, warp = tid >> 5;
    const int bid = blockIdx.x;
    const int rank = bid & 1;
    const int c0 = 8 * (bid >> 1);
    const int cown = c0 + 4 * rank;
#define TMT 0
    TM(0, 0);
    const uint32_t bar = smem_u32(&sm.bar);
    if (tid == 0) {
        mbar_init(bar, 1);
        asm volatile("fence.mbarrier_init.release.cluster;" ::: "memory");
        mbar_expect_tx(bar, 1024 * 4 * 2);
    }
    cluster_arrive_relaxed();

    const int s0 = 1024 * rank + 4 * tid;
    uint4 kk[7], vv[4], sw[4];
#pragma unroll
    for (int i = 0; i < 4; i++) kk[3 + i] = ldg128(k + (size_t)(s0 + i) * D_ + c0);
#pragma unroll
    for (int i = 0; i < 4; i++) vv[i] = ldg128(v + (size_t)(s0 + i) * D_ + c0);
    if (lane == 0) {
#pragma unroll
        for (int i = 0; i < 3; i++) {
            const int s = s0 - 3 + i;
            kk[i] = make_uint4(0, 0, 0, 0);
            if (s >= 0) kk[i] = ldg128(k + (size_t)s * D_ + c0);
        }
    }
#pragma unroll
    for (int i = 0; i < 4; i++) sw[i] = ldg128(shift_k + (size_t)c0 * 4 + 8 * i);
    uint4 kq[4]; uint32_t nx[4];
#pragma unroll
    for (int c = 0; c < 4; c++) {
        const bf16* kr = ssm_k + (size_t)(cown + c) * S_;
        kq[c] = ldg128(kr + 8 * tid);
        nx[c] = 0u;
        if (tid < 255) nx[c] = ldg16(kr + 8 * tid + 8);
    }
    const uint32_t dval = ldg16(ssm_D + cown + (warp >> 1));
    if (tid < 64) *reinterpret_cast<uint4*>(&sm.uT[tid >> 4][(tid & 15) * 8]) = make_uint4(0, 0, 0, 0);
#pragma unroll
    for (int i = 0; i < 3; i++) {
        uint4 t;
        t.x = __shfl_up_sync(0xffffffffu, kk[4 + i].x, 1); t.y = __shfl_up_sync(0xffffffffu, kk[4 + i].y, 1);
        t.z = __shfl_up_sync(0xffffffffu, kk[4 + i].z, 1); t.w = __shfl_up_sync(0xffffffffu, kk[4 + i].w, 1);
        if (lane != 0) kk[i] = t;
    }
    uint32_t kvw[4][4];
    const uint32_t* kkw = reinterpret_cast<const uint32_t*>(kk);
    const uint32_t* vvw = reinterpret_cast<const uint32_t*>(vv);
#pragma unroll
    for (int i2 = 0; i2 < 4; i2++) {
        const uint32_t t0 = __byte_perm(sw[i2].x, sw[i2].z, 0x5410), t1 = __byte_perm(sw[i2].x, sw[i2].z, 0x7632);
        const uint32_t t2 = __byte_perm(sw[i2].y, sw[i2].w, 0x5410), t3 = __byte_perm(sw[i2].y, sw[i2].w, 0x7632);
#pragma unroll
        for (int r = 0; r < 4; r++) {
            uint32_t a = hmul2(kkw[(r + 0) * 4 + i2], t3);
            a = hadd2(a, hmul2(kkw[(r + 1) * 4 + i2], t2));
            a = hadd2(a, hmul2(kkw[(r + 2) * 4 + i2], t1));
            a = hadd2(a, hmul2(kkw[(r + 3) * 4 + i2], t0));
            kvw[r][i2] = hmul2(a, vvw[r * 4 + i2]);
        }
    }
    TM(0, 1);
    cluster_wait();
    {
        const uint32_t rbar = mapa(bar, (uint32_t)(rank ^ 1));
#pragma unroll
        for (int i2 = 0; i2 < 4; i2++) {
#pragma unroll
            for (int e = 0; e < 2; e++) {
                const uint32_t sel = e ? 0x7632 : 0x5410;
                const uint32_t w0 = __byte_perm(kvw[0][i2], kvw[1][i2], sel), w1 = __byte_perm(kvw[2][i2], kvw[3][i2], sel);
                const int cc = 2 * i2 + e;
                if ((cc >> 2) == rank) {
                    *reinterpret_cast<uint2*>(&sm.uT[cc & 3][UT_PAD + s0]) = make_uint2(w0, w1);
                } else {
                    st_async_v2(mapa(smem_u32(&sm.uT[cc & 3][UT_PAD + s0]), (uint32_t)(rank ^ 1)), w0, w1, rbar);
                }
            }
        }
    }
#pragma unroll
    for (int c = 0; c < 4; c++) {
        uint4 a, b;
        a.x = __byte_perm(kq[c].w, 0, 0x1032); a.y = __byte_perm(kq[c].z, 0, 0x1032);
        a.z = __byte_perm(kq[c].y, 0, 0x1032); a.w = __byte_perm(kq[c].x, 0, 0x1032);
        b.x = __byte_perm(nx[c], kq[c].w, 0x7610); b.y = __byte_perm(kq[c].w, kq[c].z, 0x7610);
        b.z = __byte_perm(kq[c].z, kq[c].y, 0x7610); b.w = __byte_perm(kq[c].y, kq[c].x, 0x7610);
        *reinterpret_cast<uint4*>(&sm.kr[c][0][2040 - 8 * tid]) = a;
        *reinterpret_cast<uint4*>(&sm.kr[c][1][2040 - 8 * tid]) = b;
        if (tid == 0) {
            *reinterpret_cast<uint4*>(&sm.kr[c][1][2048]) = make_uint4(kq[c].x & 0xffffu, 0, 0, 0);
        } else if (tid < 8) {
            if (tid < 4) *reinterpret_cast<uint4*>(&sm.kr[c][1][2048 + 8 * tid]) = make_uint4(0, 0, 0, 0);
            else *reinterpret_cast<uint4*>(&sm.kr[c][0][2048 + 8 * (tid - 4)]) = make_uint4(0, 0, 0, 0);
        }
    }
    TM(0, 3);
    __syncthreads();
    mbar_wait_cluster(bar, 0);
    TM(0, 4);

    const int ch = warp >> 1, half = warp & 1;
    const int g = lane >> 2, t = lane & 3;
    float acc[16][4];
#pragma unroll
    for (int i = 0; i < 16; i++) { acc[i][0] = acc[i][1] = acc[i][2] = acc[i][3] = 0.f; }
    const bf16* krlane = (g & 1) ? &sm.kr[ch][0][2047 - g + 2 * t] : &sm.kr[ch][1][2048 - g + 2 * t];
    conv_mma(sm.uT[ch], krlane, acc, lane, half);
    TM(0, 5);
    float* yp = &sm.yP[ch][40 * t + g];
    if (half) {
#pragma unroll
        for (int n = 0; n < 16; n++) {
            yp[160 * n] = acc[n][0];
            yp[160 * n + 16] = acc[n][1];
            yp[160 * n + 8] = acc[n][2];
            yp[160 * n + 24] = acc[n][3];
        }
    }
    named_bar(1 + ch, 64);
    if (!half) {
#pragma unroll
        for (int n = 0; n < 16; n++) {
            yp[160 * n] += acc[n][0];
            yp[160 * n + 16] += acc[n][1];
            yp[160 * n + 8] += acc[n][2];
            yp[160 * n + 24] += acc[n][3];
        }
    }
    named_bar(1 + ch, 64);
    TM(0, 6);
    {
        const int tt = tid & 63;
        bf16* dst = g_yT + (size_t)(cown + ch) * S_;
        const uint32_t d2 = dval * 0x10001u;
#pragma unroll
        for (int j = 0; j < 4; j++) {
            const int s = (j * 64 + tt) * 8;
            const float* src = &sm.yP[ch][s + (s >> 5) * 8];
            const float4 a = *reinterpret_cast<const float4*>(src), b = *reinterpret_cast<const float4*>(src + 4);
            const uint4 kv4 = *reinterpret_cast<const uint4*>(&sm.uT[ch][UT_PAD + s]);
            *reinterpret_cast<uint4*>(dst + s) = make_uint4(hadd2(pack_bf16(a.x, a.y), hmul2(kv4.x, d2)), hadd2(pack_bf16(a.z, a.w), hmul2(kv4.y, d2)),
                                                            hadd2(pack_bf16(b.x, b.y), hmul2(kv4.z, d2)), hadd2(pack_bf16(b.z, b.w), hmul2(kv4.w, d2)));
        }
    }
    TM(0, 7);
#undef TMT
}

__device__ __forceinline__ float warp_sum(float s) {
#pragma unroll
    for (int o = 16; o > 0; o >>= 1) s += __shfl_xor_sync(0xffffffffu, s, o);
    return s;
}
__device__ __forceinline__ uint32_t hsub2(uint32_t a, uint32_t b) {
    __nv_bfloat162 r = __hsub2_rn(*reinterpret_cast<__nv_bfloat162*>(&a), *reinterpret_cast<__nv_bfloat162*>(&b));
    return *reinterpret_cast<uint32_t*>(&r);
}
__device__ __forceinline__ void ln_row(const uint32_t (&x)[8], uint32_t (&o)[8]) {
    float s0 = 0.f, s1 = 0.f;
#pragma unroll
    for (int i = 0; i < 8; i++) { s0 += bf_lo(x[i]); s1 += bf_hi(x[i]); }
    const float mean = warp_sum(s0 + s1) * (1.0f / D_);
    float ss0 = 0.f, ss1 = 0.f;
#pragma unroll
    for (int i = 0; i < 8; i++) { const float d0 = bf_lo(x[i]) - mean, d1 = bf_hi(x[i]) - mean; ss0 += d0 * d0; ss1 += d1 * d1; }
    const float var = bf16r(warp_sum(ss0 + ss1) * (1.0f / D_));
    const float rinv = 1.0f / bf16r(sqrtf(bf16r(var + 1e-5f)));
    const uint32_t m2 = pack_bf16(mean, mean);
#pragma unroll
    for (int i = 0; i < 8; i++) {
        const uint32_t d = hsub2(x[i], m2);
        o[i] = pack_bf16(bf_lo(d) * rinv, bf_hi(d) * rinv);
    }
}

constexpr int G1_THREADS = 384;
constexpr int G1_STAGES = 3;
constexpr int G1_A_BYTES = 8 * 16384;
constexpr int G1_B_STAGE = 32768;
constexpr int G1_OFF_B = G1_A_BYTES;
constexpr int G1_OFF_BAR = G1_OFF_B + G1_STAGES * G1_B_STAGE;
constexpr int G1_SMEM = G1_OFF_BAR + 256;

__device__ __forceinline__ float sigmoid_fast(float x) {
    float t; asm("tanh.approx.f32 %0, %1;" : "=f"(t) : "f"(0.5f * x));
    return fmaf(t, 0.5f, 0.5f);
}

template <int NT>
__device__ __forceinline__ void g1_epilogue(const float (&acc)[NT * 8], bf16* out0, int t) {
#pragma unroll
    for (int j0 = 0; j0 < NT; j0 += 4) {
        uint32_t P0[4], P1[4];
#pragma unroll
        for (int jj = 0; jj < 4; jj++) {
            const int j = j0 + jj;
            float r[4];
#pragma unroll
            for (int e = 0; e < 4; e++) r[e] = sigmoid_fast(acc[4 * j + e]) * acc[4 * (NT + j) + e];
            P0[jj] = pack_bf16(r[0], r[1]);
            P1[jj] = pack_bf16(r[2], r[3]);
        }
        quad_transpose(P0[0], P0[1], P0[2], P0[3], t);
        quad_transpose(P1[0], P1[1], P1[2], P1[3], t);
        *reinterpret_cast<uint4*>(out0 + 8 * (j0 + t)) = make_uint4(P0[0], P0[1], P0[2], P0[3]);
        *reinterpret_cast<uint4*>(out0 + 8 * F_ + 8 * (j0 + t)) = make_uint4(P1[0], P1[1], P1[2], P1[3]);
    }
}

__global__ void __cluster_dims__(2, 1, 1) __launch_bounds__(G1_THREADS, 1)
gemm1_kernel(const __grid_constant__ CUtensorMap mapA, const __grid_constant__ CUtensorMap mapG4, const __grid_constant__ CUtensorMap mapU4,
             const __grid_constant__ CUtensorMap mapG3, const __grid_constant__ CUtensorMap mapU3, const bf16* __restrict__ q) {
    extern __shared__ __align__(1024) uint8_t smem_raw[];
    const uint32_t sb = smem_u32(smem_raw);
    const int tid = threadIdx.x, lane = tid & 31, warp = tid >> 5, wgi = tid >> 7;
    const int rank = blockIdx.x & 1;
    const int cb = blockIdx.x & 7, rb = blockIdx.x >> 3;
#define TMT 128
    TM(2, 0);
    pdl_launch();
    if (tid == 32) { prefetch_map(&mapA); prefetch_map(&mapG3); prefetch_map(&mapU3); }
    const uint32_t barA = sb + G1_OFF_BAR;
    const uint32_t barF = barA + 64;
    const uint32_t barE = barF + 8 * G1_STAGES;
    if (tid == 0) {
        for (int i = 0; i < 8; i++) mbar_init(barA + 8 * i, 1);
        for (int i = 0; i < G1_STAGES; i++) { mbar_init(barF + 8 * i, 1); mbar_init(barE + 8 * i, 2); }
        for (int i = 0; i < 8; i++) mbar_expect_tx(barA + 8 * i, 16384);
        asm volatile("fence.mbarrier_init.release.cluster;" ::: "memory");
        for (int it = 0; it < G1_STAGES; it++) {
            const uint32_t dst = sb + G1_OFF_B + it * G1_B_STAGE;
            mbar_expect_tx(barF + 8 * it, 32768);
            tma_load_3d(dst, &mapG4, barF + 8 * it, 0, it * 64, cb * 7);
            tma_load_3d(dst + 16384, &mapU4, barF + 8 * it, 0, it * 64, cb * 7);
        }
    }
    __syncthreads();
    cluster_arrive_relaxed();
    cluster_wait();

    if (wgi == 0) {
        reg_dealloc<40>();
        if (lane == 0 && warp == 0) {
            int st = 0, ph = 0;
            for (int it = G1_STAGES; it < 16; it++) {
                const int kc = it & 7;
                mbar_wait(barE + 8 * st, ph);
                const uint32_t dst = sb + G1_OFF_B + st * G1_B_STAGE;
                if (it < 8) {
                    mbar_expect_tx(barF + 8 * st, 32768);
                    tma_load_3d(dst, &mapG4, barF + 8 * st, 0, kc * 64, cb * 7);
                    tma_load_3d(dst + 16384, &mapU4, barF + 8 * st, 0, kc * 64, cb * 7);
                } else {
                    mbar_expect_tx(barF + 8 * st, 24576);
                    tma_load_3d(dst, &mapG3, barF + 8 * st, 0, kc * 64, cb * 7 + 4);
                    tma_load_3d(dst + 12288, &mapU3, barF + 8 * st, 0, kc * 64, cb * 7 + 4);
                }
                if (++st == G1_STAGES) { st = 0; ph ^= 1; }
            }
        } else if (lane == 0 && warp == 1) {
            unsigned int c; int spins = 0;
            do { asm volatile("ld.acquire.gpu.global.u32 %0, [%1];" : "=r"(c) : "l"(&g_cnt[rb]) : "memory"); } while (c < 8u && ++spins < (1 << 22));
            asm volatile("fence.proxy.async;" ::: "memory");
            TR(0, 0);
            for (int i = 0; i < 4; i++) {
                const int c = 2 * i + rank;
                tma_load_2d_mc(sb + c * 16384, &mapA, barA + 8 * c, c * 64, rb * 128, (uint16_t)3);
            }
        }
        __syncwarp();
    } else {
        reg_alloc<232>();
        const int cw = wgi - 1;
        const int g = lane >> 2, t = lane & 3, wl = warp & 3, tl = tid & 127;
        {
            uint32_t (*ys)[D_ / 2 + 4] = reinterpret_cast<uint32_t (*)[D_ / 2 + 4]>(smem_raw);
            const int s0 = rb * 128 + cb * 16;
            const int cwp = warp - 4, p = tid - 128;
            uint32_t x[2][8], qn[2][8];
#pragma unroll
            for (int r = 0; r < 2; r++) {
                const uint4 qa = ldg128(q + (size_t)(s0 + 2 * cwp + r) * D_ + 8 * lane);
                const uint4 qb = ldg128(q + (size_t)(s0 + 2 * cwp + r) * D_ + 8 * (lane + 32));
                x[r][0] = qa.x; x[r][1] = qa.y; x[r][2] = qa.z; x[r][3] = qa.w; x[r][4] = qb.x; x[r][5] = qb.y; x[r][6] = qb.z; x[r][7] = qb.w;
            }
            ln_row(x[0], qn[0]);
            ln_row(x[1], qn[1]);
            pdl_wait();
            TM(1, 0);
            {
                const bf16* y0 = g_yT + (size_t)(2 * p) * S_ + s0;
                const uint4 a0 = ldcg128(y0), a1 = ldcg128(y0 + 8), b0 = ldcg128(y0 + S_), b1 = ldcg128(y0 + S_ + 8);
                const uint32_t aw[8] = {a0.x, a0.y, a0.z, a0.w, a1.x, a1.y, a1.z, a1.w};
                const uint32_t bw[8] = {b0.x, b0.y, b0.z, b0.w, b1.x, b1.y, b1.z, b1.w};
#pragma unroll
                for (int j = 0; j < 8; j++) {
                    ys[2 * j][p] = __byte_perm(aw[j], bw[j], 0x5410);
                    ys[2 * j + 1][p] = __byte_perm(aw[j], bw[j], 0x7632);
                }
            }
            named_bar(1, 256);
            TM(1, 1);
#pragma unroll
            for (int r = 0; r < 2; r++) {
                uint32_t h[8], hn[8];
#pragma unroll
                for (int i = 0; i < 2; i++) {
                    const uint4 yw4 = *reinterpret_cast<const uint4*>(&ys[2 * cwp + r][4 * (lane + 32 * i)]);
                    const uint32_t yw[4] = {yw4.x, yw4.y, yw4.z, yw4.w};
#pragma unroll
                    for (int j = 0; j < 4; j++) h[4 * i + j] = hadd2(x[r][4 * i + j], hmul2(qn[r][4 * i + j], yw[j]));
                }
                ln_row(h, hn);
#pragma unroll
                for (int i = 0; i < 2; i++) {
                    const size_t off = (size_t)(s0 + 2 * cwp + r) * D_ + 8 * (lane + 32 * i);
                    *reinterpret_cast<uint4*>(g_hn + off) = make_uint4(hn[4 * i], hn[4 * i + 1], hn[4 * i + 2], hn[4 * i + 3]);
                    *reinterpret_cast<uint4*>(g_h + off) = make_uint4(h[4 * i], h[4 * i + 1], h[4 * i + 2], h[4 * i + 3]);
                }
            }
            asm volatile("fence.proxy.async;" ::: "memory");
            __threadfence();
            named_bar(1, 256);
            if (p == 0) atomicAdd(&g_cnt[rb], 1u);
            TM(1, 2);
        }
        bf16* outp = g_hh + (size_t)(rb * 128 + cw * 64 + wl * 16 + g) * F_ + cb * 224;
        int st = 0, ph = 0;
        {
            float acc[128];
#pragma unroll 1
            for (int kc = 0; kc < 8; kc++) {
                mbar_wait(barA + 8 * kc, 0);
                mbar_wait(barF + 8 * st, ph);
                if (tl == 0 && cw == 0) TR(1, kc);
                wgmma_fence();
                const uint32_t aaddr = sb + kc * 16384 + cw * 8192;
                const uint32_t baddr = sb + G1_OFF_B + st * G1_B_STAGE;
#pragma unroll
                for (int kk = 0; kk < 4; kk++)
                    wgmma_m64n256k16_ss(acc, make_desc(aaddr + kk * 32, 16, 1024, 1), make_desc(baddr + kk * 1024, 4096, 512, 2), (kc | kk) != 0);
                wgmma_commit();
                wgmma_wait<0>();
                if (tl == 0) mbar_arrive(barE + 8 * st);
                if (++st == G1_STAGES) { st = 0; ph ^= 1; }
            }
            TM(2, 1);
            g1_epilogue<16>(acc, outp, t);
            TM(2, 2);
        }
        {
            float acc[96];
#pragma unroll 1
            for (int kc = 0; kc < 8; kc++) {
                mbar_wait(barF + 8 * st, ph);
                if (tl == 0 && cw == 0) TR(1, 8 + kc);
                wgmma_fence();
                const uint32_t aaddr = sb + kc * 16384 + cw * 8192;
                const uint32_t baddr = sb + G1_OFF_B + st * G1_B_STAGE;
#pragma unroll
                for (int kk = 0; kk < 4; kk++)
                    wgmma_m64n192k16_ss(acc, make_desc(aaddr + kk * 32, 16, 1024, 1), make_desc(baddr + kk * 1024, 4096, 512, 2), (kc | kk) != 0);
                wgmma_commit();
                wgmma_wait<0>();
                if (tl == 0) mbar_arrive(barE + 8 * st);
                if (++st == G1_STAGES) { st = 0; ph ^= 1; }
            }
            TM(2, 3);
            g1_epilogue<12>(acc, outp + 128, t);
            TM(2, 4);
        }
    }
}

constexpr int G2_THREADS = 384;
constexpr int G2_STAGES = 6;
constexpr int G2_STAGE = 32768;
constexpr int G2_OFF_X = G2_STAGES * G2_STAGE;
constexpr int G2_OFF_BAR = G2_OFF_X + 32768;
constexpr int G2_SMEM = G2_OFF_BAR + 128;
constexpr int G2_KSTEPS = 14;

__global__ void __cluster_dims__(2, 1, 1) __launch_bounds__(G2_THREADS, 1)
gemm2_kernel(const __grid_constant__ CUtensorMap mapHH, const __grid_constant__ CUtensorMap mapWd, bf16* __restrict__ out) {
    extern __shared__ __align__(1024) uint8_t smem_raw[];
    const uint32_t sb = smem_u32(smem_raw);
    const int tid = threadIdx.x, lane = tid & 31, warp = tid >> 5, wgi = tid >> 7;
    const int ks = blockIdx.x & 1, nb = (blockIdx.x >> 1) & 3, rb = blockIdx.x >> 3;
    TM(3, 0);
    if (tid == 32) { prefetch_map(&mapHH); }
    const uint32_t barF = sb + G2_OFF_BAR;
    const uint32_t barE = barF + 8 * G2_STAGES;
    const uint32_t barX = barE + 8 * G2_STAGES;
    if (tid == 0) {
        for (int i = 0; i < G2_STAGES; i++) { mbar_init(barF + 8 * i, 1); mbar_init(barE + 8 * i, 2); }
        mbar_init(barX, 1);
        asm volatile("fence.mbarrier_init.release.cluster;" ::: "memory");
        mbar_expect_tx(barX, 32768);
        for (int it = 0; it < G2_STAGES; it++) {
            mbar_expect_tx(barF + 8 * it, 32768);
            tma_load_3d(sb + it * G2_STAGE + 16384, &mapWd, barF + 8 * it, 0, ks * 896 + it * 64, nb * 2);
        }
    }
    __syncthreads();
    cluster_arrive_relaxed();

    if (wgi == 0) {
        if (tid == 0) {
            pdl_wait();
            for (int it = 0; it < G2_STAGES; it++)
                tma_load_2d(sb + it * G2_STAGE, &mapHH, barF + 8 * it, ks * 896 + it * 64, rb * 128);
            int st = 0, ph = 0;
            for (int it = G2_STAGES; it < G2_KSTEPS; it++) {
                mbar_wait(barE + 8 * st, ph);
                const uint32_t dst = sb + st * G2_STAGE;
                const int k0 = ks * 896 + it * 64;
                mbar_expect_tx(barF + 8 * st, 32768);
                tma_load_2d(dst, &mapHH, barF + 8 * st, k0, rb * 128);
                tma_load_3d(dst + 16384, &mapWd, barF + 8 * st, 0, k0, nb * 2);
                if (++st == G2_STAGES) { st = 0; ph ^= 1; }
            }
        }
        __syncwarp();
        cluster_wait();
    } else {
        const int cw = wgi - 1;
        const int g = lane >> 2, t = lane & 3, wl = warp & 3;
        const int tl = tid & 127;
        int st = 0, ph = 0;
        float acc[64];
        pdl_wait();
        if (blockIdx.x == 0 && tid >= 128 && tid < 144) g_cnt[tid - 128] = 0u;
#pragma unroll 1
        for (int it = 0; it < G2_KSTEPS; it++) {
            mbar_wait(barF + 8 * st, ph);
            if (it == 0) TM(3, 1);
            wgmma_fence();
            const uint32_t aaddr = sb + st * G2_STAGE + cw * 8192;
            const uint32_t baddr = sb + st * G2_STAGE + 16384;
#pragma unroll
            for (int kk = 0; kk < 4; kk++)
                wgmma_m64n128k16_ss(acc, make_desc(aaddr + kk * 32, 16, 1024, 1), make_desc(baddr + kk * 2048, 8192, 1024, 1), (it | kk) != 0);
            wgmma_commit();
            wgmma_wait<0>();
            if (tl == 0) mbar_arrive(barE + 8 * st);
            if (++st == G2_STAGES) { st = 0; ph ^= 1; }
        }
        TM(3, 2);
        cluster_wait();
        if (cw != ks) {
            const uint32_t dst = mapa(sb + G2_OFF_X + tl * 16, (uint32_t)(ks ^ 1));
            const uint32_t rbar = mapa(barX, (uint32_t)(ks ^ 1));
#pragma unroll
            for (int i = 0; i < 16; i++) st_async_v4f(dst + i * 2048, acc[4 * i], acc[4 * i + 1], acc[4 * i + 2], acc[4 * i + 3], rbar);
        } else {
            const float4* xb = reinterpret_cast<const float4*>(smem_raw + G2_OFF_X) + tl;
            const int row0 = rb * 128 + cw * 64 + wl * 16 + g;
            const bf16* h0 = g_h + (size_t)row0 * D_ + nb * 128;
            bf16* o0 = out + (size_t)row0 * D_ + nb * 128;
            uint32_t ha[16], hb[16];
#pragma unroll
            for (int j = 0; j < 16; j++) {
                ha[j] = __ldcg(reinterpret_cast<const uint32_t*>(h0 + 8 * j + 2 * t));
                hb[j] = __ldcg(reinterpret_cast<const uint32_t*>(h0 + 8 * D_ + 8 * j + 2 * t));
            }
            mbar_wait_cluster(barX, 0);
            TM(3, 4);
#pragma unroll
            for (int j0 = 0; j0 < 16; j0 += 4) {
                uint32_t P0[4], P1[4];
#pragma unroll
                for (int jj = 0; jj < 4; jj++) {
                    const int j = j0 + jj;
                    const float4 x = xb[j * 128];
                    P0[jj] = pack_bf16(bf_lo(ha[j]) + bf16r(acc[4 * j] + x.x), bf_hi(ha[j]) + bf16r(acc[4 * j + 1] + x.y));
                    P1[jj] = pack_bf16(bf_lo(hb[j]) + bf16r(acc[4 * j + 2] + x.z), bf_hi(hb[j]) + bf16r(acc[4 * j + 3] + x.w));
                }
                quad_transpose(P0[0], P0[1], P0[2], P0[3], t);
                quad_transpose(P1[0], P1[1], P1[2], P1[3], t);
                *reinterpret_cast<uint4*>(o0 + 8 * (j0 + t)) = make_uint4(P0[0], P0[1], P0[2], P0[3]);
                *reinterpret_cast<uint4*>(o0 + 8 * D_ + 8 * (j0 + t)) = make_uint4(P1[0], P1[1], P1[2], P1[3]);
            }
        }
        TM(3, 5);
    }
#undef TMT
}

typedef CUresult (*EncodeFn)(CUtensorMap*, CUtensorMapDataType, cuuint32_t, void*, const cuuint64_t*, const cuuint64_t*,
                             const cuuint32_t*, const cuuint32_t*, CUtensorMapInterleave, CUtensorMapSwizzle,
                             CUtensorMapL2promotion, CUtensorMapFloatOOBfill);

static void enc2d(EncodeFn enc, CUtensorMap* m, const void* p, int rows, int cols, int brows, int bcols) {
    cuuint64_t dims[2] = {(cuuint64_t)cols, (cuuint64_t)rows};
    cuuint64_t strides[1] = {(cuuint64_t)cols * 2};
    cuuint32_t box[2] = {(cuuint32_t)bcols, (cuuint32_t)brows};
    cuuint32_t es[2] = {1, 1};
    enc(m, CU_TENSOR_MAP_DATA_TYPE_BFLOAT16, 2, const_cast<void*>(p), dims, strides, box, es, CU_TENSOR_MAP_INTERLEAVE_NONE,
        bcols == 32 ? CU_TENSOR_MAP_SWIZZLE_64B : CU_TENSOR_MAP_SWIZZLE_128B, CU_TENSOR_MAP_L2_PROMOTION_L2_128B, CU_TENSOR_MAP_FLOAT_OOB_FILL_NONE);
}
static void enc3d(EncodeFn enc, CUtensorMap* m, const void* p, int rows, int cols, int atom, int brows, int natoms) {
    cuuint64_t dims[3] = {(cuuint64_t)atom, (cuuint64_t)rows, (cuuint64_t)(cols / atom)};
    cuuint64_t strides[2] = {(cuuint64_t)cols * 2, (cuuint64_t)atom * 2};
    cuuint32_t box[3] = {(cuuint32_t)atom, (cuuint32_t)brows, (cuuint32_t)natoms};
    cuuint32_t es[3] = {1, 1, 1};
    enc(m, CU_TENSOR_MAP_DATA_TYPE_BFLOAT16, 3, const_cast<void*>(p), dims, strides, box, es, CU_TENSOR_MAP_INTERLEAVE_NONE,
        atom == 32 ? CU_TENSOR_MAP_SWIZZLE_64B : CU_TENSOR_MAP_SWIZZLE_128B, CU_TENSOR_MAP_L2_PROMOTION_L2_128B, CU_TENSOR_MAP_FLOAT_OOB_FILL_NONE);
}

extern "C" void kernel_launch(void* const* d_in, const int* in_sizes, int n_in, void* d_out, int out_size) {
    const bf16* q = (const bf16*)d_in[0];
    const bf16* k = (const bf16*)d_in[1];
    const bf16* v = (const bf16*)d_in[2];
    const bf16* shift_k = (const bf16*)d_in[3];
    const bf16* ssm_k = (const bf16*)d_in[4];
    const bf16* ssm_D = (const bf16*)d_in[5];
    const bf16* wg = (const bf16*)d_in[7];
    const bf16* wu = (const bf16*)d_in[8];
    const bf16* wd = (const bf16*)d_in[9];
    bf16* out = (bf16*)d_out;

    static EncodeFn enc = nullptr;
    static void *p_hn = nullptr, *p_hh = nullptr;
    if (!enc) {
        void* fn = nullptr; cudaDriverEntryPointQueryResult qr;
        cudaGetDriverEntryPoint("cuTensorMapEncodeTiled", &fn, cudaEnableDefault, &qr);
        enc = (EncodeFn)fn;
        cudaGetSymbolAddress(&p_hn, g_hn);
        cudaGetSymbolAddress(&p_hh, g_hh);
        cudaFuncSetAttribute(conv_kernel, cudaFuncAttributeMaxDynamicSharedMemorySize, (int)sizeof(K1Smem));
        cudaFuncSetAttribute(gemm1_kernel, cudaFuncAttributeMaxDynamicSharedMemorySize, G1_SMEM);
        cudaFuncSetAttribute(gemm2_kernel, cudaFuncAttributeMaxDynamicSharedMemorySize, G2_SMEM);
    }
    CUtensorMap mA, mG64, mU64, mG32, mU32, mHH, mWd;
    enc2d(enc, &mA, p_hn, S_, D_, 128, 64);
    enc3d(enc, &mG64, wg, D_, F_, 32, 64, 4);
    enc3d(enc, &mU64, wu, D_, F_, 32, 64, 4);
    enc3d(enc, &mG32, wg, D_, F_, 32, 64, 3);
    enc3d(enc, &mU32, wu, D_, F_, 32, 64, 3);
    enc2d(enc, &mHH, p_hh, S_, F_, 128, 64);
    enc3d(enc, &mWd, wd, F_, D_, 64, 64, 2);

    cudaStream_t st = cudaStreamPerThread;
    cudaLaunchAttribute at[1];
    at[0].id = cudaLaunchAttributeProgrammaticStreamSerialization;
    at[0].val.programmaticStreamSerializationAllowed = 1;
    cudaLaunchConfig_t cfg = {};
    cfg.stream = st; cfg.attrs = at; cfg.numAttrs = 1;
    conv_kernel<<<128, K1_THREADS, sizeof(K1Smem), st>>>(k, v, shift_k, ssm_k, ssm_D);
    cfg.gridDim = dim3(128); cfg.blockDim = dim3(G1_THREADS); cfg.dynamicSmemBytes = G1_SMEM;
    cudaLaunchKernelEx(&cfg, gemm1_kernel, mA, mG64, mU64, mG32, mU32, q);
    cfg.gridDim = dim3(128); cfg.blockDim = dim3(G2_THREADS); cfg.dynamicSmemBytes = G2_SMEM;
    cudaLaunchKernelEx(&cfg, gemm2_kernel, mHH, mWd, out);
}
```

```cpp
#include <cuda_runtime.h>
#include <cuda_bf16.h>
#include <cuda.h>
#include <stdint.h>

typedef __nv_bfloat16 bf16;
constexpr int S_ = 2048, D_ = 512, F_ = 1792;

__device__ bf16 g_yT[D_ * S_];
__device__ bf16 g_h[S_ * D_];
__device__ bf16 g_hn[S_ * D_];
__device__ bf16 g_hh[S_ * F_];
__device__ float2 g_st1[S_];
__device__ unsigned int g_cnt[16];

#define TM(k, i)
#define TR(k, i)
__device__ __forceinline__ uint32_t smem_u32(const void* p) { return (uint32_t)__cvta_generic_to_shared(p); }
__device__ __forceinline__ float bf16r(float x) { return __bfloat162float(__float2bfloat16_rn(x)); }
__device__ __forceinline__ float bf_lo(uint32_t w) { return __uint_as_float(w << 16); }
__device__ __forceinline__ float bf_hi(uint32_t w) { return __uint_as_float(w & 0xffff0000u); }
__device__ __forceinline__ uint32_t pack_bf16(float lo, float hi) {
    __nv_bfloat162 v = __floats2bfloat162_rn(lo, hi);
    return *reinterpret_cast<uint32_t*>(&v);
}
__device__ __forceinline__ uint32_t hmul2(uint32_t a, uint32_t b) {
    __nv_bfloat162 r = __hmul2_rn(*reinterpret_cast<__nv_bfloat162*>(&a), *reinterpret_cast<__nv_bfloat162*>(&b));
    return *reinterpret_cast<uint32_t*>(&r);
}
__device__ __forceinline__ uint32_t hadd2(uint32_t a, uint32_t b) {
    __nv_bfloat162 r = __hadd2_rn(*reinterpret_cast<__nv_bfloat162*>(&a), *reinterpret_cast<__nv_bfloat162*>(&b));
    return *reinterpret_cast<uint32_t*>(&r);
}
__device__ __forceinline__ uint4 ldg128(const void* p) {
    uint4 r; asm volatile("ld.global.nc.v4.u32 {%0,%1,%2,%3}, [%4];" : "=r"(r.x), "=r"(r.y), "=r"(r.z), "=r"(r.w) : "l"(p)); return r;
}
__device__ __forceinline__ uint4 ldcg128(const void* p) {
    uint4 r; asm volatile("ld.global.cg.v4.u32 {%0,%1,%2,%3}, [%4];" : "=r"(r.x), "=r"(r.y), "=r"(r.z), "=r"(r.w) : "l"(p)); return r;
}
__device__ __forceinline__ uint32_t ldg16(const void* p) {
    unsigned short r; asm volatile("ld.global.nc.u16 %0, [%1];" : "=h"(r) : "l"(p)); return (uint32_t)r;
}
__device__ __forceinline__ void mbar_init(uint32_t bar, int cnt) { asm volatile("mbarrier.init.shared::cta.b64 [%0], %1;" :: "r"(bar), "r"(cnt)); }
__device__ __forceinline__ void mbar_expect_tx(uint32_t bar, uint32_t bytes) { asm volatile("mbarrier.arrive.expect_tx.shared::cta.b64 _, [%0], %1;" :: "r"(bar), "r"(bytes) : "memory"); }
__device__ __forceinline__ void mbar_arrive(uint32_t bar) { asm volatile("mbarrier.arrive.shared::cta.b64 _, [%0];" :: "r"(bar) : "memory"); }
__device__ __forceinline__ void mbar_arrive_cluster(uint32_t bar, uint32_t cta) {
    asm volatile("{\n.reg .b32 ra;\nmapa.shared::cluster.u32 ra, %0, %1;\nmbarrier.arrive.shared::cluster.b64 _, [ra];\n}" :: "r"(bar), "r"(cta) : "memory");
}
__device__ __forceinline__ void mbar_wait(uint32_t bar, uint32_t parity) {
    asm volatile("{\n.reg .pred P1;\nLAB_WAIT:\nmbarrier.try_wait.parity.shared::cta.b64 P1, [%0], %1;\n@P1 bra DONE;\nbra LAB_WAIT;\nDONE:\n}" :: "r"(bar), "r"(parity) : "memory");
}
__device__ __forceinline__ void mbar_wait_cluster(uint32_t bar, uint32_t parity) {
    asm volatile("{\n.reg .pred P1;\nLAB_WAIT:\nmbarrier.try_wait.parity.acquire.cluster.shared::cta.b64 P1, [%0], %1;\n@P1 bra DONE;\nbra LAB_WAIT;\nDONE:\n}" :: "r"(bar), "r"(parity) : "memory");
}
__device__ __forceinline__ void tma_load_2d(uint32_t dst, const CUtensorMap* map, uint32_t bar, int c0, int c1) {
    asm volatile("cp.async.bulk.tensor.2d.shared::cluster.global.mbarrier::complete_tx::bytes [%0], [%1, {%3, %4}], [%2];"
        :: "r"(dst), "l"(map), "r"(bar), "r"(c0), "r"(c1) : "memory");
}
__device__ __forceinline__ void tma_load_2d_mc(uint32_t dst, const CUtensorMap* map, uint32_t bar, int c0, int c1, uint16_t mask) {
    asm volatile("cp.async.bulk.tensor.2d.shared::cluster.global.mbarrier::complete_tx::bytes.multicast::cluster [%0], [%1, {%3, %4}], [%2], %5;"
        :: "r"(dst), "l"(map), "r"(bar), "r"(c0), "r"(c1), "h"(mask) : "memory");
}
__device__ __forceinline__ void tma_load_3d(uint32_t dst, const CUtensorMap* map, uint32_t bar, int c0, int c1, int c2) {
    asm volatile("cp.async.bulk.tensor.3d.shared::cluster.global.mbarrier::complete_tx::bytes [%0], [%1, {%3, %4, %5}], [%2];"
        :: "r"(dst), "l"(map), "r"(bar), "r"(c0), "r"(c1), "r"(c2) : "memory");
}
__device__ __forceinline__ void cluster_arrive() { asm volatile("barrier.cluster.arrive.aligned;" ::: "memory"); }
__device__ __forceinline__ void cluster_arrive_relaxed() { asm volatile("barrier.cluster.arrive.relaxed.aligned;" ::: "memory"); }
__device__ __forceinline__ void cluster_wait() { asm volatile("barrier.cluster.wait.aligned;" ::: "memory"); }
__device__ __forceinline__ uint32_t mapa(uint32_t addr, uint32_t cta) {
    uint32_t r; asm volatile("mapa.shared::cluster.u32 %0, %1, %2;" : "=r"(r) : "r"(addr), "r"(cta)); return r;
}
__device__ __forceinline__ void st_async_v2(uint32_t addr, uint32_t a, uint32_t b, uint32_t rbar) {
    asm volatile("st.async.weak.shared::cluster.mbarrier::complete_tx::bytes.v2.b32 [%0], {%1, %2}, [%3];" :: "r"(addr), "r"(a), "r"(b), "r"(rbar) : "memory");
}
__device__ __forceinline__ void st_async_v4f(uint32_t addr, float a, float b, float c, float d, uint32_t rbar) {
    asm volatile("st.async.weak.shared::cluster.mbarrier::complete_tx::bytes.v4.f32 [%0], {%1, %2, %3, %4}, [%5];" :: "r"(addr), "f"(a), "f"(b), "f"(c), "f"(d), "r"(rbar) : "memory");
}
__device__ __forceinline__ void wgmma_fence() { asm volatile("wgmma.fence.sync.aligned;" ::: "memory"); }
__device__ __forceinline__ void wgmma_commit() { asm volatile("wgmma.commit_group.sync.aligned;" ::: "memory"); }
template <int N> __device__ __forceinline__ void wgmma_wait() { asm volatile("wgmma.wait_group.sync.aligned %0;" :: "n"(N) : "memory"); }
__device__ __forceinline__ uint64_t make_desc(uint32_t addr, uint32_t lbo_bytes, uint32_t sbo_bytes, uint32_t layout) {
    return (uint64_t)((addr & 0x3FFFF) >> 4) | ((uint64_t)(lbo_bytes >> 4) << 16) | ((uint64_t)(sbo_bytes >> 4) << 32) | ((uint64_t)layout << 62);
}
template <int R> __device__ __forceinline__ void reg_alloc() { asm volatile("setmaxnreg.inc.sync.aligned.u32 %0;" :: "n"(R)); }
template <int R> __device__ __forceinline__ void reg_dealloc() { asm volatile("setmaxnreg.dec.sync.aligned.u32 %0;" :: "n"(R)); }
__device__ __forceinline__ void pdl_launch() { asm volatile("griddepcontrol.launch_dependents;" ::: "memory"); }
__device__ __forceinline__ void pdl_wait() { asm volatile("griddepcontrol.wait;" ::: "memory"); }
__device__ __forceinline__ void prefetch_map(const CUtensorMap* m) { asm volatile("prefetch.tensormap [%0];" :: "l"(m) : "memory"); }
__device__ __forceinline__ void named_bar(int id, int n) { asm volatile("bar.sync %0, %1;" :: "r"(id), "r"(n) : "memory"); }

__device__ __forceinline__ void wgmma_m64n256k16_ss(float (&d)[128], uint64_t descA, uint64_t descB, int scaleD) {
    asm volatile("{\n.reg .pred p;\nsetp.ne.b32 p, %130, 0;\n"
        "wgmma.mma_async.sync.aligned.m64n256k16.f32.bf16.bf16 {%0, %1, %2, %3, %4, %5, %6, %7, %8, %9, %10, %11, %12, %13, %14, %15, %16, %17, %18, %19, %20, %21, %22, %23, %24, %25, %26, %27, %28, %29, %30, %31, %32, %33, %34, %35, %36, %37, %38, %39, %40, %41, %42, %43, %44, %45, %46, %47, %48, %49, %50, %51, %52, %53, %54, %55, %56, %57, %58, %59, %60, %61, %62, %63, %64, %65, %66, %67, %68, %69, %70, %71, %72, %73, %74, %75, %76, %77, %78, %79, %80, %81, %82, %83, %84, %85, %86, %87, %88, %89, %90, %91, %92, %93, %94, %95, %96, %97, %98, %99, %100, %101, %102, %103, %104, %105, %106, %107, %108, %109, %110, %111, %112, %113, %114, %115, %116, %117, %118, %119, %120, %121, %122, %123, %124, %125, %126, %127}, %128, %129, p, 1, 1, 0, 1;\n}\n"
        : "+f"(d[0]), "+f"(d[1]), "+f"(d[2]), "+f"(d[3]), "+f"(d[4]), "+f"(d[5]), "+f"(d[6]), "+f"(d[7]), "+f"(d[8]), "+f"(d[9]), "+f"(d[10]), "+f"(d[11]), "+f"(d[12]), "+f"(d[13]), "+f"(d[14]), "+f"(d[15]), "+f"(d[16]), "+f"(d[17]), "+f"(d[18]), "+f"(d[19]), "+f"(d[20]), "+f"(d[21]), "+f"(d[22]), "+f"(d[23]), "+f"(d[24]), "+f"(d[25]), "+f"(d[26]), "+f"(d[27]), "+f"(d[28]), "+f"(d[29]), "+f"(d[30]), "+f"(d[31]), "+f"(d[32]), "+f"(d[33]), "+f"(d[34]), "+f"(d[35]), "+f"(d[36]), "+f"(d[37]), "+f"(d[38]), "+f"(d[39]), "+f"(d[40]), "+f"(d[41]), "+f"(d[42]), "+f"(d[43]), "+f"(d[44]), "+f"(d[45]), "+f"(d[46]), "+f"(d[47]), "+f"(d[48]), "+f"(d[49]), "+f"(d[50]), "+f"(d[51]), "+f"(d[52]), "+f"(d[53]), "+f"(d[54]), "+f"(d[55]), "+f"(d[56]), "+f"(d[57]), "+f"(d[58]), "+f"(d[59]), "+f"(d[60]), "+f"(d[61]), "+f"(d[62]), "+f"(d[63]), "+f"(d[64]), "+f"(d[65]), "+f"(d[66]), "+f"(d[67]), "+f"(d[68]), "+f"(d[69]), "+f"(d[70]), "+f"(d[71]), "+f"(d[72]), "+f"(d[73]), "+f"(d[74]), "+f"(d[75]), "+f"(d[76]), "+f"(d[77]), "+f"(d[78]), "+f"(d[79]), "+f"(d[80]), "+f"(d[81]), "+f"(d[82]), "+f"(d[83]), "+f"(d[84]), "+f"(d[85]), "+f"(d[86]), "+f"(d[87]), "+f"(d[88]), "+f"(d[89]), "+f"(d[90]), "+f"(d[91]), "+f"(d[92]), "+f"(d[93]), "+f"(d[94]), "+f"(d[95]), "+f"(d[96]), "+f"(d[97]), "+f"(d[98]), "+f"(d[99]), "+f"(d[100]), "+f"(d[101]), "+f"(d[102]), "+f"(d[103]), "+f"(d[104]), "+f"(d[105]), "+f"(d[106]), "+f"(d[107]), "+f"(d[108]), "+f"(d[109]), "+f"(d[110]), "+f"(d[111]), "+f"(d[112]), "+f"(d[113]), "+f"(d[114]), "+f"(d[115]), "+f"(d[116]), "+f"(d[117]), "+f"(d[118]), "+f"(d[119]), "+f"(d[120]), "+f"(d[121]), "+f"(d[122]), "+f"(d[123]), "+f"(d[124]), "+f"(d[125]), "+f"(d[126]), "+f"(d[127])
        : "l"(descA), "l"(descB), "r"(scaleD));
}

__device__ __forceinline__ void wgmma_m64n192k16_ss(float (&d)[96], uint64_t descA, uint64_t descB, int scaleD) {
    asm volatile("{\n.reg .pred p;\nsetp.ne.b32 p, %98, 0;\n"
        "wgmma.mma_async.sync.aligned.m64n192k16.f32.bf16.bf16 {%0, %1, %2, %3, %4, %5, %6, %7, %8, %9, %10, %11, %12, %13, %14, %15, %16, %17, %18, %19, %20, %21, %22, %23, %24, %25, %26, %27, %28, %29, %30, %31, %32, %33, %34, %35, %36, %37, %38, %39, %40, %41, %42, %43, %44, %45, %46, %47, %48, %49, %50, %51, %52, %53, %54, %55, %56, %57, %58, %59, %60, %61, %62, %63, %64, %65, %66, %67, %68, %69, %70, %71, %72, %73, %74, %75, %76, %77, %78, %79, %80, %81, %82, %83, %84, %85, %86, %87, %88, %89, %90, %91, %92, %93, %94, %95}, %96, %97, p, 1, 1, 0, 1;\n}\n"
        : "+f"(d[0]), "+f"(d[1]), "+f"(d[2]), "+f"(d[3]), "+f"(d[4]), "+f"(d[5]), "+f"(d[6]), "+f"(d[7]), "+f"(d[8]), "+f"(d[9]), "+f"(d[10]), "+f"(d[11]), "+f"(d[12]), "+f"(d[13]), "+f"(d[14]), "+f"(d[15]), "+f"(d[16]), "+f"(d[17]), "+f"(d[18]), "+f"(d[19]), "+f"(d[20]), "+f"(d[21]), "+f"(d[22]), "+f"(d[23]), "+f"(d[24]), "+f"(d[25]), "+f"(d[26]), "+f"(d[27]), "+f"(d[28]), "+f"(d[29]), "+f"(d[30]), "+f"(d[31]), "+f"(d[32]), "+f"(d[33]), "+f"(d[34]), "+f"(d[35]), "+f"(d[36]), "+f"(d[37]), "+f"(d[38]), "+f"(d[39]), "+f"(d[40]), "+f"(d[41]), "+f"(d[42]), "+f"(d[43]), "+f"(d[44]), "+f"(d[45]), "+f"(d[46]), "+f"(d[47]), "+f"(d[48]), "+f"(d[49]), "+f"(d[50]), "+f"(d[51]), "+f"(d[52]), "+f"(d[53]), "+f"(d[54]), "+f"(d[55]), "+f"(d[56]), "+f"(d[57]), "+f"(d[58]), "+f"(d[59]), "+f"(d[60]), "+f"(d[61]), "+f"(d[62]), "+f"(d[63]), "+f"(d[64]), "+f"(d[65]), "+f"(d[66]), "+f"(d[67]), "+f"(d[68]), "+f"(d[69]), "+f"(d[70]), "+f"(d[71]), "+f"(d[72]), "+f"(d[73]), "+f"(d[74]), "+f"(d[75]), "+f"(d[76]), "+f"(d[77]), "+f"(d[78]), "+f"(d[79]), "+f"(d[80]), "+f"(d[81]), "+f"(d[82]), "+f"(d[83]), "+f"(d[84]), "+f"(d[85]), "+f"(d[86]), "+f"(d[87]), "+f"(d[88]), "+f"(d[89]), "+f"(d[90]), "+f"(d[91]), "+f"(d[92]), "+f"(d[93]), "+f"(d[94]), "+f"(d[95])
        : "l"(descA), "l"(descB), "r"(scaleD));
}

__device__ __forceinline__ void wgmma_m64n128k16_ss(float (&d)[64], uint64_t descA, uint64_t descB, int scaleD) {
    asm volatile("{\n.reg .pred p;\nsetp.ne.b32 p, %66, 0;\n"
        "wgmma.mma_async.sync.aligned.m64n128k16.f32.bf16.bf16 {%0, %1, %2, %3, %4, %5, %6, %7, %8, %9, %10, %11, %12, %13, %14, %15, %16, %17, %18, %19, %20, %21, %22, %23, %24, %25, %26, %27, %28, %29, %30, %31, %32, %33, %34, %35, %36, %37, %38, %39, %40, %41, %42, %43, %44, %45, %46, %47, %48, %49, %50, %51, %52, %53, %54, %55, %56, %57, %58, %59, %60, %61, %62, %63}, %64, %65, p, 1, 1, 0, 1;\n}\n"
        : "+f"(d[0]), "+f"(d[1]), "+f"(d[2]), "+f"(d[3]), "+f"(d[4]), "+f"(d[5]), "+f"(d[6]), "+f"(d[7]), "+f"(d[8]), "+f"(d[9]), "+f"(d[10]), "+f"(d[11]), "+f"(d[12]), "+f"(d[13]), "+f"(d[14]), "+f"(d[15]), "+f"(d[16]), "+f"(d[17]), "+f"(d[18]), "+f"(d[19]), "+f"(d[20]), "+f"(d[21]), "+f"(d[22]), "+f"(d[23]), "+f"(d[24]), "+f"(d[25]), "+f"(d[26]), "+f"(d[27]), "+f"(d[28]), "+f"(d[29]), "+f"(d[30]), "+f"(d[31]), "+f"(d[32]), "+f"(d[33]), "+f"(d[34]), "+f"(d[35]), "+f"(d[36]), "+f"(d[37]), "+f"(d[38]), "+f"(d[39]), "+f"(d[40]), "+f"(d[41]), "+f"(d[42]), "+f"(d[43]), "+f"(d[44]), "+f"(d[45]), "+f"(d[46]), "+f"(d[47]), "+f"(d[48]), "+f"(d[49]), "+f"(d[50]), "+f"(d[51]), "+f"(d[52]), "+f"(d[53]), "+f"(d[54]), "+f"(d[55]), "+f"(d[56]), "+f"(d[57]), "+f"(d[58]), "+f"(d[59]), "+f"(d[60]), "+f"(d[61]), "+f"(d[62]), "+f"(d[63])
        : "l"(descA), "l"(descB), "r"(scaleD));
}

__device__ __forceinline__ void quad_transpose(uint32_t& r0, uint32_t& r1, uint32_t& r2, uint32_t& r3, int t) {
    const bool o1 = t & 1, o2 = t & 2;
    uint32_t x, y;
    x = o1 ? r0 : r1; y = __shfl_xor_sync(0xffffffffu, x, 1); if (o1) r0 = y; else r1 = y;
    x = o1 ? r2 : r3; y = __shfl_xor_sync(0xffffffffu, x, 1); if (o1) r2 = y; else r3 = y;
    x = o2 ? r0 : r2; y = __shfl_xor_sync(0xffffffffu, x, 2); if (o2) r0 = y; else r2 = y;
    x = o2 ? r1 : r3; y = __shfl_xor_sync(0xffffffffu, x, 2); if (o2) r1 = y; else r3 = y;
}

__device__ __forceinline__ float warp_sum(float s) {
#pragma unroll
    for (int o = 16; o > 0; o >>= 1) s += __shfl_xor_sync(0xffffffffu, s, o);
    return s;
}
__device__ __forceinline__ uint32_t hsub2(uint32_t a, uint32_t b) {
    __nv_bfloat162 r = __hsub2_rn(*reinterpret_cast<__nv_bfloat162*>(&a), *reinterpret_cast<__nv_bfloat162*>(&b));
    return *reinterpret_cast<uint32_t*>(&r);
}
__device__ __forceinline__ void ln_stats2(const uint32_t (&x)[2][8], float2 (&st)[2]) {
    float piv[2], s[2], ss[2];
#pragma unroll
    for (int r = 0; r < 2; r++) piv[r] = __shfl_sync(0xffffffffu, bf_lo(x[r][0]), 0);
#pragma unroll
    for (int r = 0; r < 2; r++) {
        float s0 = 0.f, s1 = 0.f, q0 = 0.f, q1 = 0.f;
#pragma unroll
        for (int i = 0; i < 8; i++) {
            const float d0 = bf_lo(x[r][i]) - piv[r], d1 = bf_hi(x[r][i]) - piv[r];
            s0 += d0; s1 += d1; q0 = fmaf(d0, d0, q0); q1 = fmaf(d1, d1, q1);
        }
        s[r] = s0 + s1; ss[r] = q0 + q1;
    }
#pragma unroll
    for (int o = 16; o > 0; o >>= 1) {
#pragma unroll
        for (int r = 0; r < 2; r++) { s[r] += __shfl_xor_sync(0xffffffffu, s[r], o); ss[r] += __shfl_xor_sync(0xffffffffu, ss[r], o); }
    }
#pragma unroll
    for (int r = 0; r < 2; r++) {
        const float md = s[r] * (1.0f / D_);
        const float var = bf16r(fmaxf(fmaf(-md, md, ss[r] * (1.0f / D_)), 0.f));
        st[r] = make_float2(bf16r(piv[r] + md), 1.0f / bf16r(sqrtf(bf16r(var + 1e-5f))));
    }
}
__device__ __forceinline__ void ln_apply(const uint32_t (&x)[8], float2 st, uint32_t (&o)[8]) {
    const uint32_t m2 = pack_bf16(st.x, st.x);
#pragma unroll
    for (int i = 0; i < 8; i++) {
        const uint32_t d = hsub2(x[i], m2);
        o[i] = pack_bf16(bf_lo(d) * st.y, bf_hi(d) * st.y);
    }
}

constexpr int K1_THREADS = 256;
constexpr int UT_PAD = 128;
constexpr int UT_LEN = UT_PAD + S_;
constexpr int KR_LEN = 2080;
constexpr int YP_LEN = S_ + (S_ / 32) * 8;

struct __align__(128) K1Smem {
    bf16 uT[4][UT_LEN];
    bf16 kr[4][2][KR_LEN];
    float yP[4][YP_LEN];
    uint64_t bar;
    uint8_t pad[32768];
};

__device__ __forceinline__ void mma16816(float (&c)[4], uint32_t a0, uint32_t a1, uint32_t a2, uint32_t a3, uint32_t b0, uint32_t b1) {
    asm("mma.sync.aligned.m16n8k16.row.col.f32.bf16.bf16.f32 {%0,%1,%2,%3}, {%4,%5,%6,%7}, {%8,%9}, {%0,%1,%2,%3};"
        : "+f"(c[0]), "+f"(c[1]), "+f"(c[2]), "+f"(c[3])
        : "r"(a0), "r"(a1), "r"(a2), "r"(a3), "r"(b0), "r"(b1));
}
__device__ __forceinline__ void ldsm_x4(uint32_t& r0, uint32_t& r1, uint32_t& r2, uint32_t& r3, uint32_t addr) {
    asm volatile("ldmatrix.sync.aligned.m8n8.x4.shared.b16 {%0,%1,%2,%3}, [%4];" : "=r"(r0), "=r"(r1), "=r"(r2), "=r"(r3) : "r"(addr) : "memory");
}

__device__ __forceinline__ void conv_mma(const bf16* uTc, const bf16* krlane, float (&acc)[16][4], int lane, int half) {
    const int lrow = lane & 7, lk = (lane >> 3) & 1, lt = lane >> 4;
    const uint32_t ubase = smem_u32(uTc) + (UT_PAD + 16 * (8 * lt + lrow) + 8 * lk) * 2;
#pragma unroll 1
    for (int pp = 0; pp < 4; pp++) {
        const int p = half * 4 + pp;
        uint32_t U[16][2];
#pragma unroll
        for (int j = 0; j < 16; j += 2) ldsm_x4(U[j][0], U[j][1], U[j + 1][0], U[j + 1][1], ubase + (j * 128 - p * 16) * 2);
        const uint32_t* kp = reinterpret_cast<const uint32_t*>(krlane - 16 * p);
        const volatile uint32_t* kpv = kp;
        uint32_t a0 = kp[0], a1 = kp[-4], a2 = kp[4], a3 = kpv[0];
#pragma unroll
        for (int q = 0; q < 16; q++) {
            uint32_t b0 = 0, b1 = 0, b2 = 0, b3 = 0;
            if (q < 15) { b0 = kp[-64 * (q + 1)]; b1 = kp[-64 * (q + 1) - 4]; b2 = kp[-64 * (q + 1) + 4]; b3 = kpv[-64 * (q + 1)]; }
#pragma unroll
            for (int n = 15; n >= q; n--) mma16816(acc[n], a0, a1, a2, a3, U[n - q][0], U[n - q][1]);
            a0 = b0; a1 = b1; a2 = b2; a3 = b3;
        }
    }
}

__global__ void __cluster_dims__(2, 1, 1) __launch_bounds__(K1_THREADS, 1)
conv_kernel(const bf16* __restrict__ q, const bf16* __restrict__ k, const bf16* __restrict__ v,
            const bf16* __restrict__ shift_k, const bf16* __restrict__ ssm_k, const bf16* __restrict__ ssm_D) {
    extern __shared__ __align__(1024) uint8_t smem_raw[];
    pdl_launch();
    K1Smem& sm = *reinterpret_cast<K1Smem*>(smem_raw);
    const int tid = threadIdx.x, lane = tid & 31, warp = tid >> 5;
    const int bid = blockIdx.x;
    const int rank = bid & 1;
    const int c0 = 8 * (bid >> 1);
    const int cown = c0 + 4 * rank;
#define TMT 0
    TM(0, 0);
    const uint32_t bar = smem_u32(&sm.bar);
    if (tid == 0) {
        mbar_init(bar, 1);
        asm volatile("fence.mbarrier_init.release.cluster;" ::: "memory");
        mbar_expect_tx(bar, 1024 * 4 * 2);
    }
    cluster_arrive_relaxed();

    const int s0 = 1024 * rank + 4 * tid;
    uint4 kk[7], vv[4], sw[4];
#pragma unroll
    for (int i = 0; i < 4; i++) kk[3 + i] = ldg128(k + (size_t)(s0 + i) * D_ + c0);
#pragma unroll
    for (int i = 0; i < 4; i++) vv[i] = ldg128(v + (size_t)(s0 + i) * D_ + c0);
    if (lane == 0) {
#pragma unroll
        for (int i = 0; i < 3; i++) {
            const int s = s0 - 3 + i;
            kk[i] = make_uint4(0, 0, 0, 0);
            if (s >= 0) kk[i] = ldg128(k + (size_t)s * D_ + c0);
        }
    }
#pragma unroll
    for (int i = 0; i < 4; i++) sw[i] = ldg128(shift_k + (size_t)c0 * 4 + 8 * i);
    uint4 kq[4]; uint32_t nx[4];
#pragma unroll
    for (int c = 0; c < 4; c++) {
        const bf16* kr = ssm_k + (size_t)(cown + c) * S_;
        kq[c] = ldg128(kr + 8 * tid);
        nx[c] = 0u;
        if (tid < 255) nx[c] = ldg16(kr + 8 * tid + 8);
    }
    const uint32_t dval = ldg16(ssm_D + cown + (warp >> 1));
    uint32_t xq[2][8];
#pragma unroll
    for (int r = 0; r < 2; r++) {
        const uint4 qa = ldg128(q + (size_t)(16 * bid + 2 * warp + r) * D_ + 8 * lane);
        const uint4 qb = ldg128(q + (size_t)(16 * bid + 2 * warp + r) * D_ + 8 * (lane + 32));
        xq[r][0] = qa.x; xq[r][1] = qa.y; xq[r][2] = qa.z; xq[r][3] = qa.w; xq[r][4] = qb.x; xq[r][5] = qb.y; xq[r][6] = qb.z; xq[r][7] = qb.w;
    }
    if (tid < 64) *reinterpret_cast<uint4*>(&sm.uT[tid >> 4][(tid & 15) * 8]) = make_uint4(0, 0, 0, 0);
#pragma unroll
    for (int i = 0; i < 3; i++) {
        uint4 t;
        t.x = __shfl_up_sync(0xffffffffu, kk[4 + i].x, 1); t.y = __shfl_up_sync(0xffffffffu, kk[4 + i].y, 1);
        t.z = __shfl_up_sync(0xffffffffu, kk[4 + i].z, 1); t.w = __shfl_up_sync(0xffffffffu, kk[4 + i].w, 1);
        if (lane != 0) kk[i] = t;
    }
    uint32_t kvw[4][4];
    const uint32_t* kkw = reinterpret_cast<const uint32_t*>(kk);
    const uint32_t* vvw = reinterpret_cast<const uint32_t*>(vv);
#pragma unroll
    for (int i2 = 0; i2 < 4; i2++) {
        const uint32_t t0 = __byte_perm(sw[i2].x, sw[i2].z, 0x5410), t1 = __byte_perm(sw[i2].x, sw[i2].z, 0x7632);
        const uint32_t t2 = __byte_perm(sw[i2].y, sw[i2].w, 0x5410), t3 = __byte_perm(sw[i2].y, sw[i2].w, 0x7632);
#pragma unroll
        for (int r = 0; r < 4; r++) {
            uint32_t a = hmul2(kkw[(r + 0) * 4 + i2], t3);
            a = hadd2(a, hmul2(kkw[(r + 1) * 4 + i2], t2));
            a = hadd2(a, hmul2(kkw[(r + 2) * 4 + i2], t1));
            a = hadd2(a, hmul2(kkw[(r + 3) * 4 + i2], t0));
            kvw[r][i2] = hmul2(a, vvw[r * 4 + i2]);
        }
    }
    TM(0, 1);
    cluster_wait();
    {
        const uint32_t rbar = mapa(bar, (uint32_t)(rank ^ 1));
#pragma unroll
        for (int i2 = 0; i2 < 4; i2++) {
#pragma unroll
            for (int e = 0; e < 2; e++) {
                const uint32_t sel = e ? 0x7632 : 0x5410;
                const uint32_t w0 = __byte_perm(kvw[0][i2], kvw[1][i2], sel), w1 = __byte_perm(kvw[2][i2], kvw[3][i2], sel);
                const int cc = 2 * i2 + e;
                if ((cc >> 2) == rank) {
                    *reinterpret_cast<uint2*>(&sm.uT[cc & 3][UT_PAD + s0]) = make_uint2(w0, w1);
                } else {
                    st_async_v2(mapa(smem_u32(&sm.uT[cc & 3][UT_PAD + s0]), (uint32_t)(rank ^ 1)), w0, w1, rbar);
                }
            }
        }
    }
#pragma unroll
    for (int c = 0; c < 4; c++) {
        uint4 a, b;
        a.x = __byte_perm(kq[c].w, 0, 0x1032); a.y = __byte_perm(kq[c].z, 0, 0x1032);
        a.z = __byte_perm(kq[c].y, 0, 0x1032); a.w = __byte_perm(kq[c].x, 0, 0x1032);
        b.x = __byte_perm(nx[c], kq[c].w, 0x7610); b.y = __byte_perm(kq[c].w, kq[c].z, 0x7610);
        b.z = __byte_perm(kq[c].z, kq[c].y, 0x7610); b.w = __byte_perm(kq[c].y, kq[c].x, 0x7610);
        *reinterpret_cast<uint4*>(&sm.kr[c][0][2040 - 8 * tid]) = a;
        *reinterpret_cast<uint4*>(&sm.kr[c][1][2040 - 8 * tid]) = b;
        if (tid == 0) {
            *reinterpret_cast<uint4*>(&sm.kr[c][1][2048]) = make_uint4(kq[c].x & 0xffffu, 0, 0, 0);
        } else if (tid < 8) {
            if (tid < 4) *reinterpret_cast<uint4*>(&sm.kr[c][1][2048 + 8 * tid]) = make_uint4(0, 0, 0, 0);
            else *reinterpret_cast<uint4*>(&sm.kr[c][0][2048 + 8 * (tid - 4)]) = make_uint4(0, 0, 0, 0);
        }
    }
    {
        float2 st[2];
        ln_stats2(xq, st);
        if (lane < 2) g_st1[16 * bid + 2 * warp + lane] = lane ? st[1] : st[0];
    }
    TM(0, 3);
    __syncthreads();
    mbar_wait_cluster(bar, 0);
    TM(0, 4);

    const int ch = warp >> 1, half = warp & 1;
    const int g = lane >> 2, t = lane & 3;
    float acc[16][4];
#pragma unroll
    for (int i = 0; i < 16; i++) { acc[i][0] = acc[i][1] = acc[i][2] = acc[i][3] = 0.f; }
    const bf16* krlane = (g & 1) ? &sm.kr[ch][0][2047 - g + 2 * t] : &sm.kr[ch][1][2048 - g + 2 * t];
    conv_mma(sm.uT[ch], krlane, acc, lane, half);
    TM(0, 5);
    float* yp = &sm.yP[ch][40 * t + g];
    if (half) {
#pragma unroll
        for (int n = 0; n < 16; n++) {
            yp[160 * n] = acc[n][0];
            yp[160 * n + 16] = acc[n][1];
            yp[160 * n + 8] = acc[n][2];
            yp[160 * n + 24] = acc[n][3];
        }
    }
    named_bar(1 + ch, 64);
    if (!half) {
#pragma unroll
        for (int n = 0; n < 16; n++) {
            yp[160 * n] += acc[n][0];
            yp[160 * n + 16] += acc[n][1];
            yp[160 * n + 8] += acc[n][2];
            yp[160 * n + 24] += acc[n][3];
        }
    }
    named_bar(1 + ch, 64);
    TM(0, 6);
    {
        const int tt = tid & 63;
        bf16* dst = g_yT + (size_t)(cown + ch) * S_;
        const uint32_t d2 = dval * 0x10001u;
#pragma unroll
        for (int j = 0; j < 4; j++) {
            const int s = (j * 64 + tt) * 8;
            const float* src = &sm.yP[ch][s + (s >> 5) * 8];
            const float4 a = *reinterpret_cast<const float4*>(src), b = *reinterpret_cast<const float4*>(src + 4);
            const uint4 kv4 = *reinterpret_cast<const uint4*>(&sm.uT[ch][UT_PAD + s]);
            *reinterpret_cast<uint4*>(dst + s) = make_uint4(hadd2(pack_bf16(a.x, a.y), hmul2(kv4.x, d2)), hadd2(pack_bf16(a.z, a.w), hmul2(kv4.y, d2)),
                                                            hadd2(pack_bf16(b.x, b.y), hmul2(kv4.z, d2)), hadd2(pack_bf16(b.z, b.w), hmul2(kv4.w, d2)));
        }
    }
    TM(0, 7);
#undef TMT
}

constexpr int G1_THREADS = 384;
constexpr int G1_STAGES = 3;
constexpr int G1_A_BYTES = 8 * 16384;
constexpr int G1_B_STAGE = 32768;
constexpr int G1_OFF_B = G1_A_BYTES;
constexpr int G1_OFF_BAR = G1_OFF_B + G1_STAGES * G1_B_STAGE;
constexpr int G1_SMEM = G1_OFF_BAR + 256;

__device__ __forceinline__ float sigmoid_fast(float x) {
    float t; asm("tanh.approx.f32 %0, %1;" : "=f"(t) : "f"(0.5f * x));
    return fmaf(t, 0.5f, 0.5f);
}

template <int NT>
__device__ __forceinline__ void g1_epilogue(const float (&acc)[NT * 8], bf16* out0, int t) {
#pragma unroll
    for (int j0 = 0; j0 < NT; j0 += 4) {
        uint32_t P0[4], P1[4];
#pragma unroll
        for (int jj = 0; jj < 4; jj++) {
            const int j = j0 + jj;
            float r[4];
#pragma unroll
            for (int e = 0; e < 4; e++) r[e] = sigmoid_fast(acc[4 * j + e]) * acc[4 * (NT + j) + e];
            P0[jj] = pack_bf16(r[0], r[1]);
            P1[jj] = pack_bf16(r[2], r[3]);
        }
        quad_transpose(P0[0], P0[1], P0[2], P0[3], t);
        quad_transpose(P1[0], P1[1], P1[2], P1[3], t);
        *reinterpret_cast<uint4*>(out0 + 8 * (j0 + t)) = make_uint4(P0[0], P0[1], P0[2], P0[3]);
        *reinterpret_cast<uint4*>(out0 + 8 * F_ + 8 * (j0 + t)) = make_uint4(P1[0], P1[1], P1[2], P1[3]);
    }
}

__global__ void __cluster_dims__(2, 1, 1) __launch_bounds__(G1_THREADS, 1)
gemm1_kernel(const __grid_constant__ CUtensorMap mapA, const __grid_constant__ CUtensorMap mapG4, const __grid_constant__ CUtensorMap mapU4,
             const __grid_constant__ CUtensorMap mapG3, const __grid_constant__ CUtensorMap mapU3, const bf16* __restrict__ q) {
    extern __shared__ __align__(1024) uint8_t smem_raw[];
    const uint32_t sb = smem_u32(smem_raw);
    const int tid = threadIdx.x, lane = tid & 31, warp = tid >> 5, wgi = tid >> 7;
    const int rank = blockIdx.x & 1;
    const int cb = blockIdx.x & 7, rb = blockIdx.x >> 3;
#define TMT 128
    TM(2, 0);
    pdl_launch();
    if (tid == 32) { prefetch_map(&mapA); prefetch_map(&mapG3); prefetch_map(&mapU3); }
    const uint32_t barA = sb + G1_OFF_BAR;
    const uint32_t barF = barA + 64;
    const uint32_t barE = barF + 8 * G1_STAGES;
    if (tid == 0) {
        for (int i = 0; i < 8; i++) mbar_init(barA + 8 * i, 1);
        for (int i = 0; i < G1_STAGES; i++) { mbar_init(barF + 8 * i, 1); mbar_init(barE + 8 * i, 2); }
        for (int i = 0; i < 8; i++) mbar_expect_tx(barA + 8 * i, 16384);
        asm volatile("fence.mbarrier_init.release.cluster;" ::: "memory");
        for (int it = 0; it < G1_STAGES; it++) {
            const uint32_t dst = sb + G1_OFF_B + it * G1_B_STAGE;
            mbar_expect_tx(barF + 8 * it, 32768);
            tma_load_3d(dst, &mapG4, barF + 8 * it, 0, it * 64, cb * 7);
            tma_load_3d(dst + 16384, &mapU4, barF + 8 * it, 0, it * 64, cb * 7);
        }
    }
    __syncthreads();
    cluster_arrive_relaxed();
    cluster_wait();

    if (wgi == 0) {
        reg_dealloc<40>();
        if (lane == 0 && warp == 0) {
            int st = 0, ph = 0;
            for (int it = G1_STAGES; it < 16; it++) {
                const int kc = it & 7;
                mbar_wait(barE + 8 * st, ph);
                const uint32_t dst = sb + G1_OFF_B + st * G1_B_STAGE;
                if (it < 8) {
                    mbar_expect_tx(barF + 8 * st, 32768);
                    tma_load_3d(dst, &mapG4, barF + 8 * st, 0, kc * 64, cb * 7);
                    tma_load_3d(dst + 16384, &mapU4, barF + 8 * st, 0, kc * 64, cb * 7);
                } else {
                    mbar_expect_tx(barF + 8 * st, 24576);
                    tma_load_3d(dst, &mapG3, barF + 8 * st, 0, kc * 64, cb * 7 + 4);
                    tma_load_3d(dst + 12288, &mapU3, barF + 8 * st, 0, kc * 64, cb * 7 + 4);
                }
                if (++st == G1_STAGES) { st = 0; ph ^= 1; }
            }
        } else if (lane == 0 && warp == 1) {
            unsigned int c; int spins = 0;
            do { asm volatile("ld.acquire.gpu.global.u32 %0, [%1];" : "=r"(c) : "l"(&g_cnt[rb]) : "memory"); } while (c < 8u && ++spins < (1 << 22));
            asm volatile("fence.proxy.async;" ::: "memory");
            TR(0, 0);
            for (int i = 0; i < 4; i++) {
                const int c = 2 * i + rank;
                tma_load_2d_mc(sb + c * 16384, &mapA, barA + 8 * c, c * 64, rb * 128, (uint16_t)3);
            }
        }
        __syncwarp();
    } else {
        const int cw = wgi - 1;
        const int g = lane >> 2, t = lane & 3, wl = warp & 3, tl = tid & 127;
        {
            uint32_t (*ys)[D_ / 2 + 4] = reinterpret_cast<uint32_t (*)[D_ / 2 + 4]>(smem_raw);
            const int s0 = rb * 128 + cb * 16;
            const int cwp = warp - 4, p = tid - 128;
            uint32_t x[2][8];
#pragma unroll
            for (int r = 0; r < 2; r++) {
                const uint4 qa = ldg128(q + (size_t)(s0 + 2 * cwp + r) * D_ + 8 * lane);
                const uint4 qb = ldg128(q + (size_t)(s0 + 2 * cwp + r) * D_ + 8 * (lane + 32));
                x[r][0] = qa.x; x[r][1] = qa.y; x[r][2] = qa.z; x[r][3] = qa.w; x[r][4] = qb.x; x[r][5] = qb.y; x[r][6] = qb.z; x[r][7] = qb.w;
            }
            pdl_wait();
            TM(1, 0);
            const uint4 stw = ldcg128(&g_st1[s0 + 2 * cwp]);
            {
                const bf16* y0 = g_yT + (size_t)(2 * p) * S_ + s0;
                const uint4 a0 = ldcg128(y0), a1 = ldcg128(y0 + 8), b0 = ldcg128(y0 + S_), b1 = ldcg128(y0 + S_ + 8);
                const uint32_t aw[8] = {a0.x, a0.y, a0.z, a0.w, a1.x, a1.y, a1.z, a1.w};
                const uint32_t bw[8] = {b0.x, b0.y, b0.z, b0.w, b1.x, b1.y, b1.z, b1.w};
#pragma unroll
                for (int j = 0; j < 8; j++) {
                    ys[2 * j][p] = __byte_perm(aw[j], bw[j], 0x5410);
                    ys[2 * j + 1][p] = __byte_perm(aw[j], bw[j], 0x7632);
                }
            }
            uint32_t qn[2][8];
            ln_apply(x[0], make_float2(__uint_as_float(stw.x), __uint_as_float(stw.y)), qn[0]);
            ln_apply(x[1], make_float2(__uint_as_float(stw.z), __uint_as_float(stw.w)), qn[1]);
            named_bar(1, 256);
            TM(1, 1);
            uint32_t h[2][8], hn[2][8];
#pragma unroll
            for (int r = 0; r < 2; r++) {
#pragma unroll
                for (int i = 0; i < 2; i++) {
                    const uint4 yw4 = *reinterpret_cast<const uint4*>(&ys[2 * cwp + r][4 * (lane + 32 * i)]);
                    const uint32_t yw[4] = {yw4.x, yw4.y, yw4.z, yw4.w};
#pragma unroll
                    for (int j = 0; j < 4; j++) h[r][4 * i + j] = hadd2(x[r][4 * i + j], hmul2(qn[r][4 * i + j], yw[j]));
                }
            }
            float2 st2[2];
            ln_stats2(h, st2);
#pragma unroll
            for (int r = 0; r < 2; r++) {
                ln_apply(h[r], st2[r], hn[r]);
#pragma unroll
                for (int i = 0; i < 2; i++) {
                    const size_t off = (size_t)(s0 + 2 * cwp + r) * D_ + 8 * (lane + 32 * i);
                    *reinterpret_cast<uint4*>(g_hn + off) = make_uint4(hn[r][4 * i], hn[r][4 * i + 1], hn[r][4 * i + 2], hn[r][4 * i + 3]);
                }
            }
            named_bar(1, 256);
            if (p == 0) { __threadfence(); atomicAdd(&g_cnt[rb], 1u); }
#pragma unroll
            for (int r = 0; r < 2; r++) {
#pragma unroll
                for (int i = 0; i < 2; i++) {
                    const size_t off = (size_t)(s0 + 2 * cwp + r) * D_ + 8 * (lane + 32 * i);
                    *reinterpret_cast<uint4*>(g_h + off) = make_uint4(h[r][4 * i], h[r][4 * i + 1], h[r][4 * i + 2], h[r][4 * i + 3]);
                }
            }
            TM(1, 2);
        }
        reg_alloc<232>();
        bf16* outp = g_hh + (size_t)(rb * 128 + cw * 64 + wl * 16 + g) * F_ + cb * 224;
        int st = 0, ph = 0;
        {
            float acc[128];
#pragma unroll 1
            for (int kc = 0; kc < 8; kc++) {
                mbar_wait(barA + 8 * kc, 0);
                mbar_wait(barF + 8 * st, ph);
                if (tl == 0 && cw == 0) TR(1, kc);
                wgmma_fence();
                const uint32_t aaddr = sb + kc * 16384 + cw * 8192;
                const uint32_t baddr = sb + G1_OFF_B + st * G1_B_STAGE;
#pragma unroll
                for (int kk = 0; kk < 4; kk++)
                    wgmma_m64n256k16_ss(acc, make_desc(aaddr + kk * 32, 16, 1024, 1), make_desc(baddr + kk * 1024, 4096, 512, 2), (kc | kk) != 0);
                wgmma_commit();
                wgmma_wait<0>();
                if (tl == 0) mbar_arrive(barE + 8 * st);
                if (++st == G1_STAGES) { st = 0; ph ^= 1; }
            }
            TM(2, 1);
            g1_epilogue<16>(acc, outp, t);
            TM(2, 2);
        }
        {
            float acc[96];
#pragma unroll 1
            for (int kc = 0; kc < 8; kc++) {
                mbar_wait(barF + 8 * st, ph);
                if (tl == 0 && cw == 0) TR(1, 8 + kc);
                wgmma_fence();
                const uint32_t aaddr = sb + kc * 16384 + cw * 8192;
                const uint32_t baddr = sb + G1_OFF_B + st * G1_B_STAGE;
#pragma unroll
                for (int kk = 0; kk < 4; kk++)
                    wgmma_m64n192k16_ss(acc, make_desc(aaddr + kk * 32, 16, 1024, 1), make_desc(baddr + kk * 1024, 4096, 512, 2), (kc | kk) != 0);
                wgmma_commit();
                wgmma_wait<0>();
                if (tl == 0) mbar_arrive(barE + 8 * st);
                if (++st == G1_STAGES) { st = 0; ph ^= 1; }
            }
            TM(2, 3);
            g1_epilogue<12>(acc, outp + 128, t);
            TM(2, 4);
        }
    }
}

constexpr int G2_THREADS = 384;
constexpr int G2_STAGES = 6;
constexpr int G2_STAGE = 32768;
constexpr int G2_OFF_X = G2_STAGES * G2_STAGE;
constexpr int G2_OFF_BAR = G2_OFF_X + 32768;
constexpr int G2_SMEM = G2_OFF_BAR + 128;
constexpr int G2_KSTEPS = 14;

__global__ void __cluster_dims__(2, 1, 1) __launch_bounds__(G2_THREADS, 1)
gemm2_kernel(const __grid_constant__ CUtensorMap mapHH, const __grid_constant__ CUtensorMap mapWd, bf16* __restrict__ out) {
    extern __shared__ __align__(1024) uint8_t smem_raw[];
    const uint32_t sb = smem_u32(smem_raw);
    const int tid = threadIdx.x, lane = tid & 31, warp = tid >> 5, wgi = tid >> 7;
    const int ks = blockIdx.x & 1, nb = (blockIdx.x >> 1) & 3, rb = blockIdx.x >> 3;
    TM(3, 0);
    if (tid == 32) { prefetch_map(&mapHH); }
    const uint32_t barF = sb + G2_OFF_BAR;
    const uint32_t barE = barF + 8 * G2_STAGES;
    const uint32_t barX = barE + 8 * G2_STAGES;
    if (tid == 0) {
        for (int i = 0; i < G2_STAGES; i++) { mbar_init(barF + 8 * i, 1); mbar_init(barE + 8 * i, 2); }
        mbar_init(barX, 1);
        asm volatile("fence.mbarrier_init.release.cluster;" ::: "memory");
        mbar_expect_tx(barX, 32768);
        for (int it = 0; it < G2_STAGES; it++) {
            mbar_expect_tx(barF + 8 * it, 32768);
            tma_load_3d(sb + it * G2_STAGE + 16384, &mapWd, barF + 8 * it, 0, ks * 896 + it * 64, nb * 2);
        }
    }
    __syncthreads();
    cluster_arrive_relaxed();

    if (wgi == 0) {
        if (tid == 0) {
            pdl_wait();
            for (int it = 0; it < G2_STAGES; it++)
                tma_load_2d(sb + it * G2_STAGE, &mapHH, barF + 8 * it, ks * 896 + it * 64, rb * 128);
            int st = 0, ph = 0;
            for (int it = G2_STAGES; it < G2_KSTEPS; it++) {
                mbar_wait(barE + 8 * st, ph);
                const uint32_t dst = sb + st * G2_STAGE;
                const int k0 = ks * 896 + it * 64;
                mbar_expect_tx(barF + 8 * st, 32768);
                tma_load_2d(dst, &mapHH, barF + 8 * st, k0, rb * 128);
                tma_load_3d(dst + 16384, &mapWd, barF + 8 * st, 0, k0, nb * 2);
                if (++st == G2_STAGES) { st = 0; ph ^= 1; }
            }
        }
        __syncwarp();
        cluster_wait();
    } else {
        const int cw = wgi - 1;
        const int g = lane >> 2, t = lane & 3, wl = warp & 3;
        const int tl = tid & 127;
        int st = 0, ph = 0;
        float acc[64];
        pdl_wait();
        if (blockIdx.x == 0 && tid >= 128 && tid < 144) g_cnt[tid - 128] = 0u;
#pragma unroll 1
        for (int it = 0; it < G2_KSTEPS; it++) {
            mbar_wait(barF + 8 * st, ph);
            if (it == 0) TM(3, 1);
            wgmma_fence();
            const uint32_t aaddr = sb + st * G2_STAGE + cw * 8192;
            const uint32_t baddr = sb + st * G2_STAGE + 16384;
#pragma unroll
            for (int kk = 0; kk < 4; kk++)
                wgmma_m64n128k16_ss(acc, make_desc(aaddr + kk * 32, 16, 1024, 1), make_desc(baddr + kk * 2048, 8192, 1024, 1), (it | kk) != 0);
            wgmma_commit();
            wgmma_wait<0>();
            if (tl == 0) mbar_arrive(barE + 8 * st);
            if (++st == G2_STAGES) { st = 0; ph ^= 1; }
        }
        TM(3, 2);
        cluster_wait();
        if (cw != ks) {
            const uint32_t dst = mapa(sb + G2_OFF_X + tl * 16, (uint32_t)(ks ^ 1));
            const uint32_t rbar = mapa(barX, (uint32_t)(ks ^ 1));
#pragma unroll
            for (int i = 0; i < 16; i++) st_async_v4f(dst + i * 2048, acc[4 * i], acc[4 * i + 1], acc[4 * i + 2], acc[4 * i + 3], rbar);
        } else {
            const float4* xb = reinterpret_cast<const float4*>(smem_raw + G2_OFF_X) + tl;
            const int row0 = rb * 128 + cw * 64 + wl * 16 + g;
            const bf16* h0 = g_h + (size_t)row0 * D_ + nb * 128;
            bf16* o0 = out + (size_t)row0 * D_ + nb * 128;
            uint32_t ha[16], hb[16];
#pragma unroll
            for (int j = 0; j < 16; j++) {
                ha[j] = __ldcg(reinterpret_cast<const uint32_t*>(h0 + 8 * j + 2 * t));
                hb[j] = __ldcg(reinterpret_cast<const uint32_t*>(h0 + 8 * D_ + 8 * j + 2 * t));
            }
            mbar_wait_cluster(barX, 0);
            TM(3, 4);
#pragma unroll
            for (int j0 = 0; j0 < 16; j0 += 4) {
                uint32_t P0[4], P1[4];
#pragma unroll
                for (int jj = 0; jj < 4; jj++) {
                    const int j = j0 + jj;
                    const float4 x = xb[j * 128];
                    P0[jj] = pack_bf16(bf_lo(ha[j]) + bf16r(acc[4 * j] + x.x), bf_hi(ha[j]) + bf16r(acc[4 * j + 1] + x.y));
                    P1[jj] = pack_bf16(bf_lo(hb[j]) + bf16r(acc[4 * j + 2] + x.z), bf_hi(hb[j]) + bf16r(acc[4 * j + 3] + x.w));
                }
                quad_transpose(P0[0], P0[1], P0[2], P0[3], t);
                quad_transpose(P1[0], P1[1], P1[2], P1[3], t);
                *reinterpret_cast<uint4*>(o0 + 8 * (j0 + t)) = make_uint4(P0[0], P0[1], P0[2], P0[3]);
                *reinterpret_cast<uint4*>(o0 + 8 * D_ + 8 * (j0 + t)) = make_uint4(P1[0], P1[1], P1[2], P1[3]);
            }
        }
        TM(3, 5);
    }
#undef TMT
}

typedef CUresult (*EncodeFn)(CUtensorMap*, CUtensorMapDataType, cuuint32_t, void*, const cuuint64_t*, const cuuint64_t*,
                             const cuuint32_t*, const cuuint32_t*, CUtensorMapInterleave, CUtensorMapSwizzle,
                             CUtensorMapL2promotion, CUtensorMapFloatOOBfill);

static void enc2d(EncodeFn enc, CUtensorMap* m, const void* p, int rows, int cols, int brows, int bcols) {
    cuuint64_t dims[2] = {(cuuint64_t)cols, (cuuint64_t)rows};
    cuuint64_t strides[1] = {(cuuint64_t)cols * 2};
    cuuint32_t box[2] = {(cuuint32_t)bcols, (cuuint32_t)brows};
    cuuint32_t es[2] = {1, 1};
    enc(m, CU_TENSOR_MAP_DATA_TYPE_BFLOAT16, 2, const_cast<void*>(p), dims, strides, box, es, CU_TENSOR_MAP_INTERLEAVE_NONE,
        bcols == 32 ? CU_TENSOR_MAP_SWIZZLE_64B : CU_TENSOR_MAP_SWIZZLE_128B, CU_TENSOR_MAP_L2_PROMOTION_L2_128B, CU_TENSOR_MAP_FLOAT_OOB_FILL_NONE);
}
static void enc3d(EncodeFn enc, CUtensorMap* m, const void* p, int rows, int cols, int atom, int brows, int natoms) {
    cuuint64_t dims[3] = {(cuuint64_t)atom, (cuuint64_t)rows, (cuuint64_t)(cols / atom)};
    cuuint64_t strides[2] = {(cuuint64_t)cols * 2, (cuuint64_t)atom * 2};
    cuuint32_t box[3] = {(cuuint32_t)atom, (cuuint32_t)brows, (cuuint32_t)natoms};
    cuuint32_t es[3] = {1, 1, 1};
    enc(m, CU_TENSOR_MAP_DATA_TYPE_BFLOAT16, 3, const_cast<void*>(p), dims, strides, box, es, CU_TENSOR_MAP_INTERLEAVE_NONE,
        atom == 32 ? CU_TENSOR_MAP_SWIZZLE_64B : CU_TENSOR_MAP_SWIZZLE_128B, CU_TENSOR_MAP_L2_PROMOTION_L2_128B, CU_TENSOR_MAP_FLOAT_OOB_FILL_NONE);
}

extern "C" void kernel_launch(void* const* d_in, const int* in_sizes, int n_in, void* d_out, int out_size) {
    const bf16* q = (const bf16*)d_in[0];
    const bf16* k = (const bf16*)d_in[1];
    const bf16* v = (const bf16*)d_in[2];
    const bf16* shift_k = (const bf16*)d_in[3];
    const bf16* ssm_k = (const bf16*)d_in[4];
    const bf16* ssm_D = (const bf16*)d_in[5];
    const bf16* wg = (const bf16*)d_in[7];
    const bf16* wu = (const bf16*)d_in[8];
    const bf16* wd = (const bf16*)d_in[9];
    bf16* out = (bf16*)d_out;

    static EncodeFn enc = nullptr;
    static void *p_hn = nullptr, *p_hh = nullptr;
    if (!enc) {
        void* fn = nullptr; cudaDriverEntryPointQueryResult qr;
        cudaGetDriverEntryPoint("cuTensorMapEncodeTiled", &fn, cudaEnableDefault, &qr);
        enc = (EncodeFn)fn;
        cudaGetSymbolAddress(&p_hn, g_hn);
        cudaGetSymbolAddress(&p_hh, g_hh);
        cudaFuncSetAttribute(conv_kernel, cudaFuncAttributeMaxDynamicSharedMemorySize, (int)sizeof(K1Smem));
        cudaFuncSetAttribute(gemm1_kernel, cudaFuncAttributeMaxDynamicSharedMemorySize, G1_SMEM);
        cudaFuncSetAttribute(gemm2_kernel, cudaFuncAttributeMaxDynamicSharedMemorySize, G2_SMEM);
    }
    CUtensorMap mA, mG64, mU64, mG32, mU32, mHH, mWd;
    enc2d(enc, &mA, p_hn, S_, D_, 128, 64);
    enc3d(enc, &mG64, wg, D_, F_, 32, 64, 4);
    enc3d(enc, &mU64, wu, D_, F_, 32, 64, 4);
    enc3d(enc, &mG32, wg, D_, F_, 32, 64, 3);
    enc3d(enc, &mU32, wu, D_, F_, 32, 64, 3);
    enc2d(enc, &mHH, p_hh, S_, F_, 128, 64);
    enc3d(enc, &mWd, wd, F_, D_, 64, 64, 2);

    cudaStream_t st = cudaStreamPerThread;
    cudaLaunchAttribute at[1];
    at[0].id = cudaLaunchAttributeProgrammaticStreamSerialization;
    at[0].val.programmaticStreamSerializationAllowed = 1;
    cudaLaunchConfig_t cfg = {};
    cfg.stream = st; cfg.attrs = at; cfg.numAttrs = 1;
    conv_kernel<<<128, K1_THREADS, sizeof(K1Smem), st>>>(q, k, v, shift_k, ssm_k, ssm_D);
    cfg.gridDim = dim3(128); cfg.blockDim = dim3(G1_THREADS); cfg.dynamicSmemBytes = G1_SMEM;
    cudaLaunchKernelEx(&cfg, gemm1_kernel, mA, mG64, mU64, mG32, mU32, q);
    cfg.gridDim = dim3(128); cfg.blockDim = dim3(G2_THREADS); cfg.dynamicSmemBytes = G2_SMEM;
    cudaLaunchKernelEx(&cfg, gemm2_kernel, mHH, mWd, out);
}
```

```cpp
#include <cuda_runtime.h>
#include <cuda_bf16.h>
#include <cuda.h>
#include <stdint.h>

typedef __nv_bfloat16 bf16;
constexpr int S_ = 2048, D_ = 512, F_ = 1792;

__device__ bf16 g_yT[D_ * S_];
__device__ bf16 g_h[S_ * D_];
__device__ bf16 g_hn[S_ * D_];
__device__ bf16 g_hh[S_ * F_];
__device__ float2 g_st1[S_];
__device__ unsigned int g_cnt[16];

#define TM(k, i)
#define TR(k, i)
__device__ __forceinline__ uint32_t smem_u32(const void* p) { return (uint32_t)__cvta_generic_to_shared(p); }
__device__ __forceinline__ float bf16r(float x) { return __bfloat162float(__float2bfloat16_rn(x)); }
__device__ __forceinline__ float bf_lo(uint32_t w) { return __uint_as_float(w << 16); }
__device__ __forceinline__ float bf_hi(uint32_t w) { return __uint_as_float(w & 0xffff0000u); }
__device__ __forceinline__ uint32_t pack_bf16(float lo, float hi) {
    __nv_bfloat162 v = __floats2bfloat162_rn(lo, hi);
    return *reinterpret_cast<uint32_t*>(&v);
}
__device__ __forceinline__ uint32_t hmul2(uint32_t a, uint32_t b) {
    __nv_bfloat162 r = __hmul2_rn(*reinterpret_cast<__nv_bfloat162*>(&a), *reinterpret_cast<__nv_bfloat162*>(&b));
    return *reinterpret_cast<uint32_t*>(&r);
}
__device__ __forceinline__ uint32_t hadd2(uint32_t a, uint32_t b) {
    __nv_bfloat162 r = __hadd2_rn(*reinterpret_cast<__nv_bfloat162*>(&a), *reinterpret_cast<__nv_bfloat162*>(&b));
    return *reinterpret_cast<uint32_t*>(&r);
}
__device__ __forceinline__ uint4 ldg128(const void* p) {
    uint4 r; asm volatile("ld.global.nc.v4.u32 {%0,%1,%2,%3}, [%4];" : "=r"(r.x), "=r"(r.y), "=r"(r.z), "=r"(r.w) : "l"(p)); return r;
}
__device__ __forceinline__ uint4 ldcg128(const void* p) {
    uint4 r; asm volatile("ld.global.cg.v4.u32 {%0,%1,%2,%3}, [%4];" : "=r"(r.x), "=r"(r.y), "=r"(r.z), "=r"(r.w) : "l"(p)); return r;
}
__device__ __forceinline__ uint32_t ldg16(const void* p) {
    unsigned short r; asm volatile("ld.global.nc.u16 %0, [%1];" : "=h"(r) : "l"(p)); return (uint32_t)r;
}
__device__ __forceinline__ void mbar_init(uint32_t bar, int cnt) { asm volatile("mbarrier.init.shared::cta.b64 [%0], %1;" :: "r"(bar), "r"(cnt)); }
__device__ __forceinline__ void mbar_expect_tx(uint32_t bar, uint32_t bytes) { asm volatile("mbarrier.arrive.expect_tx.shared::cta.b64 _, [%0], %1;" :: "r"(bar), "r"(bytes) : "memory"); }
__device__ __forceinline__ void mbar_arrive(uint32_t bar) { asm volatile("mbarrier.arrive.shared::cta.b64 _, [%0];" :: "r"(bar) : "memory"); }
__device__ __forceinline__ void mbar_arrive_cluster(uint32_t bar, uint32_t cta) {
    asm volatile("{\n.reg .b32 ra;\nmapa.shared::cluster.u32 ra, %0, %1;\nmbarrier.arrive.shared::cluster.b64 _, [ra];\n}" :: "r"(bar), "r"(cta) : "memory");
}
__device__ __forceinline__ void mbar_wait(uint32_t bar, uint32_t parity) {
    asm volatile("{\n.reg .pred P1;\nLAB_WAIT:\nmbarrier.try_wait.parity.shared::cta.b64 P1, [%0], %1;\n@P1 bra DONE;\nbra LAB_WAIT;\nDONE:\n}" :: "r"(bar), "r"(parity) : "memory");
}
__device__ __forceinline__ void mbar_wait_cluster(uint32_t bar, uint32_t parity) {
    asm volatile("{\n.reg .pred P1;\nLAB_WAIT:\nmbarrier.try_wait.parity.acquire.cluster.shared::cta.b64 P1, [%0], %1;\n@P1 bra DONE;\nbra LAB_WAIT;\nDONE:\n}" :: "r"(bar), "r"(parity) : "memory");
}
__device__ __forceinline__ void tma_load_2d(uint32_t dst, const CUtensorMap* map, uint32_t bar, int c0, int c1) {
    asm volatile("cp.async.bulk.tensor.2d.shared::cluster.global.mbarrier::complete_tx::bytes [%0], [%1, {%3, %4}], [%2];"
        :: "r"(dst), "l"(map), "r"(bar), "r"(c0), "r"(c1) : "memory");
}
__device__ __forceinline__ void tma_load_2d_mc(uint32_t dst, const CUtensorMap* map, uint32_t bar, int c0, int c1, uint16_t mask) {
    asm volatile("cp.async.bulk.tensor.2d.shared::cluster.global.mbarrier::complete_tx::bytes.multicast::cluster [%0], [%1, {%3, %4}], [%2], %5;"
        :: "r"(dst), "l"(map), "r"(bar), "r"(c0), "r"(c1), "h"(mask) : "memory");
}
__device__ __forceinline__ void tma_load_3d(uint32_t dst, const CUtensorMap* map, uint32_t bar, int c0, int c1, int c2) {
    asm volatile("cp.async.bulk.tensor.3d.shared::cluster.global.mbarrier::complete_tx::bytes [%0], [%1, {%3, %4, %5}], [%2];"
        :: "r"(dst), "l"(map), "r"(bar), "r"(c0), "r"(c1), "r"(c2) : "memory");
}
__device__ __forceinline__ void cluster_arrive() { asm volatile("barrier.cluster.arrive.aligned;" ::: "memory"); }
__device__ __forceinline__ void cluster_arrive_relaxed() { asm volatile("barrier.cluster.arrive.relaxed.aligned;" ::: "memory"); }
__device__ __forceinline__ void cluster_wait() { asm volatile("barrier.cluster.wait.aligned;" ::: "memory"); }
__device__ __forceinline__ uint32_t mapa(uint32_t addr, uint32_t cta) {
    uint32_t r; asm volatile("mapa.shared::cluster.u32 %0, %1, %2;" : "=r"(r) : "r"(addr), "r"(cta)); return r;
}
__device__ __forceinline__ void st_async_v2(uint32_t addr, uint32_t a, uint32_t b, uint32_t rbar) {
    asm volatile("st.async.weak.shared::cluster.mbarrier::complete_tx::bytes.v2.b32 [%0], {%1, %2}, [%3];" :: "r"(addr), "r"(a), "r"(b), "r"(rbar) : "memory");
}
__device__ __forceinline__ void st_async_v4f(uint32_t addr, float a, float b, float c, float d, uint32_t rbar) {
    asm volatile("st.async.weak.shared::cluster.mbarrier::complete_tx::bytes.v4.f32 [%0], {%1, %2, %3, %4}, [%5];" :: "r"(addr), "f"(a), "f"(b), "f"(c), "f"(d), "r"(rbar) : "memory");
}
__device__ __forceinline__ void wgmma_fence() { asm volatile("wgmma.fence.sync.aligned;" ::: "memory"); }
__device__ __forceinline__ void wgmma_commit() { asm volatile("wgmma.commit_group.sync.aligned;" ::: "memory"); }
template <int N> __device__ __forceinline__ void wgmma_wait() { asm volatile("wgmma.wait_group.sync.aligned %0;" :: "n"(N) : "memory"); }
__device__ __forceinline__ uint64_t make_desc(uint32_t addr, uint32_t lbo_bytes, uint32_t sbo_bytes, uint32_t layout) {
    return (uint64_t)((addr & 0x3FFFF) >> 4) | ((uint64_t)(lbo_bytes >> 4) << 16) | ((uint64_t)(sbo_bytes >> 4) << 32) | ((uint64_t)layout << 62);
}
template <int R> __device__ __forceinline__ void reg_alloc() { asm volatile("setmaxnreg.inc.sync.aligned.u32 %0;" :: "n"(R)); }
template <int R> __device__ __forceinline__ void reg_dealloc() { asm volatile("setmaxnreg.dec.sync.aligned.u32 %0;" :: "n"(R)); }
__device__ __forceinline__ void pdl_launch() { asm volatile("griddepcontrol.launch_dependents;" ::: "memory"); }
__device__ __forceinline__ void pdl_wait() { asm volatile("griddepcontrol.wait;" ::: "memory"); }
__device__ __forceinline__ void prefetch_map(const CUtensorMap* m) { asm volatile("prefetch.tensormap [%0];" :: "l"(m) : "memory"); }
__device__ __forceinline__ void named_bar(int id, int n) { asm volatile("bar.sync %0, %1;" :: "r"(id), "r"(n) : "memory"); }

__device__ __forceinline__ void wgmma_m64n256k16_ss(float (&d)[128], uint64_t descA, uint64_t descB, int scaleD) {
    asm volatile("{\n.reg .pred p;\nsetp.ne.b32 p, %130, 0;\n"
        "wgmma.mma_async.sync.aligned.m64n256k16.f32.bf16.bf16 {%0, %1, %2, %3, %4, %5, %6, %7, %8, %9, %10, %11, %12, %13, %14, %15, %16, %17, %18, %19, %20, %21, %22, %23, %24, %25, %26, %27, %28, %29, %30, %31, %32, %33, %34, %35, %36, %37, %38, %39, %40, %41, %42, %43, %44, %45, %46, %47, %48, %49, %50, %51, %52, %53, %54, %55, %56, %57, %58, %59, %60, %61, %62, %63, %64, %65, %66, %67, %68, %69, %70, %71, %72, %73, %74, %75, %76, %77, %78, %79, %80, %81, %82, %83, %84, %85, %86, %87, %88, %89, %90, %91, %92, %93, %94, %95, %96, %97, %98, %99, %100, %101, %102, %103, %104, %105, %106, %107, %108, %109, %110, %111, %112, %113, %114, %115, %116, %117, %118, %119, %120, %121, %122, %123, %124, %125, %126, %127}, %128, %129, p, 1, 1, 0, 1;\n}\n"
        : "+f"(d[0]), "+f"(d[1]), "+f"(d[2]), "+f"(d[3]), "+f"(d[4]), "+f"(d[5]), "+f"(d[6]), "+f"(d[7]), "+f"(d[8]), "+f"(d[9]), "+f"(d[10]), "+f"(d[11]), "+f"(d[12]), "+f"(d[13]), "+f"(d[14]), "+f"(d[15]), "+f"(d[16]), "+f"(d[17]), "+f"(d[18]), "+f"(d[19]), "+f"(d[20]), "+f"(d[21]), "+f"(d[22]), "+f"(d[23]), "+f"(d[24]), "+f"(d[25]), "+f"(d[26]), "+f"(d[27]), "+f"(d[28]), "+f"(d[29]), "+f"(d[30]), "+f"(d[31]), "+f"(d[32]), "+f"(d[33]), "+f"(d[34]), "+f"(d[35]), "+f"(d[36]), "+f"(d[37]), "+f"(d[38]), "+f"(d[39]), "+f"(d[40]), "+f"(d[41]), "+f"(d[42]), "+f"(d[43]), "+f"(d[44]), "+f"(d[45]), "+f"(d[46]), "+f"(d[47]), "+f"(d[48]), "+f"(d[49]), "+f"(d[50]), "+f"(d[51]), "+f"(d[52]), "+f"(d[53]), "+f"(d[54]), "+f"(d[55]), "+f"(d[56]), "+f"(d[57]), "+f"(d[58]), "+f"(d[59]), "+f"(d[60]), "+f"(d[61]), "+f"(d[62]), "+f"(d[63]), "+f"(d[64]), "+f"(d[65]), "+f"(d[66]), "+f"(d[67]), "+f"(d[68]), "+f"(d[69]), "+f"(d[70]), "+f"(d[71]), "+f"(d[72]), "+f"(d[73]), "+f"(d[74]), "+f"(d[75]), "+f"(d[76]), "+f"(d[77]), "+f"(d[78]), "+f"(d[79]), "+f"(d[80]), "+f"(d[81]), "+f"(d[82]), "+f"(d[83]), "+f"(d[84]), "+f"(d[85]), "+f"(d[86]), "+f"(d[87]), "+f"(d[88]), "+f"(d[89]), "+f"(d[90]), "+f"(d[91]), "+f"(d[92]), "+f"(d[93]), "+f"(d[94]), "+f"(d[95]), "+f"(d[96]), "+f"(d[97]), "+f"(d[98]), "+f"(d[99]), "+f"(d[100]), "+f"(d[101]), "+f"(d[102]), "+f"(d[103]), "+f"(d[104]), "+f"(d[105]), "+f"(d[106]), "+f"(d[107]), "+f"(d[108]), "+f"(d[109]), "+f"(d[110]), "+f"(d[111]), "+f"(d[112]), "+f"(d[113]), "+f"(d[114]), "+f"(d[115]), "+f"(d[116]), "+f"(d[117]), "+f"(d[118]), "+f"(d[119]), "+f"(d[120]), "+f"(d[121]), "+f"(d[122]), "+f"(d[123]), "+f"(d[124]), "+f"(d[125]), "+f"(d[126]), "+f"(d[127])
        : "l"(descA), "l"(descB), "r"(scaleD));
}

__device__ __forceinline__ void wgmma_m64n192k16_ss(float (&d)[96], uint64_t descA, uint64_t descB, int scaleD) {
    asm volatile("{\n.reg .pred p;\nsetp.ne.b32 p, %98, 0;\n"
        "wgmma.mma_async.sync.aligned.m64n192k16.f32.bf16.bf16 {%0, %1, %2, %3, %4, %5, %6, %7, %8, %9, %10, %11, %12, %13, %14, %15, %16, %17, %18, %19, %20, %21, %22, %23, %24, %25, %26, %27, %28, %29, %30, %31, %32, %33, %34, %35, %36, %37, %38, %39, %40, %41, %42, %43, %44, %45, %46, %47, %48, %49, %50, %51, %52, %53, %54, %55, %56, %57, %58, %59, %60, %61, %62, %63, %64, %65, %66, %67, %68, %69, %70, %71, %72, %73, %74, %75, %76, %77, %78, %79, %80, %81, %82, %83, %84, %85, %86, %87, %88, %89, %90, %91, %92, %93, %94, %95}, %96, %97, p, 1, 1, 0, 1;\n}\n"
        : "+f"(d[0]), "+f"(d[1]), "+f"(d[2]), "+f"(d[3]), "+f"(d[4]), "+f"(d[5]), "+f"(d[6]), "+f"(d[7]), "+f"(d[8]), "+f"(d[9]), "+f"(d[10]), "+f"(d[11]), "+f"(d[12]), "+f"(d[13]), "+f"(d[14]), "+f"(d[15]), "+f"(d[16]), "+f"(d[17]), "+f"(d[18]), "+f"(d[19]), "+f"(d[20]), "+f"(d[21]), "+f"(d[22]), "+f"(d[23]), "+f"(d[24]), "+f"(d[25]), "+f"(d[26]), "+f"(d[27]), "+f"(d[28]), "+f"(d[29]), "+f"(d[30]), "+f"(d[31]), "+f"(d[32]), "+f"(d[33]), "+f"(d[34]), "+f"(d[35]), "+f"(d[36]), "+f"(d[37]), "+f"(d[38]), "+f"(d[39]), "+f"(d[40]), "+f"(d[41]), "+f"(d[42]), "+f"(d[43]), "+f"(d[44]), "+f"(d[45]), "+f"(d[46]), "+f"(d[47]), "+f"(d[48]), "+f"(d[49]), "+f"(d[50]), "+f"(d[51]), "+f"(d[52]), "+f"(d[53]), "+f"(d[54]), "+f"(d[55]), "+f"(d[56]), "+f"(d[57]), "+f"(d[58]), "+f"(d[59]), "+f"(d[60]), "+f"(d[61]), "+f"(d[62]), "+f"(d[63]), "+f"(d[64]), "+f"(d[65]), "+f"(d[66]), "+f"(d[67]), "+f"(d[68]), "+f"(d[69]), "+f"(d[70]), "+f"(d[71]), "+f"(d[72]), "+f"(d[73]), "+f"(d[74]), "+f"(d[75]), "+f"(d[76]), "+f"(d[77]), "+f"(d[78]), "+f"(d[79]), "+f"(d[80]), "+f"(d[81]), "+f"(d[82]), "+f"(d[83]), "+f"(d[84]), "+f"(d[85]), "+f"(d[86]), "+f"(d[87]), "+f"(d[88]), "+f"(d[89]), "+f"(d[90]), "+f"(d[91]), "+f"(d[92]), "+f"(d[93]), "+f"(d[94]), "+f"(d[95])
        : "l"(descA), "l"(descB), "r"(scaleD));
}

__device__ __forceinline__ void wgmma_m64n128k16_ss(float (&d)[64], uint64_t descA, uint64_t descB, int scaleD) {
    asm volatile("{\n.reg .pred p;\nsetp.ne.b32 p, %66, 0;\n"
        "wgmma.mma_async.sync.aligned.m64n128k16.f32.bf16.bf16 {%0, %1, %2, %3, %4, %5, %6, %7, %8, %9, %10, %11, %12, %13, %14, %15, %16, %17, %18, %19, %20, %21, %22, %23, %24, %25, %26, %27, %28, %29, %30, %31, %32, %33, %34, %35, %36, %37, %38, %39, %40, %41, %42, %43, %44, %45, %46, %47, %48, %49, %50, %51, %52, %53, %54, %55, %56, %57, %58, %59, %60, %61, %62, %63}, %64, %65, p, 1, 1, 0, 1;\n}\n"
        : "+f"(d[0]), "+f"(d[1]), "+f"(d[2]), "+f"(d[3]), "+f"(d[4]), "+f"(d[5]), "+f"(d[6]), "+f"(d[7]), "+f"(d[8]), "+f"(d[9]), "+f"(d[10]), "+f"(d[11]), "+f"(d[12]), "+f"(d[13]), "+f"(d[14]), "+f"(d[15]), "+f"(d[16]), "+f"(d[17]), "+f"(d[18]), "+f"(d[19]), "+f"(d[20]), "+f"(d[21]), "+f"(d[22]), "+f"(d[23]), "+f"(d[24]), "+f"(d[25]), "+f"(d[26]), "+f"(d[27]), "+f"(d[28]), "+f"(d[29]), "+f"(d[30]), "+f"(d[31]), "+f"(d[32]), "+f"(d[33]), "+f"(d[34]), "+f"(d[35]), "+f"(d[36]), "+f"(d[37]), "+f"(d[38]), "+f"(d[39]), "+f"(d[40]), "+f"(d[41]), "+f"(d[42]), "+f"(d[43]), "+f"(d[44]), "+f"(d[45]), "+f"(d[46]), "+f"(d[47]), "+f"(d[48]), "+f"(d[49]), "+f"(d[50]), "+f"(d[51]), "+f"(d[52]), "+f"(d[53]), "+f"(d[54]), "+f"(d[55]), "+f"(d[56]), "+f"(d[57]), "+f"(d[58]), "+f"(d[59]), "+f"(d[60]), "+f"(d[61]), "+f"(d[62]), "+f"(d[63])
        : "l"(descA), "l"(descB), "r"(scaleD));
}

__device__ __forceinline__ void quad_transpose(uint32_t& r0, uint32_t& r1, uint32_t& r2, uint32_t& r3, int t) {
    const bool o1 = t & 1, o2 = t & 2;
    uint32_t x, y;
    x = o1 ? r0 : r1; y = __shfl_xor_sync(0xffffffffu, x, 1); if (o1) r0 = y; else r1 = y;
    x = o1 ? r2 : r3; y = __shfl_xor_sync(0xffffffffu, x, 1); if (o1) r2 = y; else r3 = y;
    x = o2 ? r0 : r2; y = __shfl_xor_sync(0xffffffffu, x, 2); if (o2) r0 = y; else r2 = y;
    x = o2 ? r1 : r3; y = __shfl_xor_sync(0xffffffffu, x, 2); if (o2) r1 = y; else r3 = y;
}

__device__ __forceinline__ float warp_sum(float s) {
#pragma unroll
    for (int o = 16; o > 0; o >>= 1) s += __shfl_xor_sync(0xffffffffu, s, o);
    return s;
}
__device__ __forceinline__ uint32_t hsub2(uint32_t a, uint32_t b) {
    __nv_bfloat162 r = __hsub2_rn(*reinterpret_cast<__nv_bfloat162*>(&a), *reinterpret_cast<__nv_bfloat162*>(&b));
    return *reinterpret_cast<uint32_t*>(&r);
}
__device__ __forceinline__ void ln_stats2(const uint32_t (&x)[2][8], float2 (&st)[2]) {
    float piv[2], s[2], ss[2];
#pragma unroll
    for (int r = 0; r < 2; r++) piv[r] = __shfl_sync(0xffffffffu, bf_lo(x[r][0]), 0);
#pragma unroll
    for (int r = 0; r < 2; r++) {
        float s0 = 0.f, s1 = 0.f, q0 = 0.f, q1 = 0.f;
#pragma unroll
        for (int i = 0; i < 8; i++) {
            const float d0 = bf_lo(x[r][i]) - piv[r], d1 = bf_hi(x[r][i]) - piv[r];
            s0 += d0; s1 += d1; q0 = fmaf(d0, d0, q0); q1 = fmaf(d1, d1, q1);
        }
        s[r] = s0 + s1; ss[r] = q0 + q1;
    }
#pragma unroll
    for (int o = 16; o > 0; o >>= 1) {
#pragma unroll
        for (int r = 0; r < 2; r++) { s[r] += __shfl_xor_sync(0xffffffffu, s[r], o); ss[r] += __shfl_xor_sync(0xffffffffu, ss[r], o); }
    }
#pragma unroll
    for (int r = 0; r < 2; r++) {
        const float md = s[r] * (1.0f / D_);
        const float var = bf16r(fmaxf(fmaf(-md, md, ss[r] * (1.0f / D_)), 0.f));
        st[r] = make_float2(bf16r(piv[r] + md), 1.0f / bf16r(sqrtf(bf16r(var + 1e-5f))));
    }
}
__device__ __forceinline__ void ln_apply(const uint32_t (&x)[8], float2 st, uint32_t (&o)[8]) {
    const uint32_t m2 = pack_bf16(st.x, st.x);
#pragma unroll
    for (int i = 0; i < 8; i++) {
        const uint32_t d = hsub2(x[i], m2);
        o[i] = pack_bf16(bf_lo(d) * st.y, bf_hi(d) * st.y);
    }
}

constexpr int K1_THREADS = 256;
constexpr int UT_PAD = 128;
constexpr int UT_LEN = UT_PAD + S_;
constexpr int KR_LEN = 2080;
constexpr int YP_LEN = S_ + (S_ / 32) * 8;

struct __align__(128) K1Smem {
    bf16 uT[4][UT_LEN];
    bf16 kr[4][2][KR_LEN];
    float yP[4][YP_LEN];
    uint64_t bar;
    uint8_t pad[32768];
};

__device__ __forceinline__ void mma16816(float (&c)[4], uint32_t a0, uint32_t a1, uint32_t a2, uint32_t a3, uint32_t b0, uint32_t b1) {
    asm("mma.sync.aligned.m16n8k16.row.col.f32.bf16.bf16.f32 {%0,%1,%2,%3}, {%4,%5,%6,%7}, {%8,%9}, {%0,%1,%2,%3};"
        : "+f"(c[0]), "+f"(c[1]), "+f"(c[2]), "+f"(c[3])
        : "r"(a0), "r"(a1), "r"(a2), "r"(a3), "r"(b0), "r"(b1));
}
__device__ __forceinline__ void ldsm_x4(uint32_t& r0, uint32_t& r1, uint32_t& r2, uint32_t& r3, uint32_t addr) {
    asm volatile("ldmatrix.sync.aligned.m8n8.x4.shared.b16 {%0,%1,%2,%3}, [%4];" : "=r"(r0), "=r"(r1), "=r"(r2), "=r"(r3) : "r"(addr) : "memory");
}

__device__ __forceinline__ void conv_mma(const bf16* uTc, const bf16* krlane, float (&acc)[16][4], int lane, int half) {
    const int lrow = lane & 7, lk = (lane >> 3) & 1, lt = lane >> 4;
    const uint32_t ubase = smem_u32(uTc) + (UT_PAD + 16 * (8 * lt + lrow) + 8 * lk) * 2;
#pragma unroll 1
    for (int pp = 0; pp < 4; pp++) {
        const int p = half * 4 + pp;
        uint32_t U[16][2];
#pragma unroll
        for (int j = 0; j < 16; j += 2) ldsm_x4(U[j][0], U[j][1], U[j + 1][0], U[j + 1][1], ubase + (j * 128 - p * 16) * 2);
        const uint32_t* kp = reinterpret_cast<const uint32_t*>(krlane - 16 * p);
        const volatile uint32_t* kpv = kp;
        uint32_t a0 = kp[0], a1 = kp[-4], a2 = kp[4], a3 = kpv[0];
#pragma unroll
        for (int q = 0; q < 16; q++) {
            uint32_t b0 = 0, b1 = 0, b2 = 0, b3 = 0;
            if (q < 15) { b0 = kp[-64 * (q + 1)]; b1 = kp[-64 * (q + 1) - 4]; b2 = kp[-64 * (q + 1) + 4]; b3 = kpv[-64 * (q + 1)]; }
#pragma unroll
            for (int n = 15; n >= q; n--) mma16816(acc[n], a0, a1, a2, a3, U[n - q][0], U[n - q][1]);
            a0 = b0; a1 = b1; a2 = b2; a3 = b3;
        }
    }
}

__global__ void __cluster_dims__(2, 1, 1) __launch_bounds__(K1_THREADS, 1)
conv_kernel(const bf16* __restrict__ q, const bf16* __restrict__ k, const bf16* __restrict__ v,
            const bf16* __restrict__ shift_k, const bf16* __restrict__ ssm_k, const bf16* __restrict__ ssm_D) {
    extern __shared__ __align__(1024) uint8_t smem_raw[];
    pdl_launch();
    K1Smem& sm = *reinterpret_cast<K1Smem*>(smem_raw);
    const int tid = threadIdx.x, lane = tid & 31, warp = tid >> 5;
    const int bid = blockIdx.x;
    const int rank = bid & 1;
    const int c0 = 8 * (bid >> 1);
    const int cown = c0 + 4 * rank;
#define TMT 0
    TM(0, 0);
    const uint32_t bar = smem_u32(&sm.bar);
    if (tid == 0) {
        mbar_init(bar, 1);
        asm volatile("fence.mbarrier_init.release.cluster;" ::: "memory");
        mbar_expect_tx(bar, 1024 * 4 * 2);
    }
    cluster_arrive_relaxed();

    const int s0 = 1024 * rank + 4 * tid;
    uint4 kk[7], vv[4], sw[4];
#pragma unroll
    for (int i = 0; i < 4; i++) kk[3 + i] = ldg128(k + (size_t)(s0 + i) * D_ + c0);
#pragma unroll
    for (int i = 0; i < 4; i++) vv[i] = ldg128(v + (size_t)(s0 + i) * D_ + c0);
    if (lane == 0) {
#pragma unroll
        for (int i = 0; i < 3; i++) {
            const int s = s0 - 3 + i;
            kk[i] = make_uint4(0, 0, 0, 0);
            if (s >= 0) kk[i] = ldg128(k + (size_t)s * D_ + c0);
        }
    }
#pragma unroll
    for (int i = 0; i < 4; i++) sw[i] = ldg128(shift_k + (size_t)c0 * 4 + 8 * i);
    uint4 kq[4]; uint32_t nx[4];
#pragma unroll
    for (int c = 0; c < 4; c++) {
        const bf16* kr = ssm_k + (size_t)(cown + c) * S_;
        kq[c] = ldg128(kr + 8 * tid);
        nx[c] = 0u;
        if (tid < 255) nx[c] = ldg16(kr + 8 * tid + 8);
    }
    const uint32_t dval = ldg16(ssm_D + cown + (warp >> 1));
    uint32_t xq[2][8];
#pragma unroll
    for (int r = 0; r < 2; r++) {
        const uint4 qa = ldg128(q + (size_t)(16 * bid + 2 * warp + r) * D_ + 8 * lane);
        const uint4 qb = ldg128(q + (size_t)(16 * bid + 2 * warp + r) * D_ + 8 * (lane + 32));
        xq[r][0] = qa.x; xq[r][1] = qa.y; xq[r][2] = qa.z; xq[r][3] = qa.w; xq[r][4] = qb.x; xq[r][5] = qb.y; xq[r][6] = qb.z; xq[r][7] = qb.w;
    }
    if (tid < 64) *reinterpret_cast<uint4*>(&sm.uT[tid >> 4][(tid & 15) * 8]) = make_uint4(0, 0, 0, 0);
#pragma unroll
    for (int i = 0; i < 3; i++) {
        uint4 t;
        t.x = __shfl_up_sync(0xffffffffu, kk[4 + i].x, 1); t.y = __shfl_up_sync(0xffffffffu, kk[4 + i].y, 1);
        t.z = __shfl_up_sync(0xffffffffu, kk[4 + i].z, 1); t.w = __shfl_up_sync(0xffffffffu, kk[4 + i].w, 1);
        if (lane != 0) kk[i] = t;
    }
    uint32_t kvw[4][4];
    const uint32_t* kkw = reinterpret_cast<const uint32_t*>(kk);
    const uint32_t* vvw = reinterpret_cast<const uint32_t*>(vv);
#pragma unroll
    for (int i2 = 0; i2 < 4; i2++) {
        const uint32_t t0 = __byte_perm(sw[i2].x, sw[i2].z, 0x5410), t1 = __byte_perm(sw[i2].x, sw[i2].z, 0x7632);
        const uint32_t t2 = __byte_perm(sw[i2].y, sw[i2].w, 0x5410), t3 = __byte_perm(sw[i2].y, sw[i2].w, 0x7632);
#pragma unroll
        for (int r = 0; r < 4; r++) {
            uint32_t a = hmul2(kkw[(r + 0) * 4 + i2], t3);
            a = hadd2(a, hmul2(kkw[(r + 1) * 4 + i2], t2));
            a = hadd2(a, hmul2(kkw[(r + 2) * 4 + i2], t1));
            a = hadd2(a, hmul2(kkw[(r + 3) * 4 + i2], t0));
            kvw[r][i2] = hmul2(a, vvw[r * 4 + i2]);
        }
    }
    TM(0, 1);
    cluster_wait();
    {
        const uint32_t rbar = mapa(bar, (uint32_t)(rank ^ 1));
#pragma unroll
        for (int i2 = 0; i2 < 4; i2++) {
#pragma unroll
            for (int e = 0; e < 2; e++) {
                const uint32_t sel = e ? 0x7632 : 0x5410;
                const uint32_t w0 = __byte_perm(kvw[0][i2], kvw[1][i2], sel), w1 = __byte_perm(kvw[2][i2], kvw[3][i2], sel);
                const int cc = 2 * i2 + e;
                if ((cc >> 2) == rank) {
                    *reinterpret_cast<uint2*>(&sm.uT[cc & 3][UT_PAD + s0]) = make_uint2(w0, w1);
                } else {
                    st_async_v2(mapa(smem_u32(&sm.uT[cc & 3][UT_PAD + s0]), (uint32_t)(rank ^ 1)), w0, w1, rbar);
                }
            }
        }
    }
#pragma unroll
    for (int c = 0; c < 4; c++) {
        uint4 a, b;
        a.x = __byte_perm(kq[c].w, 0, 0x1032); a.y = __byte_perm(kq[c].z, 0, 0x1032);
        a.z = __byte_perm(kq[c].y, 0, 0x1032); a.w = __byte_perm(kq[c].x, 0, 0x1032);
        b.x = __byte_perm(nx[c], kq[c].w, 0x7610); b.y = __byte_perm(kq[c].w, kq[c].z, 0x7610);
        b.z = __byte_perm(kq[c].z, kq[c].y, 0x7610); b.w = __byte_perm(kq[c].y, kq[c].x, 0x7610);
        *reinterpret_cast<uint4*>(&sm.kr[c][0][2040 - 8 * tid]) = a;
        *reinterpret_cast<uint4*>(&sm.kr[c][1][2040 - 8 * tid]) = b;
        if (tid == 0) {
            *reinterpret_cast<uint4*>(&sm.kr[c][1][2048]) = make_uint4(kq[c].x & 0xffffu, 0, 0, 0);
        } else if (tid < 8) {
            if (tid < 4) *reinterpret_cast<uint4*>(&sm.kr[c][1][2048 + 8 * tid]) = make_uint4(0, 0, 0, 0);
            else *reinterpret_cast<uint4*>(&sm.kr[c][0][2048 + 8 * (tid - 4)]) = make_uint4(0, 0, 0, 0);
        }
    }
    {
        float2 st[2];
        ln_stats2(xq, st);
        if (lane < 2) g_st1[16 * bid + 2 * warp + lane] = lane ? st[1] : st[0];
    }
    TM(0, 3);
    __syncthreads();
    mbar_wait_cluster(bar, 0);
    TM(0, 4);

    const int ch = warp >> 1, half = warp & 1;
    const int g = lane >> 2, t = lane & 3;
    float acc[16][4];
#pragma unroll
    for (int i = 0; i < 16; i++) { acc[i][0] = acc[i][1] = acc[i][2] = acc[i][3] = 0.f; }
    const bf16* krlane = (g & 1) ? &sm.kr[ch][0][2047 - g + 2 * t] : &sm.kr[ch][1][2048 - g + 2 * t];
    conv_mma(sm.uT[ch], krlane, acc, lane, half);
    TM(0, 5);
    float* yp = &sm.yP[ch][40 * t + g];
    if (half) {
#pragma unroll
        for (int n = 0; n < 16; n++) {
            yp[160 * n] = acc[n][0];
            yp[160 * n + 16] = acc[n][1];
            yp[160 * n + 8] = acc[n][2];
            yp[160 * n + 24] = acc[n][3];
        }
    }
    named_bar(1 + ch, 64);
    if (!half) {
#pragma unroll
        for (int n = 0; n < 16; n++) {
            yp[160 * n] += acc[n][0];
            yp[160 * n + 16] += acc[n][1];
            yp[160 * n + 8] += acc[n][2];
            yp[160 * n + 24] += acc[n][3];
        }
    }
    named_bar(1 + ch, 64);
    TM(0, 6);
    {
        const int tt = tid & 63;
        bf16* dst = g_yT + (size_t)(cown + ch) * S_;
        const uint32_t d2 = dval * 0x10001u;
#pragma unroll
        for (int j = 0; j < 4; j++) {
            const int s = (j * 64 + tt) * 8;
            const float* src = &sm.yP[ch][s + (s >> 5) * 8];
            const float4 a = *reinterpret_cast<const float4*>(src), b = *reinterpret_cast<const float4*>(src + 4);
            const uint4 kv4 = *reinterpret_cast<const uint4*>(&sm.uT[ch][UT_PAD + s]);
            *reinterpret_cast<uint4*>(dst + s) = make_uint4(hadd2(pack_bf16(a.x, a.y), hmul2(kv4.x, d2)), hadd2(pack_bf16(a.z, a.w), hmul2(kv4.y, d2)),
                                                            hadd2(pack_bf16(b.x, b.y), hmul2(kv4.z, d2)), hadd2(pack_bf16(b.z, b.w), hmul2(kv4.w, d2)));
        }
    }
    TM(0, 7);
#undef TMT
}

constexpr int G1_THREADS = 384;
constexpr int G1_STAGES = 3;
constexpr int G1_A_BYTES = 8 * 16384;
constexpr int G1_B_STAGE = 32768;
constexpr int G1_OFF_B = G1_A_BYTES;
constexpr int G1_OFF_BAR = G1_OFF_B + G1_STAGES * G1_B_STAGE;
constexpr int G1_SMEM = G1_OFF_BAR + 256;

__device__ __forceinline__ float sigmoid_fast(float x) {
    float t; asm("tanh.approx.f32 %0, %1;" : "=f"(t) : "f"(0.5f * x));
    return fmaf(t, 0.5f, 0.5f);
}

template <int NT>
__device__ __forceinline__ void g1_epilogue(const float (&acc)[NT * 8], bf16* out0, int t) {
#pragma unroll
    for (int j0 = 0; j0 < NT; j0 += 4) {
        uint32_t P0[4], P1[4];
#pragma unroll
        for (int jj = 0; jj < 4; jj++) {
            const int j = j0 + jj;
            float r[4];
#pragma unroll
            for (int e = 0; e < 4; e++) r[e] = sigmoid_fast(acc[4 * j + e]) * acc[4 * (NT + j) + e];
            P0[jj] = pack_bf16(r[0], r[1]);
            P1[jj] = pack_bf16(r[2], r[3]);
        }
        quad_transpose(P0[0], P0[1], P0[2], P0[3], t);
        quad_transpose(P1[0], P1[1], P1[2], P1[3], t);
        *reinterpret_cast<uint4*>(out0 + 8 * (j0 + t)) = make_uint4(P0[0], P0[1], P0[2], P0[3]);
        *reinterpret_cast<uint4*>(out0 + 8 * F_ + 8 * (j0 + t)) = make_uint4(P1[0], P1[1], P1[2], P1[3]);
    }
}

__global__ void __cluster_dims__(2, 1, 1) __launch_bounds__(G1_THREADS, 1)
gemm1_kernel(const __grid_constant__ CUtensorMap mapA, const __grid_constant__ CUtensorMap mapG4, const __grid_constant__ CUtensorMap mapU4,
             const __grid_constant__ CUtensorMap mapG3, const __grid_constant__ CUtensorMap mapU3, const bf16* __restrict__ q) {
    extern __shared__ __align__(1024) uint8_t smem_raw[];
    const uint32_t sb = smem_u32(smem_raw);
    const int tid = threadIdx.x, lane = tid & 31, warp = tid >> 5, wgi = tid >> 7;
    const int rank = blockIdx.x & 1;
    const int cb = blockIdx.x & 7, rb = blockIdx.x >> 3;
#define TMT 128
    TM(2, 0);
    pdl_launch();
    if (tid == 32) { prefetch_map(&mapA); prefetch_map(&mapG4); prefetch_map(&mapU4); prefetch_map(&mapG3); prefetch_map(&mapU3); }
    const uint32_t barA = sb + G1_OFF_BAR;
    const uint32_t barF = barA + 64;
    const uint32_t barE = barF + 8 * G1_STAGES;
    if (tid == 0) {
        for (int i = 0; i < 8; i++) mbar_init(barA + 8 * i, 1);
        for (int i = 0; i < G1_STAGES; i++) { mbar_init(barF + 8 * i, 1); mbar_init(barE + 8 * i, 2); }
        for (int i = 0; i < 8; i++) mbar_expect_tx(barA + 8 * i, 16384);
        asm volatile("fence.mbarrier_init.release.cluster;" ::: "memory");
    }
    __syncthreads();
    cluster_arrive_relaxed();
    cluster_wait();

    if (wgi == 0) {
        reg_dealloc<40>();
        if (warp == 0) named_bar(1, 288);
        if (lane == 0 && warp == 0) {
            int st = 0, ph = 1;
            for (int it = 0; it < 16; it++) {
                const int kc = it & 7;
                mbar_wait(barE + 8 * st, ph);
                const uint32_t dst = sb + G1_OFF_B + st * G1_B_STAGE;
                if (it < 8) {
                    mbar_expect_tx(barF + 8 * st, 32768);
                    tma_load_3d(dst, &mapG4, barF + 8 * st, 0, kc * 64, cb * 7);
                    tma_load_3d(dst + 16384, &mapU4, barF + 8 * st, 0, kc * 64, cb * 7);
                } else {
                    mbar_expect_tx(barF + 8 * st, 24576);
                    tma_load_3d(dst, &mapG3, barF + 8 * st, 0, kc * 64, cb * 7 + 4);
                    tma_load_3d(dst + 12288, &mapU3, barF + 8 * st, 0, kc * 64, cb * 7 + 4);
                }
                if (++st == G1_STAGES) { st = 0; ph ^= 1; }
            }
        } else if (warp == 1) {
            unsigned int c; int spins = 0;
            do { asm volatile("ld.acquire.gpu.global.u32 %0, [%1];" : "=r"(c) : "l"(&g_cnt[rb]) : "memory"); } while (c < 8u && ++spins < (1 << 22));
            if (lane < 4) {
                asm volatile("fence.proxy.async;" ::: "memory");
                if (lane == 0) TR(0, 0);
                const int c = 2 * lane + rank;
                tma_load_2d_mc(sb + c * 16384, &mapA, barA + 8 * c, c * 64, rb * 128, (uint16_t)3);
            }
        }
        __syncwarp();
    } else {
        const int cw = wgi - 1;
        const int g = lane >> 2, t = lane & 3, wl = warp & 3, tl = tid & 127;
        {
            uint32_t (*ys)[D_ / 2 + 4] = reinterpret_cast<uint32_t (*)[D_ / 2 + 4]>(smem_raw);
            const int s0 = rb * 128 + cb * 16;
            const int cwp = warp - 4, p = tid - 128;
            uint32_t x[2][8];
#pragma unroll
            for (int r = 0; r < 2; r++) {
                const uint4 qa = ldg128(q + (size_t)(s0 + 2 * cwp + r) * D_ + 8 * lane);
                const uint4 qb = ldg128(q + (size_t)(s0 + 2 * cwp + r) * D_ + 8 * (lane + 32));
                x[r][0] = qa.x; x[r][1] = qa.y; x[r][2] = qa.z; x[r][3] = qa.w; x[r][4] = qb.x; x[r][5] = qb.y; x[r][6] = qb.z; x[r][7] = qb.w;
            }
            pdl_wait();
            TM(1, 0);
            const uint4 stw = ldcg128(&g_st1[s0 + 2 * cwp]);
            {
                const bf16* y0 = g_yT + (size_t)(2 * p) * S_ + s0;
                const uint4 a0 = ldcg128(y0), a1 = ldcg128(y0 + 8), b0 = ldcg128(y0 + S_), b1 = ldcg128(y0 + S_ + 8);
                const uint32_t aw[8] = {a0.x, a0.y, a0.z, a0.w, a1.x, a1.y, a1.z, a1.w};
                const uint32_t bw[8] = {b0.x, b0.y, b0.z, b0.w, b1.x, b1.y, b1.z, b1.w};
#pragma unroll
                for (int j = 0; j < 8; j++) {
                    ys[2 * j][p] = __byte_perm(aw[j], bw[j], 0x5410);
                    ys[2 * j + 1][p] = __byte_perm(aw[j], bw[j], 0x7632);
                }
            }
            uint32_t qn[2][8];
            ln_apply(x[0], make_float2(__uint_as_float(stw.x), __uint_as_float(stw.y)), qn[0]);
            ln_apply(x[1], make_float2(__uint_as_float(stw.z), __uint_as_float(stw.w)), qn[1]);
            named_bar(1, 288);
            TM(1, 1);
            uint32_t h[2][8], hn[2][8];
#pragma unroll
            for (int r = 0; r < 2; r++) {
#pragma unroll
                for (int i = 0; i < 2; i++) {
                    const uint4 yw4 = *reinterpret_cast<const uint4*>(&ys[2 * cwp + r][4 * (lane + 32 * i)]);
                    const uint32_t yw[4] = {yw4.x, yw4.y, yw4.z, yw4.w};
#pragma unroll
                    for (int j = 0; j < 4; j++) h[r][4 * i + j] = hadd2(x[r][4 * i + j], hmul2(qn[r][4 * i + j], yw[j]));
                }
            }
            float2 st2[2];
            ln_stats2(h, st2);
#pragma unroll
            for (int r = 0; r < 2; r++) {
                ln_apply(h[r], st2[r], hn[r]);
#pragma unroll
                for (int i = 0; i < 2; i++) {
                    const size_t off = (size_t)(s0 + 2 * cwp + r) * D_ + 8 * (lane + 32 * i);
                    *reinterpret_cast<uint4*>(g_hn + off) = make_uint4(hn[r][4 * i], hn[r][4 * i + 1], hn[r][4 * i + 2], hn[r][4 * i + 3]);
                }
            }
            named_bar(2, 256);
            if (p == 0) { __threadfence(); atomicAdd(&g_cnt[rb], 1u); }
#pragma unroll
            for (int r = 0; r < 2; r++) {
#pragma unroll
                for (int i = 0; i < 2; i++) {
                    const size_t off = (size_t)(s0 + 2 * cwp + r) * D_ + 8 * (lane + 32 * i);
                    *reinterpret_cast<uint4*>(g_h + off) = make_uint4(h[r][4 * i], h[r][4 * i + 1], h[r][4 * i + 2], h[r][4 * i + 3]);
                }
            }
            TM(1, 2);
        }
        reg_alloc<232>();
        bf16* outp = g_hh + (size_t)(rb * 128 + cw * 64 + wl * 16 + g) * F_ + cb * 224;
        int st = 0, ph = 0;
        {
            float acc[128];
#pragma unroll 1
            for (int kc = 0; kc < 8; kc++) {
                mbar_wait(barA + 8 * kc, 0);
                mbar_wait(barF + 8 * st, ph);
                if (tl == 0 && cw == 0) TR(1, kc);
                wgmma_fence();
                const uint32_t aaddr = sb + kc * 16384 + cw * 8192;
                const uint32_t baddr = sb + G1_OFF_B + st * G1_B_STAGE;
#pragma unroll
                for (int kk = 0; kk < 4; kk++)
                    wgmma_m64n256k16_ss(acc, make_desc(aaddr + kk * 32, 16, 1024, 1), make_desc(baddr + kk * 1024, 4096, 512, 2), (kc | kk) != 0);
                wgmma_commit();
                wgmma_wait<0>();
                if (tl == 0) mbar_arrive(barE + 8 * st);
                if (++st == G1_STAGES) { st = 0; ph ^= 1; }
            }
            TM(2, 1);
            g1_epilogue<16>(acc, outp, t);
            TM(2, 2);
        }
        {
            float acc[96];
#pragma unroll 1
            for (int kc = 0; kc < 8; kc++) {
                mbar_wait(barF + 8 * st, ph);
                if (tl == 0 && cw == 0) TR(1, 8 + kc);
                wgmma_fence();
                const uint32_t aaddr = sb + kc * 16384 + cw * 8192;
                const uint32_t baddr = sb + G1_OFF_B + st * G1_B_STAGE;
#pragma unroll
                for (int kk = 0; kk < 4; kk++)
                    wgmma_m64n192k16_ss(acc, make_desc(aaddr + kk * 32, 16, 1024, 1), make_desc(baddr + kk * 1024, 4096, 512, 2), (kc | kk) != 0);
                wgmma_commit();
                wgmma_wait<0>();
                if (tl == 0) mbar_arrive(barE + 8 * st);
                if (++st == G1_STAGES) { st = 0; ph ^= 1; }
            }
            TM(2, 3);
            g1_epilogue<12>(acc, outp + 128, t);
            TM(2, 4);
        }
    }
}

constexpr int G2_THREADS = 384;
constexpr int G2_STAGES = 6;
constexpr int G2_STAGE = 32768;
constexpr int G2_OFF_X = G2_STAGES * G2_STAGE;
constexpr int G2_OFF_BAR = G2_OFF_X + 32768;
constexpr int G2_SMEM = G2_OFF_BAR + 128;
constexpr int G2_KSTEPS = 14;

__global__ void __cluster_dims__(2, 1, 1) __launch_bounds__(G2_THREADS, 1)
gemm2_kernel(const __grid_constant__ CUtensorMap mapHH, const __grid_constant__ CUtensorMap mapWd, bf16* __restrict__ out) {
    extern __shared__ __align__(1024) uint8_t smem_raw[];
    const uint32_t sb = smem_u32(smem_raw);
    const int tid = threadIdx.x, lane = tid & 31, warp = tid >> 5, wgi = tid >> 7;
    const int ks = blockIdx.x & 1, nb = (blockIdx.x >> 1) & 3, rb = blockIdx.x >> 3;
    TM(3, 0);
    if (tid == 32) { prefetch_map(&mapHH); }
    const uint32_t barF = sb + G2_OFF_BAR;
    const uint32_t barE = barF + 8 * G2_STAGES;
    const uint32_t barX = barE + 8 * G2_STAGES;
    if (tid == 0) {
        for (int i = 0; i < G2_STAGES; i++) { mbar_init(barF + 8 * i, 1); mbar_init(barE + 8 * i, 2); }
        mbar_init(barX, 1);
        asm volatile("fence.mbarrier_init.release.cluster;" ::: "memory");
        mbar_expect_tx(barX, 32768);
        for (int it = 0; it < G2_STAGES; it++) {
            mbar_expect_tx(barF + 8 * it, 32768);
            tma_load_3d(sb + it * G2_STAGE + 16384, &mapWd, barF + 8 * it, 0, ks * 896 + it * 64, nb * 2);
        }
    }
    __syncthreads();
    cluster_arrive_relaxed();

    if (wgi == 0) {
        if (tid == 0) {
            pdl_wait();
            for (int it = 0; it < G2_STAGES; it++)
                tma_load_2d(sb + it * G2_STAGE, &mapHH, barF + 8 * it, ks * 896 + it * 64, rb * 128);
            int st = 0, ph = 0;
            for (int it = G2_STAGES; it < G2_KSTEPS; it++) {
                mbar_wait(barE + 8 * st, ph);
                const uint32_t dst = sb + st * G2_STAGE;
                const int k0 = ks * 896 + it * 64;
                mbar_expect_tx(barF + 8 * st, 32768);
                tma_load_2d(dst, &mapHH, barF + 8 * st, k0, rb * 128);
                tma_load_3d(dst + 16384, &mapWd, barF + 8 * st, 0, k0, nb * 2);
                if (++st == G2_STAGES) { st = 0; ph ^= 1; }
            }
        }
        __syncwarp();
        cluster_wait();
    } else {
        const int cw = wgi - 1;
        const int g = lane >> 2, t = lane & 3, wl = warp & 3;
        const int tl = tid & 127;
        int st = 0, ph = 0;
        float acc[64];
        pdl_wait();
        if (blockIdx.x == 0 && tid >= 128 && tid < 144) g_cnt[tid - 128] = 0u;
#pragma unroll 1
        for (int it = 0; it < G2_KSTEPS; it++) {
            mbar_wait(barF + 8 * st, ph);
            if (it == 0) TM(3, 1);
            wgmma_fence();
            const uint32_t aaddr = sb + st * G2_STAGE + cw * 8192;
            const uint32_t baddr = sb + st * G2_STAGE + 16384;
#pragma unroll
            for (int kk = 0; kk < 4; kk++)
                wgmma_m64n128k16_ss(acc, make_desc(aaddr + kk * 32, 16, 1024, 1), make_desc(baddr + kk * 2048, 8192, 1024, 1), (it | kk) != 0);
            wgmma_commit();
            wgmma_wait<0>();
            if (tl == 0) mbar_arrive(barE + 8 * st);
            if (++st == G2_STAGES) { st = 0; ph ^= 1; }
        }
        TM(3, 2);
        cluster_wait();
        if (cw != ks) {
            const uint32_t dst = mapa(sb + G2_OFF_X + tl * 16, (uint32_t)(ks ^ 1));
            const uint32_t rbar = mapa(barX, (uint32_t)(ks ^ 1));
#pragma unroll
            for (int i = 0; i < 16; i++) st_async_v4f(dst + i * 2048, acc[4 * i], acc[4 * i + 1], acc[4 * i + 2], acc[4 * i + 3], rbar);
        } else {
            const float4* xb = reinterpret_cast<const float4*>(smem_raw + G2_OFF_X) + tl;
            const int row0 = rb * 128 + cw * 64 + wl * 16 + g;
            const bf16* h0 = g_h + (size_t)row0 * D_ + nb * 128;
            bf16* o0 = out + (size_t)row0 * D_ + nb * 128;
            uint32_t ha[16], hb[16];
#pragma unroll
            for (int j = 0; j < 16; j++) {
                ha[j] = __ldcg(reinterpret_cast<const uint32_t*>(h0 + 8 * j + 2 * t));
                hb[j] = __ldcg(reinterpret_cast<const uint32_t*>(h0 + 8 * D_ + 8 * j + 2 * t));
            }
            mbar_wait_cluster(barX, 0);
            TM(3, 4);
#pragma unroll
            for (int j0 = 0; j0 < 16; j0 += 4) {
                uint32_t P0[4], P1[4];
#pragma unroll
                for (int jj = 0; jj < 4; jj++) {
                    const int j = j0 + jj;
                    const float4 x = xb[j * 128];
                    P0[jj] = pack_bf16(bf_lo(ha[j]) + bf16r(acc[4 * j] + x.x), bf_hi(ha[j]) + bf16r(acc[4 * j + 1] + x.y));
                    P1[jj] = pack_bf16(bf_lo(hb[j]) + bf16r(acc[4 * j + 2] + x.z), bf_hi(hb[j]) + bf16r(acc[4 * j + 3] + x.w));
                }
                quad_transpose(P0[0], P0[1], P0[2], P0[3], t);
                quad_transpose(P1[0], P1[1], P1[2], P1[3], t);
                *reinterpret_cast<uint4*>(o0 + 8 * (j0 + t)) = make_uint4(P0[0], P0[1], P0[2], P0[3]);
                *reinterpret_cast<uint4*>(o0 + 8 * D_ + 8 * (j0 + t)) = make_uint4(P1[0], P1[1], P1[2], P1[3]);
            }
        }
        TM(3, 5);
    }
#undef TMT
}

typedef CUresult (*EncodeFn)(CUtensorMap*, CUtensorMapDataType, cuuint32_t, void*, const cuuint64_t*, const cuuint64_t*,
                             const cuuint32_t*, const cuuint32_t*, CUtensorMapInterleave, CUtensorMapSwizzle,
                             CUtensorMapL2promotion, CUtensorMapFloatOOBfill);

static void enc2d(EncodeFn enc, CUtensorMap* m, const void* p, int rows, int cols, int brows, int bcols) {
    cuuint64_t dims[2] = {(cuuint64_t)cols, (cuuint64_t)rows};
    cuuint64_t strides[1] = {(cuuint64_t)cols * 2};
    cuuint32_t box[2] = {(cuuint32_t)bcols, (cuuint32_t)brows};
    cuuint32_t es[2] = {1, 1};
    enc(m, CU_TENSOR_MAP_DATA_TYPE_BFLOAT16, 2, const_cast<void*>(p), dims, strides, box, es, CU_TENSOR_MAP_INTERLEAVE_NONE,
        bcols == 32 ? CU_TENSOR_MAP_SWIZZLE_64B : CU_TENSOR_MAP_SWIZZLE_128B, CU_TENSOR_MAP_L2_PROMOTION_L2_128B, CU_TENSOR_MAP_FLOAT_OOB_FILL_NONE);
}
static void enc3d(EncodeFn enc, CUtensorMap* m, const void* p, int rows, int cols, int atom, int brows, int natoms) {
    cuuint64_t dims[3] = {(cuuint64_t)atom, (cuuint64_t)rows, (cuuint64_t)(cols / atom)};
    cuuint64_t strides[2] = {(cuuint64_t)cols * 2, (cuuint64_t)atom * 2};
    cuuint32_t box[3] = {(cuuint32_t)atom, (cuuint32_t)brows, (cuuint32_t)natoms};
    cuuint32_t es[3] = {1, 1, 1};
    enc(m, CU_TENSOR_MAP_DATA_TYPE_BFLOAT16, 3, const_cast<void*>(p), dims, strides, box, es, CU_TENSOR_MAP_INTERLEAVE_NONE,
        atom == 32 ? CU_TENSOR_MAP_SWIZZLE_64B : CU_TENSOR_MAP_SWIZZLE_128B, CU_TENSOR_MAP_L2_PROMOTION_L2_128B, CU_TENSOR_MAP_FLOAT_OOB_FILL_NONE);
}

extern "C" void kernel_launch(void* const* d_in, const int* in_sizes, int n_in, void* d_out, int out_size) {
    const bf16* q = (const bf16*)d_in[0];
    const bf16* k = (const bf16*)d_in[1];
    const bf16* v = (const bf16*)d_in[2];
    const bf16* shift_k = (const bf16*)d_in[3];
    const bf16* ssm_k = (const bf16*)d_in[4];
    const bf16* ssm_D = (const bf16*)d_in[5];
    const bf16* wg = (const bf16*)d_in[7];
    const bf16* wu = (const bf16*)d_in[8];
    const bf16* wd = (const bf16*)d_in[9];
    bf16* out = (bf16*)d_out;

    static EncodeFn enc = nullptr;
    static void *p_hn = nullptr, *p_hh = nullptr;
    if (!enc) {
        void* fn = nullptr; cudaDriverEntryPointQueryResult qr;
        cudaGetDriverEntryPoint("cuTensorMapEncodeTiled", &fn, cudaEnableDefault, &qr);
        enc = (EncodeFn)fn;
        cudaGetSymbolAddress(&p_hn, g_hn);
        cudaGetSymbolAddress(&p_hh, g_hh);
        cudaFuncSetAttribute(conv_kernel, cudaFuncAttributeMaxDynamicSharedMemorySize, (int)sizeof(K1Smem));
        cudaFuncSetAttribute(gemm1_kernel, cudaFuncAttributeMaxDynamicSharedMemorySize, G1_SMEM);
        cudaFuncSetAttribute(gemm2_kernel, cudaFuncAttributeMaxDynamicSharedMemorySize, G2_SMEM);
    }
    CUtensorMap mA, mG64, mU64, mG32, mU32, mHH, mWd;
    enc2d(enc, &mA, p_hn, S_, D_, 128, 64);
    enc3d(enc, &mG64, wg, D_, F_, 32, 64, 4);
    enc3d(enc, &mU64, wu, D_, F_, 32, 64, 4);
    enc3d(enc, &mG32, wg, D_, F_, 32, 64, 3);
    enc3d(enc, &mU32, wu, D_, F_, 32, 64, 3);
    enc2d(enc, &mHH, p_hh, S_, F_, 128, 64);
    enc3d(enc, &mWd, wd, F_, D_, 64, 64, 2);

    cudaStream_t st = cudaStreamPerThread;
    cudaLaunchAttribute at[1];
    at[0].id = cudaLaunchAttributeProgrammaticStreamSerialization;
    at[0].val.programmaticStreamSerializationAllowed = 1;
    cudaLaunchConfig_t cfg = {};
    cfg.stream = st; cfg.attrs = at; cfg.numAttrs = 1;
    conv_kernel<<<128, K1_THREADS, sizeof(K1Smem), st>>>(q, k, v, shift_k, ssm_k, ssm_D);
    cfg.gridDim = dim3(128); cfg.blockDim = dim3(G1_THREADS); cfg.dynamicSmemBytes = G1_SMEM;
    cudaLaunchKernelEx(&cfg, gemm1_kernel, mA, mG64, mU64, mG32, mU32, q);
    cfg.gridDim = dim3(128); cfg.blockDim = dim3(G2_THREADS); cfg.dynamicSmemBytes = G2_SMEM;
    cudaLaunchKernelEx(&cfg, gemm2_kernel, mHH, mWd, out);
}
```

```cpp
#include <cuda_runtime.h>
#include <cuda_bf16.h>
#include <cuda.h>
#include <stdint.h>

typedef __nv_bfloat16 bf16;
constexpr int S_ = 2048, D_ = 512, F_ = 1792;

__device__ bf16 g_hT[D_ * S_];
__device__ bf16 g_hh[S_ * F_];
__device__ float2 g_st1[S_];
__device__ float g_colsum[2 * F_];
__device__ unsigned int g_cnt;

#define TM(k, i)
#define TR(k, i)
__device__ __forceinline__ uint32_t smem_u32(const void* p) { return (uint32_t)__cvta_generic_to_shared(p); }
__device__ __forceinline__ float bf16r(float x) { return __bfloat162float(__float2bfloat16_rn(x)); }
__device__ __forceinline__ float bf_lo(uint32_t w) { return __uint_as_float(w << 16); }
__device__ __forceinline__ float bf_hi(uint32_t w) { return __uint_as_float(w & 0xffff0000u); }
__device__ __forceinline__ uint32_t pack_bf16(float lo, float hi) {
    __nv_bfloat162 v = __floats2bfloat162_rn(lo, hi);
    return *reinterpret_cast<uint32_t*>(&v);
}
__device__ __forceinline__ uint32_t hmul2(uint32_t a, uint32_t b) {
    __nv_bfloat162 r = __hmul2_rn(*reinterpret_cast<__nv_bfloat162*>(&a), *reinterpret_cast<__nv_bfloat162*>(&b));
    return *reinterpret_cast<uint32_t*>(&r);
}
__device__ __forceinline__ uint32_t hadd2(uint32_t a, uint32_t b) {
    __nv_bfloat162 r = __hadd2_rn(*reinterpret_cast<__nv_bfloat162*>(&a), *reinterpret_cast<__nv_bfloat162*>(&b));
    return *reinterpret_cast<uint32_t*>(&r);
}
__device__ __forceinline__ uint4 ldg128(const void* p) {
    uint4 r; asm volatile("ld.global.nc.v4.u32 {%0,%1,%2,%3}, [%4];" : "=r"(r.x), "=r"(r.y), "=r"(r.z), "=r"(r.w) : "l"(p)); return r;
}
__device__ __forceinline__ uint4 ldcg128(const void* p) {
    uint4 r; asm volatile("ld.global.cg.v4.u32 {%0,%1,%2,%3}, [%4];" : "=r"(r.x), "=r"(r.y), "=r"(r.z), "=r"(r.w) : "l"(p)); return r;
}
__device__ __forceinline__ uint32_t ldg16(const void* p) {
    unsigned short r; asm volatile("ld.global.nc.u16 %0, [%1];" : "=h"(r) : "l"(p)); return (uint32_t)r;
}
__device__ __forceinline__ void mbar_init(uint32_t bar, int cnt) { asm volatile("mbarrier.init.shared::cta.b64 [%0], %1;" :: "r"(bar), "r"(cnt)); }
__device__ __forceinline__ void mbar_expect_tx(uint32_t bar, uint32_t bytes) { asm volatile("mbarrier.arrive.expect_tx.shared::cta.b64 _, [%0], %1;" :: "r"(bar), "r"(bytes) : "memory"); }
__device__ __forceinline__ void mbar_arrive(uint32_t bar) { asm volatile("mbarrier.arrive.shared::cta.b64 _, [%0];" :: "r"(bar) : "memory"); }
__device__ __forceinline__ void mbar_arrive_cluster(uint32_t bar, uint32_t cta) {
    asm volatile("{\n.reg .b32 ra;\nmapa.shared::cluster.u32 ra, %0, %1;\nmbarrier.arrive.shared::cluster.b64 _, [ra];\n}" :: "r"(bar), "r"(cta) : "memory");
}
__device__ __forceinline__ void mbar_wait(uint32_t bar, uint32_t parity) {
    asm volatile("{\n.reg .pred P1;\nLAB_WAIT:\nmbarrier.try_wait.parity.shared::cta.b64 P1, [%0], %1;\n@P1 bra DONE;\nbra LAB_WAIT;\nDONE:\n}" :: "r"(bar), "r"(parity) : "memory");
}
__device__ __forceinline__ void mbar_wait_cluster(uint32_t bar, uint32_t parity) {
    asm volatile("{\n.reg .pred P1;\nLAB_WAIT:\nmbarrier.try_wait.parity.acquire.cluster.shared::cta.b64 P1, [%0], %1;\n@P1 bra DONE;\nbra LAB_WAIT;\nDONE:\n}" :: "r"(bar), "r"(parity) : "memory");
}
__device__ __forceinline__ void tma_load_2d(uint32_t dst, const CUtensorMap* map, uint32_t bar, int c0, int c1) {
    asm volatile("cp.async.bulk.tensor.2d.shared::cluster.global.mbarrier::complete_tx::bytes [%0], [%1, {%3, %4}], [%2];"
        :: "r"(dst), "l"(map), "r"(bar), "r"(c0), "r"(c1) : "memory");
}
__device__ __forceinline__ void tma_load_2d_mc(uint32_t dst, const CUtensorMap* map, uint32_t bar, int c0, int c1, uint16_t mask) {
    asm volatile("cp.async.bulk.tensor.2d.shared::cluster.global.mbarrier::complete_tx::bytes.multicast::cluster [%0], [%1, {%3, %4}], [%2], %5;"
        :: "r"(dst), "l"(map), "r"(bar), "r"(c0), "r"(c1), "h"(mask) : "memory");
}
__device__ __forceinline__ void tma_load_3d(uint32_t dst, const CUtensorMap* map, uint32_t bar, int c0, int c1, int c2) {
    asm volatile("cp.async.bulk.tensor.3d.shared::cluster.global.mbarrier::complete_tx::bytes [%0], [%1, {%3, %4, %5}], [%2];"
        :: "r"(dst), "l"(map), "r"(bar), "r"(c0), "r"(c1), "r"(c2) : "memory");
}
__device__ __forceinline__ void cluster_arrive() { asm volatile("barrier.cluster.arrive.aligned;" ::: "memory"); }
__device__ __forceinline__ void cluster_arrive_relaxed() { asm volatile("barrier.cluster.arrive.relaxed.aligned;" ::: "memory"); }
__device__ __forceinline__ void cluster_wait() { asm volatile("barrier.cluster.wait.aligned;" ::: "memory"); }
__device__ __forceinline__ uint32_t mapa(uint32_t addr, uint32_t cta) {
    uint32_t r; asm volatile("mapa.shared::cluster.u32 %0, %1, %2;" : "=r"(r) : "r"(addr), "r"(cta)); return r;
}
__device__ __forceinline__ void st_async_v2(uint32_t addr, uint32_t a, uint32_t b, uint32_t rbar) {
    asm volatile("st.async.weak.shared::cluster.mbarrier::complete_tx::bytes.v2.b32 [%0], {%1, %2}, [%3];" :: "r"(addr), "r"(a), "r"(b), "r"(rbar) : "memory");
}
__device__ __forceinline__ void st_async_v4f(uint32_t addr, float a, float b, float c, float d, uint32_t rbar) {
    asm volatile("st.async.weak.shared::cluster.mbarrier::complete_tx::bytes.v4.f32 [%0], {%1, %2, %3, %4}, [%5];" :: "r"(addr), "f"(a), "f"(b), "f"(c), "f"(d), "r"(rbar) : "memory");
}
__device__ __forceinline__ void wgmma_fence() { asm volatile("wgmma.fence.sync.aligned;" ::: "memory"); }
__device__ __forceinline__ void wgmma_commit() { asm volatile("wgmma.commit_group.sync.aligned;" ::: "memory"); }
template <int N> __device__ __forceinline__ void wgmma_wait() { asm volatile("wgmma.wait_group.sync.aligned %0;" :: "n"(N) : "memory"); }
__device__ __forceinline__ uint64_t make_desc(uint32_t addr, uint32_t lbo_bytes, uint32_t sbo_bytes, uint32_t layout) {
    return (uint64_t)((addr & 0x3FFFF) >> 4) | ((uint64_t)(lbo_bytes >> 4) << 16) | ((uint64_t)(sbo_bytes >> 4) << 32) | ((uint64_t)layout << 62);
}
template <int R> __device__ __forceinline__ void reg_alloc() { asm volatile("setmaxnreg.inc.sync.aligned.u32 %0;" :: "n"(R)); }
template <int R> __device__ __forceinline__ void reg_dealloc() { asm volatile("setmaxnreg.dec.sync.aligned.u32 %0;" :: "n"(R)); }
__device__ __forceinline__ void pdl_launch() { asm volatile("griddepcontrol.launch_dependents;" ::: "memory"); }
__device__ __forceinline__ void pdl_wait() { asm volatile("griddepcontrol.wait;" ::: "memory"); }
__device__ __forceinline__ void prefetch_map(const CUtensorMap* m) { asm volatile("prefetch.tensormap [%0];" :: "l"(m) : "memory"); }
__device__ __forceinline__ void named_bar(int id, int n) { asm volatile("bar.sync %0, %1;" :: "r"(id), "r"(n) : "memory"); }

__device__ __forceinline__ void wgmma_m64n256k16_ss(float (&d)[128], uint64_t descA, uint64_t descB, int scaleD) {
    asm volatile("{\n.reg .pred p;\nsetp.ne.b32 p, %130, 0;\n"
        "wgmma.mma_async.sync.aligned.m64n256k16.f32.bf16.bf16 {%0, %1, %2, %3, %4, %5, %6, %7, %8, %9, %10, %11, %12, %13, %14, %15, %16, %17, %18, %19, %20, %21, %22, %23, %24, %25, %26, %27, %28, %29, %30, %31, %32, %33, %34, %35, %36, %37, %38, %39, %40, %41, %42, %43, %44, %45, %46, %47, %48, %49, %50, %51, %52, %53, %54, %55, %56, %57, %58, %59, %60, %61, %62, %63, %64, %65, %66, %67, %68, %69, %70, %71, %72, %73, %74, %75, %76, %77, %78, %79, %80, %81, %82, %83, %84, %85, %86, %87, %88, %89, %90, %91, %92, %93, %94, %95, %96, %97, %98, %99, %100, %101, %102, %103, %104, %105, %106, %107, %108, %109, %110, %111, %112, %113, %114, %115, %116, %117, %118, %119, %120, %121, %122, %123, %124, %125, %126, %127}, %128, %129, p, 1, 1, 1, 1;\n}\n"
        : "+f"(d[0]), "+f"(d[1]), "+f"(d[2]), "+f"(d[3]), "+f"(d[4]), "+f"(d[5]), "+f"(d[6]), "+f"(d[7]), "+f"(d[8]), "+f"(d[9]), "+f"(d[10]), "+f"(d[11]), "+f"(d[12]), "+f"(d[13]), "+f"(d[14]), "+f"(d[15]), "+f"(d[16]), "+f"(d[17]), "+f"(d[18]), "+f"(d[19]), "+f"(d[20]), "+f"(d[21]), "+f"(d[22]), "+f"(d[23]), "+f"(d[24]), "+f"(d[25]), "+f"(d[26]), "+f"(d[27]), "+f"(d[28]), "+f"(d[29]), "+f"(d[30]), "+f"(d[31]), "+f"(d[32]), "+f"(d[33]), "+f"(d[34]), "+f"(d[35]), "+f"(d[36]), "+f"(d[37]), "+f"(d[38]), "+f"(d[39]), "+f"(d[40]), "+f"(d[41]), "+f"(d[42]), "+f"(d[43]), "+f"(d[44]), "+f"(d[45]), "+f"(d[46]), "+f"(d[47]), "+f"(d[48]), "+f"(d[49]), "+f"(d[50]), "+f"(d[51]), "+f"(d[52]), "+f"(d[53]), "+f"(d[54]), "+f"(d[55]), "+f"(d[56]), "+f"(d[57]), "+f"(d[58]), "+f"(d[59]), "+f"(d[60]), "+f"(d[61]), "+f"(d[62]), "+f"(d[63]), "+f"(d[64]), "+f"(d[65]), "+f"(d[66]), "+f"(d[67]), "+f"(d[68]), "+f"(d[69]), "+f"(d[70]), "+f"(d[71]), "+f"(d[72]), "+f"(d[73]), "+f"(d[74]), "+f"(d[75]), "+f"(d[76]), "+f"(d[77]), "+f"(d[78]), "+f"(d[79]), "+f"(d[80]), "+f"(d[81]), "+f"(d[82]), "+f"(d[83]), "+f"(d[84]), "+f"(d[85]), "+f"(d[86]), "+f"(d[87]), "+f"(d[88]), "+f"(d[89]), "+f"(d[90]), "+f"(d[91]), "+f"(d[92]), "+f"(d[93]), "+f"(d[94]), "+f"(d[95]), "+f"(d[96]), "+f"(d[97]), "+f"(d[98]), "+f"(d[99]), "+f"(d[100]), "+f"(d[101]), "+f"(d[102]), "+f"(d[103]), "+f"(d[104]), "+f"(d[105]), "+f"(d[106]), "+f"(d[107]), "+f"(d[108]), "+f"(d[109]), "+f"(d[110]), "+f"(d[111]), "+f"(d[112]), "+f"(d[113]), "+f"(d[114]), "+f"(d[115]), "+f"(d[116]), "+f"(d[117]), "+f"(d[118]), "+f"(d[119]), "+f"(d[120]), "+f"(d[121]), "+f"(d[122]), "+f"(d[123]), "+f"(d[124]), "+f"(d[125]), "+f"(d[126]), "+f"(d[127])
        : "l"(descA), "l"(descB), "r"(scaleD));
}

__device__ __forceinline__ void wgmma_m64n192k16_ss(float (&d)[96], uint64_t descA, uint64_t descB, int scaleD) {
    asm volatile("{\n.reg .pred p;\nsetp.ne.b32 p, %98, 0;\n"
        "wgmma.mma_async.sync.aligned.m64n192k16.f32.bf16.bf16 {%0, %1, %2, %3, %4, %5, %6, %7, %8, %9, %10, %11, %12, %13, %14, %15, %16, %17, %18, %19, %20, %21, %22, %23, %24, %25, %26, %27, %28, %29, %30, %31, %32, %33, %34, %35, %36, %37, %38, %39, %40, %41, %42, %43, %44, %45, %46, %47, %48, %49, %50, %51, %52, %53, %54, %55, %56, %57, %58, %59, %60, %61, %62, %63, %64, %65, %66, %67, %68, %69, %70, %71, %72, %73, %74, %75, %76, %77, %78, %79, %80, %81, %82, %83, %84, %85, %86, %87, %88, %89, %90, %91, %92, %93, %94, %95}, %96, %97, p, 1, 1, 1, 1;\n}\n"
        : "+f"(d[0]), "+f"(d[1]), "+f"(d[2]), "+f"(d[3]), "+f"(d[4]), "+f"(d[5]), "+f"(d[6]), "+f"(d[7]), "+f"(d[8]), "+f"(d[9]), "+f"(d[10]), "+f"(d[11]), "+f"(d[12]), "+f"(d[13]), "+f"(d[14]), "+f"(d[15]), "+f"(d[16]), "+f"(d[17]), "+f"(d[18]), "+f"(d[19]), "+f"(d[20]), "+f"(d[21]), "+f"(d[22]), "+f"(d[23]), "+f"(d[24]), "+f"(d[25]), "+f"(d[26]), "+f"(d[27]), "+f"(d[28]), "+f"(d[29]), "+f"(d[30]), "+f"(d[31]), "+f"(d[32]), "+f"(d[33]), "+f"(d[34]), "+f"(d[35]), "+f"(d[36]), "+f"(d[37]), "+f"(d[38]), "+f"(d[39]), "+f"(d[40]), "+f"(d[41]), "+f"(d[42]), "+f"(d[43]), "+f"(d[44]), "+f"(d[45]), "+f"(d[46]), "+f"(d[47]), "+f"(d[48]), "+f"(d[49]), "+f"(d[50]), "+f"(d[51]), "+f"(d[52]), "+f"(d[53]), "+f"(d[54]), "+f"(d[55]), "+f"(d[56]), "+f"(d[57]), "+f"(d[58]), "+f"(d[59]), "+f"(d[60]), "+f"(d[61]), "+f"(d[62]), "+f"(d[63]), "+f"(d[64]), "+f"(d[65]), "+f"(d[66]), "+f"(d[67]), "+f"(d[68]), "+f"(d[69]), "+f"(d[70]), "+f"(d[71]), "+f"(d[72]), "+f"(d[73]), "+f"(d[74]), "+f"(d[75]), "+f"(d[76]), "+f"(d[77]), "+f"(d[78]), "+f"(d[79]), "+f"(d[80]), "+f"(d[81]), "+f"(d[82]), "+f"(d[83]), "+f"(d[84]), "+f"(d[85]), "+f"(d[86]), "+f"(d[87]), "+f"(d[88]), "+f"(d[89]), "+f"(d[90]), "+f"(d[91]), "+f"(d[92]), "+f"(d[93]), "+f"(d[94]), "+f"(d[95])
        : "l"(descA), "l"(descB), "r"(scaleD));
}

__device__ __forceinline__ void wgmma_m64n128k16_ss(float (&d)[64], uint64_t descA, uint64_t descB, int scaleD) {
    asm volatile("{\n.reg .pred p;\nsetp.ne.b32 p, %66, 0;\n"
        "wgmma.mma_async.sync.aligned.m64n128k16.f32.bf16.bf16 {%0, %1, %2, %3, %4, %5, %6, %7, %8, %9, %10, %11, %12, %13, %14, %15, %16, %17, %18, %19, %20, %21, %22, %23, %24, %25, %26, %27, %28, %29, %30, %31, %32, %33, %34, %35, %36, %37, %38, %39, %40, %41, %42, %43, %44, %45, %46, %47, %48, %49, %50, %51, %52, %53, %54, %55, %56, %57, %58, %59, %60, %61, %62, %63}, %64, %65, p, 1, 1, 0, 1;\n}\n"
        : "+f"(d[0]), "+f"(d[1]), "+f"(d[2]), "+f"(d[3]), "+f"(d[4]), "+f"(d[5]), "+f"(d[6]), "+f"(d[7]), "+f"(d[8]), "+f"(d[9]), "+f"(d[10]), "+f"(d[11]), "+f"(d[12]), "+f"(d[13]), "+f"(d[14]), "+f"(d[15]), "+f"(d[16]), "+f"(d[17]), "+f"(d[18]), "+f"(d[19]), "+f"(d[20]), "+f"(d[21]), "+f"(d[22]), "+f"(d[23]), "+f"(d[24]), "+f"(d[25]), "+f"(d[26]), "+f"(d[27]), "+f"(d[28]), "+f"(d[29]), "+f"(d[30]), "+f"(d[31]), "+f"(d[32]), "+f"(d[33]), "+f"(d[34]), "+f"(d[35]), "+f"(d[36]), "+f"(d[37]), "+f"(d[38]), "+f"(d[39]), "+f"(d[40]), "+f"(d[41]), "+f"(d[42]), "+f"(d[43]), "+f"(d[44]), "+f"(d[45]), "+f"(d[46]), "+f"(d[47]), "+f"(d[48]), "+f"(d[49]), "+f"(d[50]), "+f"(d[51]), "+f"(d[52]), "+f"(d[53]), "+f"(d[54]), "+f"(d[55]), "+f"(d[56]), "+f"(d[57]), "+f"(d[58]), "+f"(d[59]), "+f"(d[60]), "+f"(d[61]), "+f"(d[62]), "+f"(d[63])
        : "l"(descA), "l"(descB), "r"(scaleD));
}

__device__ __forceinline__ void quad_transpose(uint32_t& r0, uint32_t& r1, uint32_t& r2, uint32_t& r3, int t) {
    const bool o1 = t & 1, o2 = t & 2;
    uint32_t x, y;
    x = o1 ? r0 : r1; y = __shfl_xor_sync(0xffffffffu, x, 1); if (o1) r0 = y; else r1 = y;
    x = o1 ? r2 : r3; y = __shfl_xor_sync(0xffffffffu, x, 1); if (o1) r2 = y; else r3 = y;
    x = o2 ? r0 : r2; y = __shfl_xor_sync(0xffffffffu, x, 2); if (o2) r0 = y; else r2 = y;
    x = o2 ? r1 : r3; y = __shfl_xor_sync(0xffffffffu, x, 2); if (o2) r1 = y; else r3 = y;
}

__device__ __forceinline__ float warp_sum(float s) {
#pragma unroll
    for (int o = 16; o > 0; o >>= 1) s += __shfl_xor_sync(0xffffffffu, s, o);
    return s;
}
__device__ __forceinline__ uint32_t hsub2(uint32_t a, uint32_t b) {
    __nv_bfloat162 r = __hsub2_rn(*reinterpret_cast<__nv_bfloat162*>(&a), *reinterpret_cast<__nv_bfloat162*>(&b));
    return *reinterpret_cast<uint32_t*>(&r);
}
__device__ __forceinline__ void ln_stats2(const uint32_t (&x)[2][8], float2 (&st)[2]) {
    float piv[2], s[2], ss[2];
#pragma unroll
    for (int r = 0; r < 2; r++) piv[r] = __shfl_sync(0xffffffffu, bf_lo(x[r][0]), 0);
#pragma unroll
    for (int r = 0; r < 2; r++) {
        float s0 = 0.f, s1 = 0.f, q0 = 0.f, q1 = 0.f;
#pragma unroll
        for (int i = 0; i < 8; i++) {
            const float d0 = bf_lo(x[r][i]) - piv[r], d1 = bf_hi(x[r][i]) - piv[r];
            s0 += d0; s1 += d1; q0 = fmaf(d0, d0, q0); q1 = fmaf(d1, d1, q1);
        }
        s[r] = s0 + s1; ss[r] = q0 + q1;
    }
#pragma unroll
    for (int o = 16; o > 0; o >>= 1) {
#pragma unroll
        for (int r = 0; r < 2; r++) { s[r] += __shfl_xor_sync(0xffffffffu, s[r], o); ss[r] += __shfl_xor_sync(0xffffffffu, ss[r], o); }
    }
#pragma unroll
    for (int r = 0; r < 2; r++) {
        const float md = s[r] * (1.0f / D_);
        const float var = bf16r(fmaxf(fmaf(-md, md, ss[r] * (1.0f / D_)), 0.f));
        st[r] = make_float2(bf16r(piv[r] + md), 1.0f / bf16r(sqrtf(bf16r(var + 1e-5f))));
    }
}
__device__ __forceinline__ void ln_apply(const uint32_t (&x)[8], float2 st, uint32_t (&o)[8]) {
    const uint32_t m2 = pack_bf16(st.x, st.x);
#pragma unroll
    for (int i = 0; i < 8; i++) {
        const uint32_t d = hsub2(x[i], m2);
        o[i] = pack_bf16(bf_lo(d) * st.y, bf_hi(d) * st.y);
    }
}

constexpr int K1_THREADS = 288;
constexpr int UT_PAD = 128;
constexpr int UT_LEN = UT_PAD + S_;
constexpr int KR_LEN = 2080;
constexpr int YP_LEN = S_ + (S_ / 32) * 8;

struct __align__(128) K1Smem {
    bf16 uT[4][UT_LEN];
    bf16 xT[4][S_];
    bf16 kr[4][2][KR_LEN];
    float yP[4][YP_LEN];
    float2 st[S_];
    uint4 wS[512][4];
    float red[8][32];
    uint64_t bar;
};

__device__ __forceinline__ void mma16816(float (&c)[4], uint32_t a0, uint32_t a1, uint32_t a2, uint32_t a3, uint32_t b0, uint32_t b1) {
    asm("mma.sync.aligned.m16n8k16.row.col.f32.bf16.bf16.f32 {%0,%1,%2,%3}, {%4,%5,%6,%7}, {%8,%9}, {%0,%1,%2,%3};"
        : "+f"(c[0]), "+f"(c[1]), "+f"(c[2]), "+f"(c[3])
        : "r"(a0), "r"(a1), "r"(a2), "r"(a3), "r"(b0), "r"(b1));
}
__device__ __forceinline__ void ldsm_x4(uint32_t& r0, uint32_t& r1, uint32_t& r2, uint32_t& r3, uint32_t addr) {
    asm volatile("ldmatrix.sync.aligned.m8n8.x4.shared.b16 {%0,%1,%2,%3}, [%4];" : "=r"(r0), "=r"(r1), "=r"(r2), "=r"(r3) : "r"(addr) : "memory");
}

__device__ __forceinline__ void conv_mma(const bf16* uTc, const bf16* krlane, float (&acc)[16][4], int lane, int half) {
    const int lrow = lane & 7, lk = (lane >> 3) & 1, lt = lane >> 4;
    const uint32_t ubase = smem_u32(uTc) + (UT_PAD + 16 * (8 * lt + lrow) + 8 * lk) * 2;
#pragma unroll 1
    for (int pp = 0; pp < 4; pp++) {
        const int p = half * 4 + pp;
        uint32_t U[16][2];
#pragma unroll
        for (int j = 0; j < 16; j += 2) ldsm_x4(U[j][0], U[j][1], U[j + 1][0], U[j + 1][1], ubase + (j * 128 - p * 16) * 2);
        const uint32_t* kp = reinterpret_cast<const uint32_t*>(krlane - 16 * p);
        const volatile uint32_t* kpv = kp;
        uint32_t a0 = kp[0], a1 = kp[-4], a2 = kp[4], a3 = kpv[0];
#pragma unroll
        for (int q = 0; q < 16; q++) {
            uint32_t b0 = 0, b1 = 0, b2 = 0, b3 = 0;
            if (q < 15) { b0 = kp[-64 * (q + 1)]; b1 = kp[-64 * (q + 1) - 4]; b2 = kp[-64 * (q + 1) + 4]; b3 = kpv[-64 * (q + 1)]; }
#pragma unroll
            for (int n = 15; n >= q; n--) mma16816(acc[n], a0, a1, a2, a3, U[n - q][0], U[n - q][1]);
            a0 = b0; a1 = b1; a2 = b2; a3 = b3;
        }
    }
}

__device__ __forceinline__ void cp_async16(uint32_t dst, const void* src) {
    asm volatile("cp.async.cg.shared.global [%0], [%1], 16;" :: "r"(dst), "l"(src) : "memory");
}

__global__ void __cluster_dims__(2, 1, 1) __launch_bounds__(K1_THREADS, 1)
conv_kernel(const bf16* __restrict__ q, const bf16* __restrict__ k, const bf16* __restrict__ v,
            const bf16* __restrict__ shift_k, const bf16* __restrict__ ssm_k, const bf16* __restrict__ ssm_D,
            const bf16* __restrict__ wg, const bf16* __restrict__ wu, const bf16* __restrict__ wd) {
    extern __shared__ __align__(1024) uint8_t smem_raw[];
    pdl_launch();
    K1Smem& sm = *reinterpret_cast<K1Smem*>(smem_raw);
    const int tid = threadIdx.x, lane = tid & 31, warp = tid >> 5;
    const int bid = blockIdx.x;
    const int rank = bid & 1;
    const int c0 = 8 * (bid >> 1);
    const int cown = c0 + 4 * rank;
#define TMT 0
    TM(0, 0);
    const uint32_t bar = smem_u32(&sm.bar);
    if (tid == 0) {
        mbar_init(bar, 1);
        asm volatile("fence.mbarrier_init.release.cluster;" ::: "memory");
        mbar_expect_tx(bar, 2 * 1024 * 4 * 2);
    }
    cluster_arrive_relaxed();

    if (warp < 8) {
        const int s0 = 1024 * rank + 4 * tid;
        uint4 kk[7], vv[4], qq[4], sw[4];
#pragma unroll
        for (int i = 0; i < 4; i++) kk[3 + i] = ldg128(k + (size_t)(s0 + i) * D_ + c0);
#pragma unroll
        for (int i = 0; i < 4; i++) vv[i] = ldg128(v + (size_t)(s0 + i) * D_ + c0);
        if (lane == 0) {
#pragma unroll
            for (int i = 0; i < 3; i++) {
                const int s = s0 - 3 + i;
                kk[i] = make_uint4(0, 0, 0, 0);
                if (s >= 0) kk[i] = ldg128(k + (size_t)s * D_ + c0);
            }
        }
#pragma unroll
        for (int i = 0; i < 4; i++) sw[i] = ldg128(shift_k + (size_t)c0 * 4 + 8 * i);
        uint4 kq[4]; uint32_t nx[4];
#pragma unroll
        for (int c = 0; c < 4; c++) {
            const bf16* kr = ssm_k + (size_t)(cown + c) * S_;
            kq[c] = ldg128(kr + 8 * tid);
            nx[c] = 0u;
            if (tid < 255) nx[c] = ldg16(kr + 8 * tid + 8);
        }
        const uint32_t dval = ldg16(ssm_D + cown + (warp >> 1));
#pragma unroll
        for (int i = 0; i < 4; i++) qq[i] = ldg128(q + (size_t)(s0 + i) * D_ + c0);
        uint32_t xq[2][8];
#pragma unroll
        for (int r = 0; r < 2; r++) {
            const uint4 qa = ldg128(q + (size_t)(16 * bid + 2 * warp + r) * D_ + 8 * lane);
            const uint4 qb = ldg128(q + (size_t)(16 * bid + 2 * warp + r) * D_ + 8 * (lane + 32));
            xq[r][0] = qa.x; xq[r][1] = qa.y; xq[r][2] = qa.z; xq[r][3] = qa.w; xq[r][4] = qb.x; xq[r][5] = qb.y; xq[r][6] = qb.z; xq[r][7] = qb.w;
        }
        if (tid < 64) *reinterpret_cast<uint4*>(&sm.uT[tid >> 4][(tid & 15) * 8]) = make_uint4(0, 0, 0, 0);
#pragma unroll
        for (int i = 0; i < 3; i++) {
            uint4 t;
            t.x = __shfl_up_sync(0xffffffffu, kk[4 + i].x, 1); t.y = __shfl_up_sync(0xffffffffu, kk[4 + i].y, 1);
            t.z = __shfl_up_sync(0xffffffffu, kk[4 + i].z, 1); t.w = __shfl_up_sync(0xffffffffu, kk[4 + i].w, 1);
            if (lane != 0) kk[i] = t;
        }
        uint32_t kvw[4][4];
        const uint32_t* kkw = reinterpret_cast<const uint32_t*>(kk);
        const uint32_t* vvw = reinterpret_cast<const uint32_t*>(vv);
        const uint32_t* qqw = reinterpret_cast<const uint32_t*>(qq);
#pragma unroll
        for (int i2 = 0; i2 < 4; i2++) {
            const uint32_t t0 = __byte_perm(sw[i2].x, sw[i2].z, 0x5410), t1 = __byte_perm(sw[i2].x, sw[i2].z, 0x7632);
            const uint32_t t2 = __byte_perm(sw[i2].y, sw[i2].w, 0x5410), t3 = __byte_perm(sw[i2].y, sw[i2].w, 0x7632);
#pragma unroll
            for (int r = 0; r < 4; r++) {
                uint32_t a = hmul2(kkw[(r + 0) * 4 + i2], t3);
                a = hadd2(a, hmul2(kkw[(r + 1) * 4 + i2], t2));
                a = hadd2(a, hmul2(kkw[(r + 2) * 4 + i2], t1));
                a = hadd2(a, hmul2(kkw[(r + 3) * 4 + i2], t0));
                kvw[r][i2] = hmul2(a, vvw[r * 4 + i2]);
            }
        }
        TM(0, 1);
        cluster_wait();
        const uint32_t rbar = mapa(bar, (uint32_t)(rank ^ 1));
#pragma unroll
        for (int i2 = 0; i2 < 4; i2++) {
#pragma unroll
            for (int e = 0; e < 2; e++) {
                const uint32_t sel = e ? 0x7632 : 0x5410;
                const uint32_t w0 = __byte_perm(kvw[0][i2], kvw[1][i2], sel), w1 = __byte_perm(kvw[2][i2], kvw[3][i2], sel);
                const int cc = 2 * i2 + e;
                if ((cc >> 2) == rank) *reinterpret_cast<uint2*>(&sm.uT[cc & 3][UT_PAD + s0]) = make_uint2(w0, w1);
                else st_async_v2(mapa(smem_u32(&sm.uT[cc & 3][UT_PAD + s0]), (uint32_t)(rank ^ 1)), w0, w1, rbar);
            }
        }
#pragma unroll
        for (int c = 0; c < 4; c++) {
            uint4 a, b;
            a.x = __byte_perm(kq[c].w, 0, 0x1032); a.y = __byte_perm(kq[c].z, 0, 0x1032);
            a.z = __byte_perm(kq[c].y, 0, 0x1032); a.w = __byte_perm(kq[c].x, 0, 0x1032);
            b.x = __byte_perm(nx[c], kq[c].w, 0x7610); b.y = __byte_perm(kq[c].w, kq[c].z, 0x7610);
            b.z = __byte_perm(kq[c].z, kq[c].y, 0x7610); b.w = __byte_perm(kq[c].y, kq[c].x, 0x7610);
            *reinterpret_cast<uint4*>(&sm.kr[c][0][2040 - 8 * tid]) = a;
            *reinterpret_cast<uint4*>(&sm.kr[c][1][2040 - 8 * tid]) = b;
            if (tid == 0) {
                *reinterpret_cast<uint4*>(&sm.kr[c][1][2048]) = make_uint4(kq[c].x & 0xffffu, 0, 0, 0);
            } else if (tid < 8) {
                if (tid < 4) *reinterpret_cast<uint4*>(&sm.kr[c][1][2048 + 8 * tid]) = make_uint4(0, 0, 0, 0);
                else *reinterpret_cast<uint4*>(&sm.kr[c][0][2048 + 8 * (tid - 4)]) = make_uint4(0, 0, 0, 0);
            }
        }
#pragma unroll
        for (int i2 = 0; i2 < 4; i2++) {
#pragma unroll
            for (int e = 0; e < 2; e++) {
                const uint32_t sel = e ? 0x7632 : 0x5410;
                const uint32_t w0 = __byte_perm(qqw[i2], qqw[4 + i2], sel), w1 = __byte_perm(qqw[8 + i2], qqw[12 + i2], sel);
                const int cc = 2 * i2 + e;
                if ((cc >> 2) == rank) *reinterpret_cast<uint2*>(&sm.xT[cc & 3][s0]) = make_uint2(w0, w1);
                else st_async_v2(mapa(smem_u32(&sm.xT[cc & 3][s0]), (uint32_t)(rank ^ 1)), w0, w1, rbar);
            }
        }
        {
            float2 st[2];
            ln_stats2(xq, st);
            if (lane < 2) g_st1[16 * bid + 2 * warp + lane] = lane ? st[1] : st[0];
        }
        TM(0, 3);
        named_bar(6, 288);
        mbar_wait_cluster(bar, 0);
        TM(0, 4);

        const int ch = warp >> 1, half = warp & 1;
        const int g = lane >> 2, t = lane & 3;
        float acc[16][4];
#pragma unroll
        for (int i = 0; i < 16; i++) { acc[i][0] = acc[i][1] = acc[i][2] = acc[i][3] = 0.f; }
        const bf16* krlane = (g & 1) ? &sm.kr[ch][0][2047 - g + 2 * t] : &sm.kr[ch][1][2048 - g + 2 * t];
        conv_mma(sm.uT[ch], krlane, acc, lane, half);
        TM(0, 5);
        float* yp = &sm.yP[ch][40 * t + g];
        if (half) {
#pragma unroll
            for (int n = 0; n < 16; n++) {
                yp[160 * n] = acc[n][0];
                yp[160 * n + 16] = acc[n][1];
                yp[160 * n + 8] = acc[n][2];
                yp[160 * n + 24] = acc[n][3];
            }
        }
        named_bar(1 + ch, 64);
        if (!half) {
#pragma unroll
            for (int n = 0; n < 16; n++) {
                yp[160 * n] += acc[n][0];
                yp[160 * n + 16] += acc[n][1];
                yp[160 * n + 8] += acc[n][2];
                yp[160 * n + 24] += acc[n][3];
            }
        }
        named_bar(7, 288);
        TM(0, 6);
        {
            const int tt = tid & 63;
            bf16* dst = g_hT + (size_t)(cown + ch) * S_;
            const uint32_t d2 = dval * 0x10001u;
#pragma unroll
            for (int j = 0; j < 4; j++) {
                const int s = (j * 64 + tt) * 8;
                const float* src = &sm.yP[ch][s + (s >> 5) * 8];
                const float4 a = *reinterpret_cast<const float4*>(src), b = *reinterpret_cast<const float4*>(src + 4);
                const uint4 kv4 = *reinterpret_cast<const uint4*>(&sm.uT[ch][UT_PAD + s]);
                const uint4 x4 = *reinterpret_cast<const uint4*>(&sm.xT[ch][s]);
                const uint32_t y2[4] = {hadd2(pack_bf16(a.x, a.y), hmul2(kv4.x, d2)), hadd2(pack_bf16(a.z, a.w), hmul2(kv4.y, d2)),
                                        hadd2(pack_bf16(b.x, b.y), hmul2(kv4.z, d2)), hadd2(pack_bf16(b.z, b.w), hmul2(kv4.w, d2))};
                const uint32_t xw[4] = {x4.x, x4.y, x4.z, x4.w};
                uint32_t o[4];
#pragma unroll
                for (int i = 0; i < 4; i++) {
                    const float4 st = *reinterpret_cast<const float4*>(&sm.st[s + 2 * i]);
                    const uint32_t d = hsub2(xw[i], pack_bf16(st.x, st.z));
                    const uint32_t qn = pack_bf16(bf_lo(d) * st.y, bf_hi(d) * st.w);
                    o[i] = hadd2(xw[i], hmul2(qn, y2[i]));
                }
                *reinterpret_cast<uint4*>(dst + s) = make_uint4(o[0], o[1], o[2], o[3]);
            }
        }
        if (bid < 112) {
            const int cq = tid & 3, rgp = tid >> 2;
            float cs[8];
#pragma unroll
            for (int i = 0; i < 8; i++) cs[i] = 0.f;
#pragma unroll
            for (int r = 0; r < 8; r++) {
                const uint4 w = sm.wS[r * 64 + rgp][cq];
                cs[0] += bf_lo(w.x); cs[1] += bf_hi(w.x); cs[2] += bf_lo(w.y); cs[3] += bf_hi(w.y);
                cs[4] += bf_lo(w.z); cs[5] += bf_hi(w.z); cs[6] += bf_lo(w.w); cs[7] += bf_hi(w.w);
            }
#pragma unroll
            for (int i = 0; i < 8; i++) {
                cs[i] += __shfl_xor_sync(0xffffffffu, cs[i], 4);
                cs[i] += __shfl_xor_sync(0xffffffffu, cs[i], 8);
                cs[i] += __shfl_xor_sync(0xffffffffu, cs[i], 16);
            }
            if (lane < 4) {
#pragma unroll
                for (int i = 0; i < 8; i++) sm.red[warp][lane * 8 + i] = cs[i];
            }
            named_bar(5, 256);
            if (tid < 32) {
                float s = 0.f;
#pragma unroll
                for (int w = 0; w < 8; w++) s += sm.red[w][tid];
                g_colsum[32 * bid + tid] = s;
            }
        }
        TM(0, 7);
    } else {
        cluster_wait();
        named_bar(6, 288);
        if (lane == 0) { __threadfence(); atomicAdd(&g_cnt, 1u); }
        if (bid < 112) {
            const bf16* wp = (bid < 56) ? (wg + 32 * bid) : (wu + 32 * (bid - 56));
#pragma unroll 4
            for (int i = 0; i < 64; i++) {
                const int idx = i * 32 + lane;
                cp_async16(smem_u32(&sm.wS[idx >> 2][idx & 3]), wp + (size_t)(idx >> 2) * F_ + (idx & 3) * 8);
            }
        }
        if (lane == 0) asm volatile("cp.async.bulk.prefetch.L2.global [%0], %1;" :: "l"(wd + (size_t)bid * 7168), "r"(14336) : "memory");
        {
            unsigned int c; int spins = 0;
            do { asm volatile("ld.acquire.gpu.global.u32 %0, [%1];" : "=r"(c) : "l"(&g_cnt) : "memory"); } while (c < gridDim.x && ++spins < (1 << 22));
        }
#pragma unroll 4
        for (int i = 0; i < 32; i++) cp_async16(smem_u32(&sm.st[2 * (i * 32 + lane)]), &g_st1[2 * (i * 32 + lane)]);
        asm volatile("cp.async.wait_all;" ::: "memory");
        named_bar(7, 288);
    }
#undef TMT
}

constexpr int G1_THREADS = 384;
constexpr int G1_STAGES = 3;
constexpr int G1_A_BYTES = 8 * 16384;
constexpr int G1_B_STAGE = 32768;
constexpr int G1_OFF_B = G1_A_BYTES;
constexpr int G1_OFF_STATS = G1_OFF_B + G1_STAGES * G1_B_STAGE;
constexpr int G1_OFF_CS = G1_OFF_STATS + 1024;
constexpr int G1_OFF_BAR = G1_OFF_CS + 1792;
constexpr int G1_SMEM = G1_OFF_BAR + 128;

__device__ __forceinline__ float tanh_fast(float x) { float t; asm("tanh.approx.f32 %0, %1;" : "=f"(t) : "f"(x)); return t; }

template <int NT>
__device__ __forceinline__ void g1_epilogue(const float (&acc)[NT * 8], const float* cs_g, const float* cs_u, float2 st0, float2 st1, bf16* out0, int t) {
    const float r0 = st0.y, r1 = st1.y, m0 = -st0.x * st0.y, m1 = -st1.x * st1.y;
#pragma unroll
    for (int j0 = 0; j0 < NT; j0 += 4) {
        uint32_t P0[4], P1[4];
#pragma unroll
        for (int jj = 0; jj < 4; jj++) {
            const int j = j0 + jj;
            const float2 cg = *reinterpret_cast<const float2*>(cs_g + 8 * j + 2 * t);
            const float2 cu = *reinterpret_cast<const float2*>(cs_u + 8 * j + 2 * t);
            float r[4];
#pragma unroll
            for (int e = 0; e < 4; e++) {
                const float rr = (e < 2) ? r0 : r1, mm = (e < 2) ? m0 : m1;
                const float gv = fmaf(acc[4 * j + e], rr, mm * ((e & 1) ? cg.y : cg.x));
                const float uv = fmaf(acc[4 * (NT + j) + e], rr, mm * ((e & 1) ? cu.y : cu.x));
                r[e] = fmaf(tanh_fast(0.5f * gv), 0.5f, 0.5f) * uv;
            }
            P0[jj] = pack_bf16(r[0], r[1]);
            P1[jj] = pack_bf16(r[2], r[3]);
        }
        quad_transpose(P0[0], P0[1], P0[2], P0[3], t);
        quad_transpose(P1[0], P1[1], P1[2], P1[3], t);
        *reinterpret_cast<uint4*>(out0 + 8 * (j0 + t)) = make_uint4(P0[0], P0[1], P0[2], P0[3]);
        *reinterpret_cast<uint4*>(out0 + 8 * F_ + 8 * (j0 + t)) = make_uint4(P1[0], P1[1], P1[2], P1[3]);
    }
}

__global__ void __cluster_dims__(2, 1, 1) __launch_bounds__(G1_THREADS, 1)
gemm1_kernel(const __grid_constant__ CUtensorMap mapA, const __grid_constant__ CUtensorMap mapG4, const __grid_constant__ CUtensorMap mapU4,
             const __grid_constant__ CUtensorMap mapG3, const __grid_constant__ CUtensorMap mapU3) {
    extern __shared__ __align__(1024) uint8_t smem_raw[];
    const uint32_t sb = smem_u32(smem_raw);
    const int tid = threadIdx.x, lane = tid & 31, warp = tid >> 5, wgi = tid >> 7;
    const int rank = blockIdx.x & 1;
    const int cb = blockIdx.x & 7, rb = blockIdx.x >> 3;
#define TMT 128
    TM(2, 0);
    pdl_launch();
    if (tid == 32) { prefetch_map(&mapA); prefetch_map(&mapG3); prefetch_map(&mapU3); }
    const uint32_t barA = sb + G1_OFF_BAR;
    const uint32_t barF = barA + 64;
    const uint32_t barE = barF + 8 * G1_STAGES;
    const uint32_t barS = barE + 8 * G1_STAGES;
    if (tid == 0) {
        for (int i = 0; i < 8; i++) mbar_init(barA + 8 * i, 1);
        for (int i = 0; i < G1_STAGES; i++) { mbar_init(barF + 8 * i, 1); mbar_init(barE + 8 * i, 2); }
        mbar_init(barS, 3);
        for (int i = 0; i < 8; i++) mbar_expect_tx(barA + 8 * i, 16384);
        asm volatile("fence.mbarrier_init.release.cluster;" ::: "memory");
    }
    __syncthreads();
    cluster_arrive_relaxed();

    if (wgi == 0) {
        reg_dealloc<56>();
        if (warp == 0) {
            if (lane == 0) {
                int st = 0, ph = 1;
                for (int it = 0; it < 16; it++) {
                    const int kc = it & 7;
                    mbar_wait(barE + 8 * st, ph);
                    const uint32_t dst = sb + G1_OFF_B + st * G1_B_STAGE;
                    if (it < 8) {
                        mbar_expect_tx(barF + 8 * st, 32768);
                        tma_load_3d(dst, &mapG4, barF + 8 * st, 0, kc * 64, cb * 7);
                        tma_load_3d(dst + 16384, &mapU4, barF + 8 * st, 0, kc * 64, cb * 7);
                    } else {
                        mbar_expect_tx(barF + 8 * st, 24576);
                        tma_load_3d(dst, &mapG3, barF + 8 * st, 0, kc * 64, cb * 7 + 4);
                        tma_load_3d(dst + 12288, &mapU3, barF + 8 * st, 0, kc * 64, cb * 7 + 4);
                    }
                    if (++st == G1_STAGES) { st = 0; ph ^= 1; }
                }
            }
            __syncwarp();
            cluster_wait();
        } else if (warp == 1) {
            cluster_wait();
            pdl_wait();
            if (lane < 8) {
                const int c = 2 * (lane >> 1) + rank, mh = lane & 1;
                tma_load_2d_mc(sb + c * 16384 + mh * 8192, &mapA, barA + 8 * c, rb * 128 + mh * 64, c * 64, (uint16_t)3);
            }
            __syncwarp();
            float* cs = reinterpret_cast<float*>(smem_raw + G1_OFF_CS);
            for (int i = lane; i < 448; i += 32) cs[i] = __ldcg((i < 224) ? &g_colsum[cb * 224 + i] : &g_colsum[F_ + cb * 224 + (i - 224)]);
            __syncwarp();
            if (lane == 0) mbar_arrive(barS);
        } else {
            cluster_wait();
            const int mh = warp - 2;
            const uint8_t* base = smem_raw + mh * 8192 + (lane & 3) * 4;
            const int mc = lane >> 2;
            float p0 = 0.f, p1 = 0.f, s0 = 0.f, s1 = 0.f, q0 = 0.f, q1 = 0.f;
#pragma unroll 1
            for (int kc = 0; kc < 8; kc++) {
                mbar_wait(barA + 8 * kc, 0);
                if (kc == 0) { const uint32_t w = *reinterpret_cast<const uint32_t*>(base + mc * 16); p0 = bf_lo(w); p1 = bf_hi(w); }
#pragma unroll 2
                for (int k8 = 0; k8 < 8; k8++) {
#pragma unroll
                    for (int kk = 0; kk < 8; kk++) {
                        const uint32_t w = *reinterpret_cast<const uint32_t*>(base + kc * 16384 + (k8 * 8 + kk) * 128 + ((mc ^ kk) << 4));
                        const float d0 = bf_lo(w) - p0, d1 = bf_hi(w) - p1;
                        s0 += d0; s1 += d1; q0 = fmaf(d0, d0, q0); q1 = fmaf(d1, d1, q1);
                    }
                }
            }
            float4 o;
            {
                const float md = s0 * (1.0f / D_);
                const float var = bf16r(fmaxf(fmaf(-md, md, q0 * (1.0f / D_)), 0.f));
                o.x = bf16r(p0 + md); o.y = 1.0f / bf16r(sqrtf(bf16r(var + 1e-5f)));
            }
            {
                const float md = s1 * (1.0f / D_);
                const float var = bf16r(fmaxf(fmaf(-md, md, q1 * (1.0f / D_)), 0.f));
                o.z = bf16r(p1 + md); o.w = 1.0f / bf16r(sqrtf(bf16r(var + 1e-5f)));
            }
            *reinterpret_cast<float4*>(smem_raw + G1_OFF_STATS + (mh * 64 + 2 * lane) * 8) = o;
            __syncwarp();
            if (lane == 0) mbar_arrive(barS);
        }
    } else {
        reg_alloc<224>();
        cluster_wait();
        const int cw = wgi - 1;
        const int g = lane >> 2, t = lane & 3, wl = warp & 3, tl = tid & 127;
        bf16* outp = g_hh + (size_t)(rb * 128 + cw * 64 + wl * 16 + g) * F_ + cb * 224;
        const float* cs = reinterpret_cast<const float*>(smem_raw + G1_OFF_CS);
        const float2* stats = reinterpret_cast<const float2*>(smem_raw + G1_OFF_STATS);
        int st = 0, ph = 0;
        {
            float acc[128];
#pragma unroll 1
            for (int kc = 0; kc < 8; kc++) {
                mbar_wait(barA + 8 * kc, 0);
                mbar_wait(barF + 8 * st, ph);
                if (tl == 0 && cw == 0) TR(1, kc);
                wgmma_fence();
                const uint32_t aaddr = sb + kc * 16384 + cw * 8192;
                const uint32_t baddr = sb + G1_OFF_B + st * G1_B_STAGE;
#pragma unroll
                for (int kk = 0; kk < 4; kk++)
                    wgmma_m64n256k16_ss(acc, make_desc(aaddr + kk * 2048, 8192, 1024, 1), make_desc(baddr + kk * 1024, 4096, 512, 2), (kc | kk) != 0);
                wgmma_commit();
                wgmma_wait<0>();
                if (tl == 0) mbar_arrive(barE + 8 * st);
                if (++st == G1_STAGES) { st = 0; ph ^= 1; }
            }
            TM(2, 1);
            mbar_wait(barS, 0);
            pdl_wait();
            TM(2, 5);
            g1_epilogue<16>(acc, cs, cs + 224, stats[cw * 64 + wl * 16 + g], stats[cw * 64 + wl * 16 + g + 8], outp, t);
            TM(2, 2);
        }
        {
            float acc[96];
#pragma unroll 1
            for (int kc = 0; kc < 8; kc++) {
                mbar_wait(barF + 8 * st, ph);
                if (tl == 0 && cw == 0) TR(1, 8 + kc);
                wgmma_fence();
                const uint32_t aaddr = sb + kc * 16384 + cw * 8192;
                const uint32_t baddr = sb + G1_OFF_B + st * G1_B_STAGE;
#pragma unroll
                for (int kk = 0; kk < 4; kk++)
                    wgmma_m64n192k16_ss(acc, make_desc(aaddr + kk * 2048, 8192, 1024, 1), make_desc(baddr + kk * 1024, 4096, 512, 2), (kc | kk) != 0);
                wgmma_commit();
                wgmma_wait<0>();
                if (tl == 0) mbar_arrive(barE + 8 * st);
                if (++st == G1_STAGES) { st = 0; ph ^= 1; }
            }
            TM(2, 3);
            g1_epilogue<12>(acc, cs + 128, cs + 224 + 128, stats[cw * 64 + wl * 16 + g], stats[cw * 64 + wl * 16 + g + 8], outp + 128, t);
            TM(2, 4);
        }
    }
}

constexpr int G2_THREADS = 384;
constexpr int G2_STAGES = 6;
constexpr int G2_STAGE = 32768;
constexpr int G2_OFF_X = G2_STAGES * G2_STAGE;
constexpr int G2_OFF_BAR = G2_OFF_X + 32768;
constexpr int G2_SMEM = G2_OFF_BAR + 128;
constexpr int G2_KSTEPS = 14;

__device__ __forceinline__ void ldsm_x4_t(uint32_t& r0, uint32_t& r1, uint32_t& r2, uint32_t& r3, uint32_t addr) {
    asm volatile("ldmatrix.sync.aligned.m8n8.x4.trans.shared.b16 {%0,%1,%2,%3}, [%4];" : "=r"(r0), "=r"(r1), "=r"(r2), "=r"(r3) : "r"(addr) : "memory");
}

__global__ void __cluster_dims__(2, 1, 1) __launch_bounds__(G2_THREADS, 1)
gemm2_kernel(const __grid_constant__ CUtensorMap mapHH, const __grid_constant__ CUtensorMap mapWd, const __grid_constant__ CUtensorMap mapH,
             bf16* __restrict__ out) {
    extern __shared__ __align__(1024) uint8_t smem_raw[];
    const uint32_t sb = smem_u32(smem_raw);
    const int tid = threadIdx.x, lane = tid & 31, warp = tid >> 5, wgi = tid >> 7;
    const int ks = blockIdx.x & 1, nb = (blockIdx.x >> 1) & 3, rb = blockIdx.x >> 3;
    TM(3, 0);
    if (tid == 32) { prefetch_map(&mapHH); prefetch_map(&mapH); }
    const uint32_t barF = sb + G2_OFF_BAR;
    const uint32_t barE = barF + 8 * G2_STAGES;
    const uint32_t barX = barE + 8 * G2_STAGES;
    if (tid == 0) {
        for (int i = 0; i < G2_STAGES; i++) { mbar_init(barF + 8 * i, 1); mbar_init(barE + 8 * i, 2); }
        mbar_init(barX, 1);
        asm volatile("fence.mbarrier_init.release.cluster;" ::: "memory");
        mbar_expect_tx(barX, 32768);
        for (int it = 0; it < G2_STAGES; it++) {
            mbar_expect_tx(barF + 8 * it, 32768);
            tma_load_3d(sb + it * G2_STAGE + 16384, &mapWd, barF + 8 * it, 0, ks * 896 + it * 64, nb * 2);
        }
    }
    __syncthreads();
    cluster_arrive_relaxed();

    if (wgi == 0) {
        if (tid == 0) {
            pdl_wait();
            for (int it = 0; it < G2_STAGES; it++)
                tma_load_2d(sb + it * G2_STAGE, &mapHH, barF + 8 * it, ks * 896 + it * 64, rb * 128);
            if (blockIdx.x == 0) g_cnt = 0u;
            int st = 0, ph = 0;
            for (int it = G2_STAGES; it < G2_KSTEPS; it++) {
                mbar_wait(barE + 8 * st, ph);
                const uint32_t dst = sb + st * G2_STAGE;
                const int k0 = ks * 896 + it * 64;
                mbar_expect_tx(barF + 8 * st, 32768);
                tma_load_2d(dst, &mapHH, barF + 8 * st, k0, rb * 128);
                tma_load_3d(dst + 16384, &mapWd, barF + 8 * st, 0, k0, nb * 2);
                if (++st == G2_STAGES) { st = 0; ph ^= 1; }
            }
            mbar_wait(barE + 8 * st, ph);
            mbar_expect_tx(barF + 8 * st, 16384);
            tma_load_2d(sb + st * G2_STAGE, &mapH, barF + 8 * st, rb * 128 + ks * 64, nb * 128);
        }
        __syncwarp();
        cluster_wait();
    } else {
        const int cw = wgi - 1;
        const int g = lane >> 2, t = lane & 3, wl = warp & 3;
        const int tl = tid & 127;
        int st = 0, ph = 0;
        float acc[64];
#pragma unroll 1
        for (int it = 0; it < G2_KSTEPS; it++) {
            mbar_wait(barF + 8 * st, ph);
            if (it == 0) TM(3, 1);
            wgmma_fence();
            const uint32_t aaddr = sb + st * G2_STAGE + cw * 8192;
            const uint32_t baddr = sb + st * G2_STAGE + 16384;
#pragma unroll
            for (int kk = 0; kk < 4; kk++)
                wgmma_m64n128k16_ss(acc, make_desc(aaddr + kk * 32, 16, 1024, 1), make_desc(baddr + kk * 2048, 8192, 1024, 1), (it | kk) != 0);
            wgmma_commit();
            wgmma_wait<0>();
            if (tl == 0) mbar_arrive(barE + 8 * st);
            if (++st == G2_STAGES) { st = 0; ph ^= 1; }
        }
        TM(3, 2);
        cluster_wait();
        if (cw != ks) {
            const uint32_t dst = mapa(sb + G2_OFF_X + tl * 16, (uint32_t)(ks ^ 1));
            const uint32_t rbar = mapa(barX, (uint32_t)(ks ^ 1));
#pragma unroll
            for (int i = 0; i < 16; i++) st_async_v4f(dst + i * 2048, acc[4 * i], acc[4 * i + 1], acc[4 * i + 2], acc[4 * i + 3], rbar);
        } else {
            const float4* xb = reinterpret_cast<const float4*>(smem_raw + G2_OFF_X) + tl;
            const int row0 = rb * 128 + cw * 64 + wl * 16 + g;
            bf16* o0 = out + (size_t)row0 * D_ + nb * 128;
            uint32_t ha[16], hb[16];
            mbar_wait(barF + 8 * st, ph);
            {
                const int chl = 8 * (lane >> 4) + (lane & 7), sb8 = 2 * wl + ((lane >> 3) & 1);
                const uint32_t hbase = sb + st * G2_STAGE + chl * 128 + ((sb8 ^ (lane & 7)) << 4);
#pragma unroll
                for (int j = 0; j < 16; j += 2) ldsm_x4_t(ha[j], hb[j], ha[j + 1], hb[j + 1], hbase + j * 1024);
            }
            mbar_wait_cluster(barX, 0);
            TM(3, 4);
#pragma unroll
            for (int j0 = 0; j0 < 16; j0 += 4) {
                uint32_t P0[4], P1[4];
#pragma unroll
                for (int jj = 0; jj < 4; jj++) {
                    const int j = j0 + jj;
                    const float4 x = xb[j * 128];
                    P0[jj] = hadd2(ha[j], pack_bf16(acc[4 * j] + x.x, acc[4 * j + 1] + x.y));
                    P1[jj] = hadd2(hb[j], pack_bf16(acc[4 * j + 2] + x.z, acc[4 * j + 3] + x.w));
                }
                quad_transpose(P0[0], P0[1], P0[2], P0[3], t);
                quad_transpose(P1[0], P1[1], P1[2], P1[3], t);
                *reinterpret_cast<uint4*>(o0 + 8 * (j0 + t)) = make_uint4(P0[0], P0[1], P0[2], P0[3]);
                *reinterpret_cast<uint4*>(o0 + 8 * D_ + 8 * (j0 + t)) = make_uint4(P1[0], P1[1], P1[2], P1[3]);
            }
        }
        TM(3, 5);
    }
#undef TMT
}

typedef CUresult (*EncodeFn)(CUtensorMap*, CUtensorMapDataType, cuuint32_t, void*, const cuuint64_t*, const cuuint64_t*,
                             const cuuint32_t*, const cuuint32_t*, CUtensorMapInterleave, CUtensorMapSwizzle,
                             CUtensorMapL2promotion, CUtensorMapFloatOOBfill);

static void enc2d(EncodeFn enc, CUtensorMap* m, const void* p, int rows, int cols, int brows, int bcols) {
    cuuint64_t dims[2] = {(cuuint64_t)cols, (cuuint64_t)rows};
    cuuint64_t strides[1] = {(cuuint64_t)cols * 2};
    cuuint32_t box[2] = {(cuuint32_t)bcols, (cuuint32_t)brows};
    cuuint32_t es[2] = {1, 1};
    enc(m, CU_TENSOR_MAP_DATA_TYPE_BFLOAT16, 2, const_cast<void*>(p), dims, strides, box, es, CU_TENSOR_MAP_INTERLEAVE_NONE,
        bcols == 32 ? CU_TENSOR_MAP_SWIZZLE_64B : CU_TENSOR_MAP_SWIZZLE_128B, CU_TENSOR_MAP_L2_PROMOTION_L2_128B, CU_TENSOR_MAP_FLOAT_OOB_FILL_NONE);
}
static void enc3d(EncodeFn enc, CUtensorMap* m, const void* p, int rows, int cols, int atom, int brows, int natoms) {
    cuuint64_t dims[3] = {(cuuint64_t)atom, (cuuint64_t)rows, (cuuint64_t)(cols / atom)};
    cuuint64_t strides[2] = {(cuuint64_t)cols * 2, (cuuint64_t)atom * 2};
    cuuint32_t box[3] = {(cuuint32_t)atom, (cuuint32_t)brows, (cuuint32_t)natoms};
    cuuint32_t es[3] = {1, 1, 1};
    enc(m, CU_TENSOR_MAP_DATA_TYPE_BFLOAT16, 3, const_cast<void*>(p), dims, strides, box, es, CU_TENSOR_MAP_INTERLEAVE_NONE,
        atom == 32 ? CU_TENSOR_MAP_SWIZZLE_64B : CU_TENSOR_MAP_SWIZZLE_128B, CU_TENSOR_MAP_L2_PROMOTION_L2_128B, CU_TENSOR_MAP_FLOAT_OOB_FILL_NONE);
}

extern "C" void kernel_launch(void* const* d_in, const int* in_sizes, int n_in, void* d_out, int out_size) {
    const bf16* q = (const bf16*)d_in[0];
    const bf16* k = (const bf16*)d_in[1];
    const bf16* v = (const bf16*)d_in[2];
    const bf16* shift_k = (const bf16*)d_in[3];
    const bf16* ssm_k = (const bf16*)d_in[4];
    const bf16* ssm_D = (const bf16*)d_in[5];
    const bf16* wg = (const bf16*)d_in[7];
    const bf16* wu = (const bf16*)d_in[8];
    const bf16* wd = (const bf16*)d_in[9];
    bf16* out = (bf16*)d_out;

    static EncodeFn enc = nullptr;
    static void *p_hT = nullptr, *p_hh = nullptr;
    if (!enc) {
        void* fn = nullptr; cudaDriverEntryPointQueryResult qr;
        cudaGetDriverEntryPoint("cuTensorMapEncodeTiled", &fn, cudaEnableDefault, &qr);
        enc = (EncodeFn)fn;
        cudaGetSymbolAddress(&p_hT, g_hT);
        cudaGetSymbolAddress(&p_hh, g_hh);
        cudaFuncSetAttribute(conv_kernel, cudaFuncAttributeMaxDynamicSharedMemorySize, (int)sizeof(K1Smem));
        cudaFuncSetAttribute(gemm1_kernel, cudaFuncAttributeMaxDynamicSharedMemorySize, G1_SMEM);
        cudaFuncSetAttribute(gemm2_kernel, cudaFuncAttributeMaxDynamicSharedMemorySize, G2_SMEM);
    }
    CUtensorMap mA, mG64, mU64, mG32, mU32, mHH, mWd, mH;
    enc2d(enc, &mA, p_hT, D_, S_, 64, 64);
    enc2d(enc, &mH, p_hT, D_, S_, 128, 64);
    enc3d(enc, &mG64, wg, D_, F_, 32, 64, 4);
    enc3d(enc, &mU64, wu, D_, F_, 32, 64, 4);
    enc3d(enc, &mG32, wg, D_, F_, 32, 64, 3);
    enc3d(enc, &mU32, wu, D_, F_, 32, 64, 3);
    enc2d(enc, &mHH, p_hh, S_, F_, 128, 64);
    enc3d(enc, &mWd, wd, F_, D_, 64, 64, 2);

    cudaStream_t st = cudaStreamPerThread;
    cudaLaunchAttribute at[1];
    at[0].id = cudaLaunchAttributeProgrammaticStreamSerialization;
    at[0].val.programmaticStreamSerializationAllowed = 1;
    cudaLaunchConfig_t cfg = {};
    cfg.stream = st; cfg.attrs = at; cfg.numAttrs = 1;
    conv_kernel<<<128, K1_THREADS, sizeof(K1Smem), st>>>(q, k, v, shift_k, ssm_k, ssm_D, wg, wu, wd);
    cfg.gridDim = dim3(128); cfg.blockDim = dim3(G1_THREADS); cfg.dynamicSmemBytes = G1_SMEM;
    cudaLaunchKernelEx(&cfg, gemm1_kernel, mA, mG64, mU64, mG32, mU32);
    cfg.gridDim = dim3(128); cfg.blockDim = dim3(G2_THREADS); cfg.dynamicSmemBytes = G2_SMEM;
    cudaLaunchKernelEx(&cfg, gemm2_kernel, mHH, mWd, mH, out);
}
```

```cpp
#include <cuda_runtime.h>
#include <cuda_bf16.h>
#include <cuda.h>
#include <stdint.h>

typedef __nv_bfloat16 bf16;
constexpr int S_ = 2048, D_ = 512, F_ = 1792;

__device__ bf16 g_hT[D_ * S_];
__device__ bf16 g_hh[S_ * F_];
__device__ float2 g_st1[S_];
__device__ float g_colsum[2 * F_];
__device__ unsigned int g_cnt;

#define TM(k, i)
#define TR(k, i)
__device__ __forceinline__ uint32_t smem_u32(const void* p) { return (uint32_t)__cvta_generic_to_shared(p); }
__device__ __forceinline__ float bf16r(float x) { return __bfloat162float(__float2bfloat16_rn(x)); }
__device__ __forceinline__ float bf_lo(uint32_t w) { return __uint_as_float(w << 16); }
__device__ __forceinline__ float bf_hi(uint32_t w) { return __uint_as_float(w & 0xffff0000u); }
__device__ __forceinline__ uint32_t pack_bf16(float lo, float hi) {
    __nv_bfloat162 v = __floats2bfloat162_rn(lo, hi);
    return *reinterpret_cast<uint32_t*>(&v);
}
__device__ __forceinline__ uint32_t hmul2(uint32_t a, uint32_t b) {
    __nv_bfloat162 r = __hmul2_rn(*reinterpret_cast<__nv_bfloat162*>(&a), *reinterpret_cast<__nv_bfloat162*>(&b));
    return *reinterpret_cast<uint32_t*>(&r);
}
__device__ __forceinline__ uint32_t hadd2(uint32_t a, uint32_t b) {
    __nv_bfloat162 r = __hadd2_rn(*reinterpret_cast<__nv_bfloat162*>(&a), *reinterpret_cast<__nv_bfloat162*>(&b));
    return *reinterpret_cast<uint32_t*>(&r);
}
__device__ __forceinline__ uint4 ldg128(const void* p) {
    uint4 r; asm volatile("ld.global.nc.v4.u32 {%0,%1,%2,%3}, [%4];" : "=r"(r.x), "=r"(r.y), "=r"(r.z), "=r"(r.w) : "l"(p)); return r;
}
__device__ __forceinline__ uint4 ldcg128(const void* p) {
    uint4 r; asm volatile("ld.global.cg.v4.u32 {%0,%1,%2,%3}, [%4];" : "=r"(r.x), "=r"(r.y), "=r"(r.z), "=r"(r.w) : "l"(p)); return r;
}
__device__ __forceinline__ uint32_t ldg16(const void* p) {
    unsigned short r; asm volatile("ld.global.nc.u16 %0, [%1];" : "=h"(r) : "l"(p)); return (uint32_t)r;
}
__device__ __forceinline__ void mbar_init(uint32_t bar, int cnt) { asm volatile("mbarrier.init.shared::cta.b64 [%0], %1;" :: "r"(bar), "r"(cnt)); }
__device__ __forceinline__ void mbar_expect_tx(uint32_t bar, uint32_t bytes) { asm volatile("mbarrier.arrive.expect_tx.shared::cta.b64 _, [%0], %1;" :: "r"(bar), "r"(bytes) : "memory"); }
__device__ __forceinline__ void mbar_arrive(uint32_t bar) { asm volatile("mbarrier.arrive.shared::cta.b64 _, [%0];" :: "r"(bar) : "memory"); }
__device__ __forceinline__ void mbar_arrive_cluster(uint32_t bar, uint32_t cta) {
    asm volatile("{\n.reg .b32 ra;\nmapa.shared::cluster.u32 ra, %0, %1;\nmbarrier.arrive.shared::cluster.b64 _, [ra];\n}" :: "r"(bar), "r"(cta) : "memory");
}
__device__ __forceinline__ void mbar_wait(uint32_t bar, uint32_t parity) {
    asm volatile("{\n.reg .pred P1;\nLAB_WAIT:\nmbarrier.try_wait.parity.shared::cta.b64 P1, [%0], %1;\n@P1 bra DONE;\nbra LAB_WAIT;\nDONE:\n}" :: "r"(bar), "r"(parity) : "memory");
}
__device__ __forceinline__ void mbar_wait_cluster(uint32_t bar, uint32_t parity) {
    asm volatile("{\n.reg .pred P1;\nLAB_WAIT:\nmbarrier.try_wait.parity.acquire.cluster.shared::cta.b64 P1, [%0], %1;\n@P1 bra DONE;\nbra LAB_WAIT;\nDONE:\n}" :: "r"(bar), "r"(parity) : "memory");
}
__device__ __forceinline__ void tma_load_2d(uint32_t dst, const CUtensorMap* map, uint32_t bar, int c0, int c1) {
    asm volatile("cp.async.bulk.tensor.2d.shared::cluster.global.mbarrier::complete_tx::bytes [%0], [%1, {%3, %4}], [%2];"
        :: "r"(dst), "l"(map), "r"(bar), "r"(c0), "r"(c1) : "memory");
}
__device__ __forceinline__ void tma_load_2d_mc(uint32_t dst, const CUtensorMap* map, uint32_t bar, int c0, int c1, uint16_t mask) {
    asm volatile("cp.async.bulk.tensor.2d.shared::cluster.global.mbarrier::complete_tx::bytes.multicast::cluster [%0], [%1, {%3, %4}], [%2], %5;"
        :: "r"(dst), "l"(map), "r"(bar), "r"(c0), "r"(c1), "h"(mask) : "memory");
}
__device__ __forceinline__ void tma_load_3d(uint32_t dst, const CUtensorMap* map, uint32_t bar, int c0, int c1, int c2) {
    asm volatile("cp.async.bulk.tensor.3d.shared::cluster.global.mbarrier::complete_tx::bytes [%0], [%1, {%3, %4, %5}], [%2];"
        :: "r"(dst), "l"(map), "r"(bar), "r"(c0), "r"(c1), "r"(c2) : "memory");
}
__device__ __forceinline__ void cluster_arrive() { asm volatile("barrier.cluster.arrive.aligned;" ::: "memory"); }
__device__ __forceinline__ void cluster_arrive_relaxed() { asm volatile("barrier.cluster.arrive.relaxed.aligned;" ::: "memory"); }
__device__ __forceinline__ void cluster_wait() { asm volatile("barrier.cluster.wait.aligned;" ::: "memory"); }
__device__ __forceinline__ uint32_t mapa(uint32_t addr, uint32_t cta) {
    uint32_t r; asm volatile("mapa.shared::cluster.u32 %0, %1, %2;" : "=r"(r) : "r"(addr), "r"(cta)); return r;
}
__device__ __forceinline__ void st_async_v2(uint32_t addr, uint32_t a, uint32_t b, uint32_t rbar) {
    asm volatile("st.async.weak.shared::cluster.mbarrier::complete_tx::bytes.v2.b32 [%0], {%1, %2}, [%3];" :: "r"(addr), "r"(a), "r"(b), "r"(rbar) : "memory");
}
__device__ __forceinline__ void st_async_v4f(uint32_t addr, float a, float b, float c, float d, uint32_t rbar) {
    asm volatile("st.async.weak.shared::cluster.mbarrier::complete_tx::bytes.v4.f32 [%0], {%1, %2, %3, %4}, [%5];" :: "r"(addr), "f"(a), "f"(b), "f"(c), "f"(d), "r"(rbar) : "memory");
}
__device__ __forceinline__ void wgmma_fence() { asm volatile("wgmma.fence.sync.aligned;" ::: "memory"); }
__device__ __forceinline__ void wgmma_commit() { asm volatile("wgmma.commit_group.sync.aligned;" ::: "memory"); }
template <int N> __device__ __forceinline__ void wgmma_wait() { asm volatile("wgmma.wait_group.sync.aligned %0;" :: "n"(N) : "memory"); }
__device__ __forceinline__ uint64_t make_desc(uint32_t addr, uint32_t lbo_bytes, uint32_t sbo_bytes, uint32_t layout) {
    return (uint64_t)((addr & 0x3FFFF) >> 4) | ((uint64_t)(lbo_bytes >> 4) << 16) | ((uint64_t)(sbo_bytes >> 4) << 32) | ((uint64_t)layout << 62);
}
template <int R> __device__ __forceinline__ void reg_alloc() { asm volatile("setmaxnreg.inc.sync.aligned.u32 %0;" :: "n"(R)); }
template <int R> __device__ __forceinline__ void reg_dealloc() { asm volatile("setmaxnreg.dec.sync.aligned.u32 %0;" :: "n"(R)); }
__device__ __forceinline__ void pdl_launch() { asm volatile("griddepcontrol.launch_dependents;" ::: "memory"); }
__device__ __forceinline__ void pdl_wait() { asm volatile("griddepcontrol.wait;" ::: "memory"); }
__device__ __forceinline__ void prefetch_map(const CUtensorMap* m) { asm volatile("prefetch.tensormap [%0];" :: "l"(m) : "memory"); }
__device__ __forceinline__ void named_bar(int id, int n) { asm volatile("bar.sync %0, %1;" :: "r"(id), "r"(n) : "memory"); }

__device__ __forceinline__ void wgmma_m64n256k16_ss(float (&d)[128], uint64_t descA, uint64_t descB, int scaleD) {
    asm volatile("{\n.reg .pred p;\nsetp.ne.b32 p, %130, 0;\n"
        "wgmma.mma_async.sync.aligned.m64n256k16.f32.bf16.bf16 {%0, %1, %2, %3, %4, %5, %6, %7, %8, %9, %10, %11, %12, %13, %14, %15, %16, %17, %18, %19, %20, %21, %22, %23, %24, %25, %26, %27, %28, %29, %30, %31, %32, %33, %34, %35, %36, %37, %38, %39, %40, %41, %42, %43, %44, %45, %46, %47, %48, %49, %50, %51, %52, %53, %54, %55, %56, %57, %58, %59, %60, %61, %62, %63, %64, %65, %66, %67, %68, %69, %70, %71, %72, %73, %74, %75, %76, %77, %78, %79, %80, %81, %82, %83, %84, %85, %86, %87, %88, %89, %90, %91, %92, %93, %94, %95, %96, %97, %98, %99, %100, %101, %102, %103, %104, %105, %106, %107, %108, %109, %110, %111, %112, %113, %114, %115, %116, %117, %118, %119, %120, %121, %122, %123, %124, %125, %126, %127}, %128, %129, p, 1, 1, 1, 1;\n}\n"
        : "+f"(d[0]), "+f"(d[1]), "+f"(d[2]), "+f"(d[3]), "+f"(d[4]), "+f"(d[5]), "+f"(d[6]), "+f"(d[7]), "+f"(d[8]), "+f"(d[9]), "+f"(d[10]), "+f"(d[11]), "+f"(d[12]), "+f"(d[13]), "+f"(d[14]), "+f"(d[15]), "+f"(d[16]), "+f"(d[17]), "+f"(d[18]), "+f"(d[19]), "+f"(d[20]), "+f"(d[21]), "+f"(d[22]), "+f"(d[23]), "+f"(d[24]), "+f"(d[25]), "+f"(d[26]), "+f"(d[27]), "+f"(d[28]), "+f"(d[29]), "+f"(d[30]), "+f"(d[31]), "+f"(d[32]), "+f"(d[33]), "+f"(d[34]), "+f"(d[35]), "+f"(d[36]), "+f"(d[37]), "+f"(d[38]), "+f"(d[39]), "+f"(d[40]), "+f"(d[41]), "+f"(d[42]), "+f"(d[43]), "+f"(d[44]), "+f"(d[45]), "+f"(d[46]), "+f"(d[47]), "+f"(d[48]), "+f"(d[49]), "+f"(d[50]), "+f"(d[51]), "+f"(d[52]), "+f"(d[53]), "+f"(d[54]), "+f"(d[55]), "+f"(d[56]), "+f"(d[57]), "+f"(d[58]), "+f"(d[59]), "+f"(d[60]), "+f"(d[61]), "+f"(d[62]), "+f"(d[63]), "+f"(d[64]), "+f"(d[65]), "+f"(d[66]), "+f"(d[67]), "+f"(d[68]), "+f"(d[69]), "+f"(d[70]), "+f"(d[71]), "+f"(d[72]), "+f"(d[73]), "+f"(d[74]), "+f"(d[75]), "+f"(d[76]), "+f"(d[77]), "+f"(d[78]), "+f"(d[79]), "+f"(d[80]), "+f"(d[81]), "+f"(d[82]), "+f"(d[83]), "+f"(d[84]), "+f"(d[85]), "+f"(d[86]), "+f"(d[87]), "+f"(d[88]), "+f"(d[89]), "+f"(d[90]), "+f"(d[91]), "+f"(d[92]), "+f"(d[93]), "+f"(d[94]), "+f"(d[95]), "+f"(d[96]), "+f"(d[97]), "+f"(d[98]), "+f"(d[99]), "+f"(d[100]), "+f"(d[101]), "+f"(d[102]), "+f"(d[103]), "+f"(d[104]), "+f"(d[105]), "+f"(d[106]), "+f"(d[107]), "+f"(d[108]), "+f"(d[109]), "+f"(d[110]), "+f"(d[111]), "+f"(d[112]), "+f"(d[113]), "+f"(d[114]), "+f"(d[115]), "+f"(d[116]), "+f"(d[117]), "+f"(d[118]), "+f"(d[119]), "+f"(d[120]), "+f"(d[121]), "+f"(d[122]), "+f"(d[123]), "+f"(d[124]), "+f"(d[125]), "+f"(d[126]), "+f"(d[127])
        : "l"(descA), "l"(descB), "r"(scaleD));
}

__device__ __forceinline__ void wgmma_m64n192k16_ss(float (&d)[96], uint64_t descA, uint64_t descB, int scaleD) {
    asm volatile("{\n.reg .pred p;\nsetp.ne.b32 p, %98, 0;\n"
        "wgmma.mma_async.sync.aligned.m64n192k16.f32.bf16.bf16 {%0, %1, %2, %3, %4, %5, %6, %7, %8, %9, %10, %11, %12, %13, %14, %15, %16, %17, %18, %19, %20, %21, %22, %23, %24, %25, %26, %27, %28, %29, %30, %31, %32, %33, %34, %35, %36, %37, %38, %39, %40, %41, %42, %43, %44, %45, %46, %47, %48, %49, %50, %51, %52, %53, %54, %55, %56, %57, %58, %59, %60, %61, %62, %63, %64, %65, %66, %67, %68, %69, %70, %71, %72, %73, %74, %75, %76, %77, %78, %79, %80, %81, %82, %83, %84, %85, %86, %87, %88, %89, %90, %91, %92, %93, %94, %95}, %96, %97, p, 1, 1, 1, 1;\n}\n"
        : "+f"(d[0]), "+f"(d[1]), "+f"(d[2]), "+f"(d[3]), "+f"(d[4]), "+f"(d[5]), "+f"(d[6]), "+f"(d[7]), "+f"(d[8]), "+f"(d[9]), "+f"(d[10]), "+f"(d[11]), "+f"(d[12]), "+f"(d[13]), "+f"(d[14]), "+f"(d[15]), "+f"(d[16]), "+f"(d[17]), "+f"(d[18]), "+f"(d[19]), "+f"(d[20]), "+f"(d[21]), "+f"(d[22]), "+f"(d[23]), "+f"(d[24]), "+f"(d[25]), "+f"(d[26]), "+f"(d[27]), "+f"(d[28]), "+f"(d[29]), "+f"(d[30]), "+f"(d[31]), "+f"(d[32]), "+f"(d[33]), "+f"(d[34]), "+f"(d[35]), "+f"(d[36]), "+f"(d[37]), "+f"(d[38]), "+f"(d[39]), "+f"(d[40]), "+f"(d[41]), "+f"(d[42]), "+f"(d[43]), "+f"(d[44]), "+f"(d[45]), "+f"(d[46]), "+f"(d[47]), "+f"(d[48]), "+f"(d[49]), "+f"(d[50]), "+f"(d[51]), "+f"(d[52]), "+f"(d[53]), "+f"(d[54]), "+f"(d[55]), "+f"(d[56]), "+f"(d[57]), "+f"(d[58]), "+f"(d[59]), "+f"(d[60]), "+f"(d[61]), "+f"(d[62]), "+f"(d[63]), "+f"(d[64]), "+f"(d[65]), "+f"(d[66]), "+f"(d[67]), "+f"(d[68]), "+f"(d[69]), "+f"(d[70]), "+f"(d[71]), "+f"(d[72]), "+f"(d[73]), "+f"(d[74]), "+f"(d[75]), "+f"(d[76]), "+f"(d[77]), "+f"(d[78]), "+f"(d[79]), "+f"(d[80]), "+f"(d[81]), "+f"(d[82]), "+f"(d[83]), "+f"(d[84]), "+f"(d[85]), "+f"(d[86]), "+f"(d[87]), "+f"(d[88]), "+f"(d[89]), "+f"(d[90]), "+f"(d[91]), "+f"(d[92]), "+f"(d[93]), "+f"(d[94]), "+f"(d[95])
        : "l"(descA), "l"(descB), "r"(scaleD));
}

__device__ __forceinline__ void wgmma_m64n128k16_ss(float (&d)[64], uint64_t descA, uint64_t descB, int scaleD) {
    asm volatile("{\n.reg .pred p;\nsetp.ne.b32 p, %66, 0;\n"
        "wgmma.mma_async.sync.aligned.m64n128k16.f32.bf16.bf16 {%0, %1, %2, %3, %4, %5, %6, %7, %8, %9, %10, %11, %12, %13, %14, %15, %16, %17, %18, %19, %20, %21, %22, %23, %24, %25, %26, %27, %28, %29, %30, %31, %32, %33, %34, %35, %36, %37, %38, %39, %40, %41, %42, %43, %44, %45, %46, %47, %48, %49, %50, %51, %52, %53, %54, %55, %56, %57, %58, %59, %60, %61, %62, %63}, %64, %65, p, 1, 1, 0, 1;\n}\n"
        : "+f"(d[0]), "+f"(d[1]), "+f"(d[2]), "+f"(d[3]), "+f"(d[4]), "+f"(d[5]), "+f"(d[6]), "+f"(d[7]), "+f"(d[8]), "+f"(d[9]), "+f"(d[10]), "+f"(d[11]), "+f"(d[12]), "+f"(d[13]), "+f"(d[14]), "+f"(d[15]), "+f"(d[16]), "+f"(d[17]), "+f"(d[18]), "+f"(d[19]), "+f"(d[20]), "+f"(d[21]), "+f"(d[22]), "+f"(d[23]), "+f"(d[24]), "+f"(d[25]), "+f"(d[26]), "+f"(d[27]), "+f"(d[28]), "+f"(d[29]), "+f"(d[30]), "+f"(d[31]), "+f"(d[32]), "+f"(d[33]), "+f"(d[34]), "+f"(d[35]), "+f"(d[36]), "+f"(d[37]), "+f"(d[38]), "+f"(d[39]), "+f"(d[40]), "+f"(d[41]), "+f"(d[42]), "+f"(d[43]), "+f"(d[44]), "+f"(d[45]), "+f"(d[46]), "+f"(d[47]), "+f"(d[48]), "+f"(d[49]), "+f"(d[50]), "+f"(d[51]), "+f"(d[52]), "+f"(d[53]), "+f"(d[54]), "+f"(d[55]), "+f"(d[56]), "+f"(d[57]), "+f"(d[58]), "+f"(d[59]), "+f"(d[60]), "+f"(d[61]), "+f"(d[62]), "+f"(d[63])
        : "l"(descA), "l"(descB), "r"(scaleD));
}

__device__ __forceinline__ void quad_transpose(uint32_t& r0, uint32_t& r1, uint32_t& r2, uint32_t& r3, int t) {
    const bool o1 = t & 1, o2 = t & 2;
    uint32_t x, y;
    x = o1 ? r0 : r1; y = __shfl_xor_sync(0xffffffffu, x, 1); if (o1) r0 = y; else r1 = y;
    x = o1 ? r2 : r3; y = __shfl_xor_sync(0xffffffffu, x, 1); if (o1) r2 = y; else r3 = y;
    x = o2 ? r0 : r2; y = __shfl_xor_sync(0xffffffffu, x, 2); if (o2) r0 = y; else r2 = y;
    x = o2 ? r1 : r3; y = __shfl_xor_sync(0xffffffffu, x, 2); if (o2) r1 = y; else r3 = y;
}

__device__ __forceinline__ float warp_sum(float s) {
#pragma unroll
    for (int o = 16; o > 0; o >>= 1) s += __shfl_xor_sync(0xffffffffu, s, o);
    return s;
}
__device__ __forceinline__ uint32_t hsub2(uint32_t a, uint32_t b) {
    __nv_bfloat162 r = __hsub2_rn(*reinterpret_cast<__nv_bfloat162*>(&a), *reinterpret_cast<__nv_bfloat162*>(&b));
    return *reinterpret_cast<uint32_t*>(&r);
}
__device__ __forceinline__ void ln_stats2(const uint32_t (&x)[2][8], float2 (&st)[2]) {
    float piv[2], s[2], ss[2];
#pragma unroll
    for (int r = 0; r < 2; r++) piv[r] = __shfl_sync(0xffffffffu, bf_lo(x[r][0]), 0);
#pragma unroll
    for (int r = 0; r < 2; r++) {
        float s0 = 0.f, s1 = 0.f, q0 = 0.f, q1 = 0.f;
#pragma unroll
        for (int i = 0; i < 8; i++) {
            const float d0 = bf_lo(x[r][i]) - piv[r], d1 = bf_hi(x[r][i]) - piv[r];
            s0 += d0; s1 += d1; q0 = fmaf(d0, d0, q0); q1 = fmaf(d1, d1, q1);
        }
        s[r] = s0 + s1; ss[r] = q0 + q1;
    }
#pragma unroll
    for (int o = 16; o > 0; o >>= 1) {
#pragma unroll
        for (int r = 0; r < 2; r++) { s[r] += __shfl_xor_sync(0xffffffffu, s[r], o); ss[r] += __shfl_xor_sync(0xffffffffu, ss[r], o); }
    }
#pragma unroll
    for (int r = 0; r < 2; r++) {
        const float md = s[r] * (1.0f / D_);
        const float var = bf16r(fmaxf(fmaf(-md, md, ss[r] * (1.0f / D_)), 0.f));
        st[r] = make_float2(bf16r(piv[r] + md), 1.0f / bf16r(sqrtf(bf16r(var + 1e-5f))));
    }
}
__device__ __forceinline__ void ln_apply(const uint32_t (&x)[8], float2 st, uint32_t (&o)[8]) {
    const uint32_t m2 = pack_bf16(st.x, st.x);
#pragma unroll
    for (int i = 0; i < 8; i++) {
        const uint32_t d = hsub2(x[i], m2);
        o[i] = pack_bf16(bf_lo(d) * st.y, bf_hi(d) * st.y);
    }
}

constexpr int K1_THREADS = 288;
constexpr int UT_PAD = 128;
constexpr int UT_LEN = UT_PAD + S_;
constexpr int KR_LEN = 2080;
constexpr int YP_LEN = S_ + (S_ / 32) * 8;

struct __align__(128) K1Smem {
    bf16 uT[4][UT_LEN];
    bf16 xT[4][S_];
    bf16 kr[4][2][KR_LEN];
    float yP[4][YP_LEN];
    float2 st[S_];
    uint4 wS[512][4];
    float red[8][32];
    uint64_t bar, bar2;
};

__device__ __forceinline__ void mma16816(float (&c)[4], uint32_t a0, uint32_t a1, uint32_t a2, uint32_t a3, uint32_t b0, uint32_t b1) {
    asm("mma.sync.aligned.m16n8k16.row.col.f32.bf16.bf16.f32 {%0,%1,%2,%3}, {%4,%5,%6,%7}, {%8,%9}, {%0,%1,%2,%3};"
        : "+f"(c[0]), "+f"(c[1]), "+f"(c[2]), "+f"(c[3])
        : "r"(a0), "r"(a1), "r"(a2), "r"(a3), "r"(b0), "r"(b1));
}
__device__ __forceinline__ void ldsm_x4(uint32_t& r0, uint32_t& r1, uint32_t& r2, uint32_t& r3, uint32_t addr) {
    asm volatile("ldmatrix.sync.aligned.m8n8.x4.shared.b16 {%0,%1,%2,%3}, [%4];" : "=r"(r0), "=r"(r1), "=r"(r2), "=r"(r3) : "r"(addr) : "memory");
}

__device__ __forceinline__ void conv_mma(const bf16* uTc, const bf16* krlane, float (&acc)[16][4], int lane, int half) {
    const int lrow = lane & 7, lk = (lane >> 3) & 1, lt = lane >> 4;
    const uint32_t ubase = smem_u32(uTc) + (UT_PAD + 16 * (8 * lt + lrow) + 8 * lk) * 2;
#pragma unroll 1
    for (int pp = 0; pp < 4; pp++) {
        const int p = half * 4 + pp;
        uint32_t U[16][2];
#pragma unroll
        for (int j = 0; j < 16; j += 2) ldsm_x4(U[j][0], U[j][1], U[j + 1][0], U[j + 1][1], ubase + (j * 128 - p * 16) * 2);
        const uint32_t* kp = reinterpret_cast<const uint32_t*>(krlane - 16 * p);
        const volatile uint32_t* kpv = kp;
        uint32_t a0 = kp[0], a1 = kp[-4], a2 = kp[4], a3 = kpv[0];
#pragma unroll
        for (int q = 0; q < 16; q++) {
            uint32_t b0 = 0, b1 = 0, b2 = 0, b3 = 0;
            if (q < 15) { b0 = kp[-64 * (q + 1)]; b1 = kp[-64 * (q + 1) - 4]; b2 = kp[-64 * (q + 1) + 4]; b3 = kpv[-64 * (q + 1)]; }
#pragma unroll
            for (int n = 15; n >= q; n--) mma16816(acc[n], a0, a1, a2, a3, U[n - q][0], U[n - q][1]);
            a0 = b0; a1 = b1; a2 = b2; a3 = b3;
        }
    }
}

__device__ __forceinline__ void cp_async16(uint32_t dst, const void* src) {
    asm volatile("cp.async.cg.shared.global [%0], [%1], 16;" :: "r"(dst), "l"(src) : "memory");
}

__global__ void __cluster_dims__(2, 1, 1) __launch_bounds__(K1_THREADS, 1)
conv_kernel(const bf16* __restrict__ q, const bf16* __restrict__ k, const bf16* __restrict__ v,
            const bf16* __restrict__ shift_k, const bf16* __restrict__ ssm_k, const bf16* __restrict__ ssm_D,
            const bf16* __restrict__ wg, const bf16* __restrict__ wu, const bf16* __restrict__ wd) {
    extern __shared__ __align__(1024) uint8_t smem_raw[];
    pdl_launch();
    K1Smem& sm = *reinterpret_cast<K1Smem*>(smem_raw);
    const int tid = threadIdx.x, lane = tid & 31, warp = tid >> 5;
    const int bid = blockIdx.x;
    const int rank = bid & 1;
    const int c0 = 8 * (bid >> 1);
    const int cown = c0 + 4 * rank;
#define TMT 0
    TM(0, 0);
    const uint32_t bar = smem_u32(&sm.bar);
    if (tid == 0) {
        mbar_init(bar, 1);
        mbar_init(bar + 8, 1);
        asm volatile("fence.mbarrier_init.release.cluster;" ::: "memory");
        mbar_expect_tx(bar, 1024 * 4 * 2);
        mbar_expect_tx(bar + 8, 1024 * 4 * 2);
    }
    cluster_arrive_relaxed();

    if (warp < 8) {
        const int s0 = 1024 * rank + 4 * tid;
        uint4 kk[7], vv[4], qq[4], sw[4];
#pragma unroll
        for (int i = 0; i < 4; i++) kk[3 + i] = ldg128(k + (size_t)(s0 + i) * D_ + c0);
#pragma unroll
        for (int i = 0; i < 4; i++) vv[i] = ldg128(v + (size_t)(s0 + i) * D_ + c0);
        if (lane == 0) {
#pragma unroll
            for (int i = 0; i < 3; i++) {
                const int s = s0 - 3 + i;
                kk[i] = make_uint4(0, 0, 0, 0);
                if (s >= 0) kk[i] = ldg128(k + (size_t)s * D_ + c0);
            }
        }
#pragma unroll
        for (int i = 0; i < 4; i++) sw[i] = ldg128(shift_k + (size_t)c0 * 4 + 8 * i);
        uint4 kq[4]; uint32_t nx[4];
#pragma unroll
        for (int c = 0; c < 4; c++) {
            const bf16* kr = ssm_k + (size_t)(cown + c) * S_;
            kq[c] = ldg128(kr + 8 * tid);
            nx[c] = 0u;
            if (tid < 255) nx[c] = ldg16(kr + 8 * tid + 8);
        }
        const uint32_t dval = ldg16(ssm_D + cown + (warp >> 1));
        uint32_t xq[2][8];
#pragma unroll
        for (int r = 0; r < 2; r++) {
            const uint4 qa = ldg128(q + (size_t)(16 * bid + 2 * warp + r) * D_ + 8 * lane);
            const uint4 qb = ldg128(q + (size_t)(16 * bid + 2 * warp + r) * D_ + 8 * (lane + 32));
            xq[r][0] = qa.x; xq[r][1] = qa.y; xq[r][2] = qa.z; xq[r][3] = qa.w; xq[r][4] = qb.x; xq[r][5] = qb.y; xq[r][6] = qb.z; xq[r][7] = qb.w;
        }
#pragma unroll
        for (int i = 0; i < 4; i++) qq[i] = ldg128(q + (size_t)(s0 + i) * D_ + c0);
        if (tid < 64) *reinterpret_cast<uint4*>(&sm.uT[tid >> 4][(tid & 15) * 8]) = make_uint4(0, 0, 0, 0);
#pragma unroll
        for (int i = 0; i < 3; i++) {
            uint4 t;
            t.x = __shfl_up_sync(0xffffffffu, kk[4 + i].x, 1); t.y = __shfl_up_sync(0xffffffffu, kk[4 + i].y, 1);
            t.z = __shfl_up_sync(0xffffffffu, kk[4 + i].z, 1); t.w = __shfl_up_sync(0xffffffffu, kk[4 + i].w, 1);
            if (lane != 0) kk[i] = t;
        }
        uint32_t kvw[4][4];
        const uint32_t* kkw = reinterpret_cast<const uint32_t*>(kk);
        const uint32_t* vvw = reinterpret_cast<const uint32_t*>(vv);
        const uint32_t* qqw = reinterpret_cast<const uint32_t*>(qq);
#pragma unroll
        for (int i2 = 0; i2 < 4; i2++) {
            const uint32_t t0 = __byte_perm(sw[i2].x, sw[i2].z, 0x5410), t1 = __byte_perm(sw[i2].x, sw[i2].z, 0x7632);
            const uint32_t t2 = __byte_perm(sw[i2].y, sw[i2].w, 0x5410), t3 = __byte_perm(sw[i2].y, sw[i2].w, 0x7632);
#pragma unroll
            for (int r = 0; r < 4; r++) {
                uint32_t a = hmul2(kkw[(r + 0) * 4 + i2], t3);
                a = hadd2(a, hmul2(kkw[(r + 1) * 4 + i2], t2));
                a = hadd2(a, hmul2(kkw[(r + 2) * 4 + i2], t1));
                a = hadd2(a, hmul2(kkw[(r + 3) * 4 + i2], t0));
                kvw[r][i2] = hmul2(a, vvw[r * 4 + i2]);
            }
        }
        TM(0, 1);
        cluster_wait();
        const uint32_t rbar = mapa(bar, (uint32_t)(rank ^ 1));
#pragma unroll
        for (int i2 = 0; i2 < 4; i2++) {
#pragma unroll
            for (int e = 0; e < 2; e++) {
                const uint32_t sel = e ? 0x7632 : 0x5410;
                const uint32_t w0 = __byte_perm(kvw[0][i2], kvw[1][i2], sel), w1 = __byte_perm(kvw[2][i2], kvw[3][i2], sel);
                const int cc = 2 * i2 + e;
                if ((cc >> 2) == rank) *reinterpret_cast<uint2*>(&sm.uT[cc & 3][UT_PAD + s0]) = make_uint2(w0, w1);
                else st_async_v2(mapa(smem_u32(&sm.uT[cc & 3][UT_PAD + s0]), (uint32_t)(rank ^ 1)), w0, w1, rbar);
            }
        }
#pragma unroll
        for (int c = 0; c < 4; c++) {
            uint4 a, b;
            a.x = __byte_perm(kq[c].w, 0, 0x1032); a.y = __byte_perm(kq[c].z, 0, 0x1032);
            a.z = __byte_perm(kq[c].y, 0, 0x1032); a.w = __byte_perm(kq[c].x, 0, 0x1032);
            b.x = __byte_perm(nx[c], kq[c].w, 0x7610); b.y = __byte_perm(kq[c].w, kq[c].z, 0x7610);
            b.z = __byte_perm(kq[c].z, kq[c].y, 0x7610); b.w = __byte_perm(kq[c].y, kq[c].x, 0x7610);
            *reinterpret_cast<uint4*>(&sm.kr[c][0][2040 - 8 * tid]) = a;
            *reinterpret_cast<uint4*>(&sm.kr[c][1][2040 - 8 * tid]) = b;
            if (tid == 0) {
                *reinterpret_cast<uint4*>(&sm.kr[c][1][2048]) = make_uint4(kq[c].x & 0xffffu, 0, 0, 0);
            } else if (tid < 8) {
                if (tid < 4) *reinterpret_cast<uint4*>(&sm.kr[c][1][2048 + 8 * tid]) = make_uint4(0, 0, 0, 0);
                else *reinterpret_cast<uint4*>(&sm.kr[c][0][2048 + 8 * (tid - 4)]) = make_uint4(0, 0, 0, 0);
            }
        }
        {
            float2 st[2];
            ln_stats2(xq, st);
            if (lane < 2) g_st1[16 * bid + 2 * warp + lane] = lane ? st[1] : st[0];
        }
        TM(0, 3);
        named_bar(6, 288);
        mbar_wait_cluster(bar, 0);
        TM(0, 4);

        const int ch = warp >> 1, half = warp & 1;
        const int g = lane >> 2, t = lane & 3;
        float acc[16][4];
#pragma unroll
        for (int i = 0; i < 16; i++) { acc[i][0] = acc[i][1] = acc[i][2] = acc[i][3] = 0.f; }
        const bf16* krlane = (g & 1) ? &sm.kr[ch][0][2047 - g + 2 * t] : &sm.kr[ch][1][2048 - g + 2 * t];
        conv_mma(sm.uT[ch], krlane, acc, lane, half);
        TM(0, 5);
#pragma unroll
        for (int i2 = 0; i2 < 4; i2++) {
#pragma unroll
            for (int e = 0; e < 2; e++) {
                const uint32_t sel = e ? 0x7632 : 0x5410;
                const uint32_t w0 = __byte_perm(qqw[i2], qqw[4 + i2], sel), w1 = __byte_perm(qqw[8 + i2], qqw[12 + i2], sel);
                const int cc = 2 * i2 + e;
                if ((cc >> 2) == rank) *reinterpret_cast<uint2*>(&sm.xT[cc & 3][s0]) = make_uint2(w0, w1);
                else st_async_v2(mapa(smem_u32(&sm.xT[cc & 3][s0]), (uint32_t)(rank ^ 1)), w0, w1, rbar + 8);
            }
        }
        float* yp = &sm.yP[ch][40 * t + g];
        if (half) {
#pragma unroll
            for (int n = 0; n < 16; n++) {
                yp[160 * n] = acc[n][0];
                yp[160 * n + 16] = acc[n][1];
                yp[160 * n + 8] = acc[n][2];
                yp[160 * n + 24] = acc[n][3];
            }
        }
        named_bar(1 + ch, 64);
        if (!half) {
#pragma unroll
            for (int n = 0; n < 16; n++) {
                yp[160 * n] += acc[n][0];
                yp[160 * n + 16] += acc[n][1];
                yp[160 * n + 8] += acc[n][2];
                yp[160 * n + 24] += acc[n][3];
            }
        }
        named_bar(7, 288);
        mbar_wait_cluster(bar + 8, 0);
        TM(0, 6);
        {
            const int tt = tid & 63;
            bf16* dst = g_hT + (size_t)(cown + ch) * S_;
            const uint32_t d2 = dval * 0x10001u;
#pragma unroll
            for (int j = 0; j < 4; j++) {
                const int s = (j * 64 + tt) * 8;
                const float* src = &sm.yP[ch][s + (s >> 5) * 8];
                const float4 a = *reinterpret_cast<const float4*>(src), b = *reinterpret_cast<const float4*>(src + 4);
                const uint4 kv4 = *reinterpret_cast<const uint4*>(&sm.uT[ch][UT_PAD + s]);
                const uint4 x4 = *reinterpret_cast<const uint4*>(&sm.xT[ch][s]);
                const uint32_t y2[4] = {hadd2(pack_bf16(a.x, a.y), hmul2(kv4.x, d2)), hadd2(pack_bf16(a.z, a.w), hmul2(kv4.y, d2)),
                                        hadd2(pack_bf16(b.x, b.y), hmul2(kv4.z, d2)), hadd2(pack_bf16(b.z, b.w), hmul2(kv4.w, d2))};
                const uint32_t xw[4] = {x4.x, x4.y, x4.z, x4.w};
                uint32_t o[4];
#pragma unroll
                for (int i = 0; i < 4; i++) {
                    const float4 st = *reinterpret_cast<const float4*>(&sm.st[s + 2 * i]);
                    const uint32_t d = hsub2(xw[i], pack_bf16(st.x, st.z));
                    const uint32_t qn = pack_bf16(bf_lo(d) * st.y, bf_hi(d) * st.w);
                    o[i] = hadd2(xw[i], hmul2(qn, y2[i]));
                }
                *reinterpret_cast<uint4*>(dst + s) = make_uint4(o[0], o[1], o[2], o[3]);
            }
        }
        TM(0, 7);
    } else {
        cluster_wait();
        named_bar(6, 288);
        if (lane == 0) { __threadfence(); atomicAdd(&g_cnt, 1u); }
        if (bid < 112) {
            const bf16* wp = (bid < 56) ? (wg + 32 * bid) : (wu + 32 * (bid - 56));
#pragma unroll 4
            for (int i = 0; i < 64; i++) {
                const int idx = i * 32 + lane;
                cp_async16(smem_u32(&sm.wS[idx >> 2][idx & 3]), wp + (size_t)(idx >> 2) * F_ + (idx & 3) * 8);
            }
        }
        if (lane == 0) asm volatile("cp.async.bulk.prefetch.L2.global [%0], %1;" :: "l"(wd + (size_t)bid * 7168), "r"(14336) : "memory");
        asm volatile("cp.async.wait_all;" ::: "memory");
        __syncwarp();
        if (bid < 112) {
            const int cq = lane & 3, rgp = lane >> 2;
            float cs[8];
#pragma unroll
            for (int i = 0; i < 8; i++) cs[i] = 0.f;
#pragma unroll 4
            for (int r = 0; r < 64; r++) {
                const uint4 w = sm.wS[r * 8 + rgp][cq];
                cs[0] += bf_lo(w.x); cs[1] += bf_hi(w.x); cs[2] += bf_lo(w.y); cs[3] += bf_hi(w.y);
                cs[4] += bf_lo(w.z); cs[5] += bf_hi(w.z); cs[6] += bf_lo(w.w); cs[7] += bf_hi(w.w);
            }
#pragma unroll
            for (int i = 0; i < 8; i++) {
                cs[i] += __shfl_xor_sync(0xffffffffu, cs[i], 4);
                cs[i] += __shfl_xor_sync(0xffffffffu, cs[i], 8);
                cs[i] += __shfl_xor_sync(0xffffffffu, cs[i], 16);
            }
            if (lane < 4) {
                *reinterpret_cast<float4*>(&g_colsum[32 * bid + lane * 8]) = make_float4(cs[0], cs[1], cs[2], cs[3]);
                *reinterpret_cast<float4*>(&g_colsum[32 * bid + lane * 8 + 4]) = make_float4(cs[4], cs[5], cs[6], cs[7]);
            }
        }
        {
            unsigned int c; int spins = 0;
            do { asm volatile("ld.acquire.gpu.global.u32 %0, [%1];" : "=r"(c) : "l"(&g_cnt) : "memory"); } while (c < gridDim.x && ++spins < (1 << 22));
        }
#pragma unroll 4
        for (int i = 0; i < 32; i++) cp_async16(smem_u32(&sm.st[2 * (i * 32 + lane)]), &g_st1[2 * (i * 32 + lane)]);
        asm volatile("cp.async.wait_all;" ::: "memory");
        named_bar(7, 288);
    }
#undef TMT
}

constexpr int G1_THREADS = 384;
constexpr int G1_STAGES = 3;
constexpr int G1_A_BYTES = 8 * 16384;
constexpr int G1_B_STAGE = 32768;
constexpr int G1_OFF_B = G1_A_BYTES;
constexpr int G1_OFF_STATS = G1_OFF_B + G1_STAGES * G1_B_STAGE;
constexpr int G1_OFF_CS = G1_OFF_STATS + 1024;
constexpr int G1_OFF_BAR = G1_OFF_CS + 1792;
constexpr int G1_SMEM = G1_OFF_BAR + 128;

__device__ __forceinline__ float tanh_fast(float x) { float t; asm("tanh.approx.f32 %0, %1;" : "=f"(t) : "f"(x)); return t; }

template <int NT>
__device__ __forceinline__ void g1_epilogue(const float (&acc)[NT * 8], const float* cs_g, const float* cs_u, float2 st0, float2 st1, bf16* out0, int t) {
    const float r0 = st0.y, r1 = st1.y, m0 = -st0.x * st0.y, m1 = -st1.x * st1.y;
#pragma unroll
    for (int j0 = 0; j0 < NT; j0 += 4) {
        uint32_t P0[4], P1[4];
#pragma unroll
        for (int jj = 0; jj < 4; jj++) {
            const int j = j0 + jj;
            const float2 cg = *reinterpret_cast<const float2*>(cs_g + 8 * j + 2 * t);
            const float2 cu = *reinterpret_cast<const float2*>(cs_u + 8 * j + 2 * t);
            float r[4];
#pragma unroll
            for (int e = 0; e < 4; e++) {
                const float rr = (e < 2) ? r0 : r1, mm = (e < 2) ? m0 : m1;
                const float gv = fmaf(acc[4 * j + e], rr, mm * ((e & 1) ? cg.y : cg.x));
                const float uv = fmaf(acc[4 * (NT + j) + e], rr, mm * ((e & 1) ? cu.y : cu.x));
                r[e] = fmaf(tanh_fast(0.5f * gv), 0.5f, 0.5f) * uv;
            }
            P0[jj] = pack_bf16(r[0], r[1]);
            P1[jj] = pack_bf16(r[2], r[3]);
        }
        quad_transpose(P0[0], P0[1], P0[2], P0[3], t);
        quad_transpose(P1[0], P1[1], P1[2], P1[3], t);
        *reinterpret_cast<uint4*>(out0 + 8 * (j0 + t)) = make_uint4(P0[0], P0[1], P0[2], P0[3]);
        *reinterpret_cast<uint4*>(out0 + 8 * F_ + 8 * (j0 + t)) = make_uint4(P1[0], P1[1], P1[2], P1[3]);
    }
}

__global__ void __cluster_dims__(2, 1, 1) __launch_bounds__(G1_THREADS, 1)
gemm1_kernel(const __grid_constant__ CUtensorMap mapA, const __grid_constant__ CUtensorMap mapG4, const __grid_constant__ CUtensorMap mapU4,
             const __grid_constant__ CUtensorMap mapG3, const __grid_constant__ CUtensorMap mapU3) {
    extern __shared__ __align__(1024) uint8_t smem_raw[];
    const uint32_t sb = smem_u32(smem_raw);
    const int tid = threadIdx.x, lane = tid & 31, warp = tid >> 5, wgi = tid >> 7;
    const int rank = blockIdx.x & 1;
    const int cb = blockIdx.x & 7, rb = blockIdx.x >> 3;
#define TMT 128
    TM(2, 0);
    pdl_launch();
    if (tid == 32) { prefetch_map(&mapA); prefetch_map(&mapG3); prefetch_map(&mapU3); }
    const uint32_t barA = sb + G1_OFF_BAR;
    const uint32_t barF = barA + 64;
    const uint32_t barE = barF + 8 * G1_STAGES;
    const uint32_t barS = barE + 8 * G1_STAGES;
    if (tid == 0) {
        for (int i = 0; i < 8; i++) mbar_init(barA + 8 * i, 1);
        for (int i = 0; i < G1_STAGES; i++) { mbar_init(barF + 8 * i, 1); mbar_init(barE + 8 * i, 2); }
        mbar_init(barS, 1);
        for (int i = 0; i < 8; i++) mbar_expect_tx(barA + 8 * i, 16384);
        asm volatile("fence.mbarrier_init.release.cluster;" ::: "memory");
    }
    __syncthreads();
    cluster_arrive_relaxed();

    if (wgi == 0) {
        reg_dealloc<40>();
        if (warp == 0) {
            if (lane == 0) {
                int st = 0, ph = 1;
                for (int it = 0; it < 16; it++) {
                    const int kc = it & 7;
                    mbar_wait(barE + 8 * st, ph);
                    const uint32_t dst = sb + G1_OFF_B + st * G1_B_STAGE;
                    if (it < 8) {
                        mbar_expect_tx(barF + 8 * st, 32768);
                        tma_load_3d(dst, &mapG4, barF + 8 * st, 0, kc * 64, cb * 7);
                        tma_load_3d(dst + 16384, &mapU4, barF + 8 * st, 0, kc * 64, cb * 7);
                    } else {
                        mbar_expect_tx(barF + 8 * st, 24576);
                        tma_load_3d(dst, &mapG3, barF + 8 * st, 0, kc * 64, cb * 7 + 4);
                        tma_load_3d(dst + 12288, &mapU3, barF + 8 * st, 0, kc * 64, cb * 7 + 4);
                    }
                    if (++st == G1_STAGES) { st = 0; ph ^= 1; }
                }
            }
            __syncwarp();
            cluster_wait();
        } else if (warp == 1) {
            cluster_wait();
            pdl_wait();
            if (lane < 8) {
                const int c = 2 * (lane >> 1) + rank, mh = lane & 1;
                tma_load_2d_mc(sb + c * 16384 + mh * 8192, &mapA, barA + 8 * c, rb * 128 + mh * 64, c * 64, (uint16_t)3);
            }
            __syncwarp();
            float* cs = reinterpret_cast<float*>(smem_raw + G1_OFF_CS);
            for (int i = lane; i < 448; i += 32) cs[i] = __ldcg((i < 224) ? &g_colsum[cb * 224 + i] : &g_colsum[F_ + cb * 224 + (i - 224)]);
            __syncwarp();
            if (lane == 0) mbar_arrive(barS);
        } else {
            cluster_wait();
        }
    } else {
        reg_alloc<232>();
        cluster_wait();
        const int cw = wgi - 1;
        const int g = lane >> 2, t = lane & 3, wl = warp & 3, tl = tid & 127;
        bf16* outp = g_hh + (size_t)(rb * 128 + cw * 64 + wl * 16 + g) * F_ + cb * 224;
        const float* cs = reinterpret_cast<const float*>(smem_raw + G1_OFF_CS);
        int st = 0, ph = 0;
        float2 st0, st1;
        {
            float acc[128];
            const int kq = lane >> 3, mp = lane & 7;
            const uint8_t* sbase = smem_raw + cw * 8192 + kq * 128 + (mp & 3) * 4;
            const int mc = 2 * wl + (mp >> 2);
            float p0 = 0.f, p1 = 0.f, s0 = 0.f, s1 = 0.f, q0 = 0.f, q1 = 0.f;
#pragma unroll 1
            for (int kc = 0; kc < 8; kc++) {
                mbar_wait(barA + 8 * kc, 0);
                mbar_wait(barF + 8 * st, ph);
                if (tl == 0 && cw == 0) TR(1, kc);
                wgmma_fence();
                const uint32_t aaddr = sb + kc * 16384 + cw * 8192;
                const uint32_t baddr = sb + G1_OFF_B + st * G1_B_STAGE;
#pragma unroll
                for (int kk = 0; kk < 4; kk++)
                    wgmma_m64n256k16_ss(acc, make_desc(aaddr + kk * 2048, 8192, 1024, 1), make_desc(baddr + kk * 1024, 4096, 512, 2), (kc | kk) != 0);
                wgmma_commit();
                if (kc == 0) {
                    const uint32_t w = *reinterpret_cast<const uint32_t*>(smem_raw + cw * 8192 + (mc << 4) + (mp & 3) * 4);
                    p0 = bf_lo(w); p1 = bf_hi(w);
                }
#pragma unroll
                for (int i = 0; i < 16; i++) {
                    const int kr = 4 * i;
                    const uint32_t w = *reinterpret_cast<const uint32_t*>(sbase + kc * 16384 + kr * 128 + ((mc ^ ((kr + kq) & 7)) << 4));
                    const float d0 = bf_lo(w) - p0, d1 = bf_hi(w) - p1;
                    s0 += d0; s1 += d1; q0 = fmaf(d0, d0, q0); q1 = fmaf(d1, d1, q1);
                }
                wgmma_wait<0>();
                if (tl == 0) mbar_arrive(barE + 8 * st);
                if (++st == G1_STAGES) { st = 0; ph ^= 1; }
            }
            TM(2, 1);
            {
#pragma unroll
                for (int o = 8; o <= 16; o <<= 1) {
                    s0 += __shfl_xor_sync(0xffffffffu, s0, o); s1 += __shfl_xor_sync(0xffffffffu, s1, o);
                    q0 += __shfl_xor_sync(0xffffffffu, q0, o); q1 += __shfl_xor_sync(0xffffffffu, q1, o);
                }
                const float md0 = s0 * (1.0f / D_), md1 = s1 * (1.0f / D_);
                const float v0 = bf16r(fmaxf(fmaf(-md0, md0, q0 * (1.0f / D_)), 0.f)), v1 = bf16r(fmaxf(fmaf(-md1, md1, q1 * (1.0f / D_)), 0.f));
                const float ma = bf16r(p0 + md0), mb = bf16r(p1 + md1);
                const float ra = 1.0f / bf16r(sqrtf(bf16r(v0 + 1e-5f))), rbb = 1.0f / bf16r(sqrtf(bf16r(v1 + 1e-5f)));
                const float mA = __shfl_sync(0xffffffffu, ma, g >> 1), mB = __shfl_sync(0xffffffffu, mb, g >> 1);
                const float rA = __shfl_sync(0xffffffffu, ra, g >> 1), rB = __shfl_sync(0xffffffffu, rbb, g >> 1);
                const float mC = __shfl_sync(0xffffffffu, ma, 4 + (g >> 1)), mD = __shfl_sync(0xffffffffu, mb, 4 + (g >> 1));
                const float rC = __shfl_sync(0xffffffffu, ra, 4 + (g >> 1)), rD = __shfl_sync(0xffffffffu, rbb, 4 + (g >> 1));
                st0 = (g & 1) ? make_float2(mB, rB) : make_float2(mA, rA);
                st1 = (g & 1) ? make_float2(mD, rD) : make_float2(mC, rC);
            }
            mbar_wait(barS, 0);
            pdl_wait();
            TM(2, 5);
            g1_epilogue<16>(acc, cs, cs + 224, st0, st1, outp, t);
            TM(2, 2);
        }
        {
            float acc[96];
#pragma unroll 1
            for (int kc = 0; kc < 8; kc++) {
                mbar_wait(barF + 8 * st, ph);
                if (tl == 0 && cw == 0) TR(1, 8 + kc);
                wgmma_fence();
                const uint32_t aaddr = sb + kc * 16384 + cw * 8192;
                const uint32_t baddr = sb + G1_OFF_B + st * G1_B_STAGE;
#pragma unroll
                for (int kk = 0; kk < 4; kk++)
                    wgmma_m64n192k16_ss(acc, make_desc(aaddr + kk * 2048, 8192, 1024, 1), make_desc(baddr + kk * 1024, 4096, 512, 2), (kc | kk) != 0);
                wgmma_commit();
                wgmma_wait<0>();
                if (tl == 0) mbar_arrive(barE + 8 * st);
                if (++st == G1_STAGES) { st = 0; ph ^= 1; }
            }
            TM(2, 3);
            g1_epilogue<12>(acc, cs + 128, cs + 224 + 128, st0, st1, outp + 128, t);
            TM(2, 4);
        }
    }
}

constexpr int G2_THREADS = 384;
constexpr int G2_STAGES = 6;
constexpr int G2_STAGE = 32768;
constexpr int G2_OFF_X = G2_STAGES * G2_STAGE;
constexpr int G2_OFF_BAR = G2_OFF_X + 32768;
constexpr int G2_SMEM = G2_OFF_BAR + 128;
constexpr int G2_KSTEPS = 14;

__device__ __forceinline__ void ldsm_x4_t(uint32_t& r0, uint32_t& r1, uint32_t& r2, uint32_t& r3, uint32_t addr) {
    asm volatile("ldmatrix.sync.aligned.m8n8.x4.trans.shared.b16 {%0,%1,%2,%3}, [%4];" : "=r"(r0), "=r"(r1), "=r"(r2), "=r"(r3) : "r"(addr) : "memory");
}

__global__ void __cluster_dims__(2, 1, 1) __launch_bounds__(G2_THREADS, 1)
gemm2_kernel(const __grid_constant__ CUtensorMap mapHH, const __grid_constant__ CUtensorMap mapWd, const __grid_constant__ CUtensorMap mapH,
             bf16* __restrict__ out) {
    extern __shared__ __align__(1024) uint8_t smem_raw[];
    const uint32_t sb = smem_u32(smem_raw);
    const int tid = threadIdx.x, lane = tid & 31, warp = tid >> 5, wgi = tid >> 7;
    const int ks = blockIdx.x & 1, nb = (blockIdx.x >> 1) & 3, rb = blockIdx.x >> 3;
    TM(3, 0);
    if (tid == 32) { prefetch_map(&mapHH); prefetch_map(&mapH); }
    const uint32_t barF = sb + G2_OFF_BAR;
    const uint32_t barE = barF + 8 * G2_STAGES;
    const uint32_t barX = barE + 8 * G2_STAGES;
    if (tid == 0) {
        for (int i = 0; i < G2_STAGES; i++) { mbar_init(barF + 8 * i, 1); mbar_init(barE + 8 * i, 2); }
        mbar_init(barX, 1);
        asm volatile("fence.mbarrier_init.release.cluster;" ::: "memory");
        mbar_expect_tx(barX, 32768);
        for (int it = 0; it < G2_STAGES; it++) {
            mbar_expect_tx(barF + 8 * it, 32768);
            tma_load_3d(sb + it * G2_STAGE + 16384, &mapWd, barF + 8 * it, 0, ks * 896 + it * 64, nb * 2);
        }
    }
    __syncthreads();
    cluster_arrive_relaxed();

    if (wgi == 0) {
        if (tid == 0) {
            pdl_wait();
            for (int it = 0; it < G2_STAGES; it++)
                tma_load_2d(sb + it * G2_STAGE, &mapHH, barF + 8 * it, ks * 896 + it * 64, rb * 128);
            if (blockIdx.x == 0) g_cnt = 0u;
            int st = 0, ph = 0;
            for (int it = G2_STAGES; it < G2_KSTEPS; it++) {
                mbar_wait(barE + 8 * st, ph);
                const uint32_t dst = sb + st * G2_STAGE;
                const int k0 = ks * 896 + it * 64;
                mbar_expect_tx(barF + 8 * st, 32768);
                tma_load_2d(dst, &mapHH, barF + 8 * st, k0, rb * 128);
                tma_load_3d(dst + 16384, &mapWd, barF + 8 * st, 0, k0, nb * 2);
                if (++st == G2_STAGES) { st = 0; ph ^= 1; }
            }
            mbar_wait(barE + 8 * st, ph);
            mbar_expect_tx(barF + 8 * st, 16384);
            tma_load_2d(sb + st * G2_STAGE, &mapH, barF + 8 * st, rb * 128 + ks * 64, nb * 128);
        }
        __syncwarp();
        cluster_wait();
    } else {
        const int cw = wgi - 1;
        const int g = lane >> 2, t = lane & 3, wl = warp & 3;
        const int tl = tid & 127;
        int st = 0, ph = 0;
        float acc[64];
#pragma unroll 1
        for (int it = 0; it < G2_KSTEPS; it++) {
            mbar_wait(barF + 8 * st, ph);
            if (it == 0) TM(3, 1);
            wgmma_fence();
            const uint32_t aaddr = sb + st * G2_STAGE + cw * 8192;
            const uint32_t baddr = sb + st * G2_STAGE + 16384;
#pragma unroll
            for (int kk = 0; kk < 4; kk++)
                wgmma_m64n128k16_ss(acc, make_desc(aaddr + kk * 32, 16, 1024, 1), make_desc(baddr + kk * 2048, 8192, 1024, 1), (it | kk) != 0);
            wgmma_commit();
            wgmma_wait<0>();
            if (tl == 0) mbar_arrive(barE + 8 * st);
            if (++st == G2_STAGES) { st = 0; ph ^= 1; }
        }
        TM(3, 2);
        cluster_wait();
        if (cw != ks) {
            const uint32_t dst = mapa(sb + G2_OFF_X + tl * 16, (uint32_t)(ks ^ 1));
            const uint32_t rbar = mapa(barX, (uint32_t)(ks ^ 1));
#pragma unroll
            for (int i = 0; i < 16; i++) st_async_v4f(dst + i * 2048, acc[4 * i], acc[4 * i + 1], acc[4 * i + 2], acc[4 * i + 3], rbar);
        } else {
            const float4* xb = reinterpret_cast<const float4*>(smem_raw + G2_OFF_X) + tl;
            const int row0 = rb * 128 + cw * 64 + wl * 16 + g;
            bf16* o0 = out + (size_t)row0 * D_ + nb * 128;
            uint32_t ha[16], hb[16];
            mbar_wait(barF + 8 * st, ph);
            {
                const int chl = 8 * (lane >> 4) + (lane & 7), sb8 = 2 * wl + ((lane >> 3) & 1);
                const uint32_t hbase = sb + st * G2_STAGE + chl * 128 + ((sb8 ^ (lane & 7)) << 4);
#pragma unroll
                for (int j = 0; j < 16; j += 2) ldsm_x4_t(ha[j], hb[j], ha[j + 1], hb[j + 1], hbase + j * 1024);
            }
            mbar_wait_cluster(barX, 0);
            TM(3, 4);
#pragma unroll
            for (int j0 = 0; j0 < 16; j0 += 4) {
                uint32_t P0[4], P1[4];
#pragma unroll
                for (int jj = 0; jj < 4; jj++) {
                    const int j = j0 + jj;
                    const float4 x = xb[j * 128];
                    P0[jj] = hadd2(ha[j], pack_bf16(acc[4 * j] + x.x, acc[4 * j + 1] + x.y));
                    P1[jj] = hadd2(hb[j], pack_bf16(acc[4 * j + 2] + x.z, acc[4 * j + 3] + x.w));
                }
                quad_transpose(P0[0], P0[1], P0[2], P0[3], t);
                quad_transpose(P1[0], P1[1], P1[2], P1[3], t);
                *reinterpret_cast<uint4*>(o0 + 8 * (j0 + t)) = make_uint4(P0[0], P0[1], P0[2], P0[3]);
                *reinterpret_cast<uint4*>(o0 + 8 * D_ + 8 * (j0 + t)) = make_uint4(P1[0], P1[1], P1[2], P1[3]);
            }
        }
        TM(3, 5);
    }
#undef TMT
}

typedef CUresult (*EncodeFn)(CUtensorMap*, CUtensorMapDataType, cuuint32_t, void*, const cuuint64_t*, const cuuint64_t*,
                             const cuuint32_t*, const cuuint32_t*, CUtensorMapInterleave, CUtensorMapSwizzle,
                             CUtensorMapL2promotion, CUtensorMapFloatOOBfill);

static void enc2d(EncodeFn enc, CUtensorMap* m, const void* p, int rows, int cols, int brows, int bcols) {
    cuuint64_t dims[2] = {(cuuint64_t)cols, (cuuint64_t)rows};
    cuuint64_t strides[1] = {(cuuint64_t)cols * 2};
    cuuint32_t box[2] = {(cuuint32_t)bcols, (cuuint32_t)brows};
    cuuint32_t es[2] = {1, 1};
    enc(m, CU_TENSOR_MAP_DATA_TYPE_BFLOAT16, 2, const_cast<void*>(p), dims, strides, box, es, CU_TENSOR_MAP_INTERLEAVE_NONE,
        bcols == 32 ? CU_TENSOR_MAP_SWIZZLE_64B : CU_TENSOR_MAP_SWIZZLE_128B, CU_TENSOR_MAP_L2_PROMOTION_L2_128B, CU_TENSOR_MAP_FLOAT_OOB_FILL_NONE);
}
static void enc3d(EncodeFn enc, CUtensorMap* m, const void* p, int rows, int cols, int atom, int brows, int natoms) {
    cuuint64_t dims[3] = {(cuuint64_t)atom, (cuuint64_t)rows, (cuuint64_t)(cols / atom)};
    cuuint64_t strides[2] = {(cuuint64_t)cols * 2, (cuuint64_t)atom * 2};
    cuuint32_t box[3] = {(cuuint32_t)atom, (cuuint32_t)brows, (cuuint32_t)natoms};
    cuuint32_t es[3] = {1, 1, 1};
    enc(m, CU_TENSOR_MAP_DATA_TYPE_BFLOAT16, 3, const_cast<void*>(p), dims, strides, box, es, CU_TENSOR_MAP_INTERLEAVE_NONE,
        atom == 32 ? CU_TENSOR_MAP_SWIZZLE_64B : CU_TENSOR_MAP_SWIZZLE_128B, CU_TENSOR_MAP_L2_PROMOTION_L2_128B, CU_TENSOR_MAP_FLOAT_OOB_FILL_NONE);
}

extern "C" void kernel_launch(void* const* d_in, const int* in_sizes, int n_in, void* d_out, int out_size) {
    const bf16* q = (const bf16*)d_in[0];
    const bf16* k = (const bf16*)d_in[1];
    const bf16* v = (const bf16*)d_in[2];
    const bf16* shift_k = (const bf16*)d_in[3];
    const bf16* ssm_k = (const bf16*)d_in[4];
    const bf16* ssm_D = (const bf16*)d_in[5];
    const bf16* wg = (const bf16*)d_in[7];
    const bf16* wu = (const bf16*)d_in[8];
    const bf16* wd = (const bf16*)d_in[9];
    bf16* out = (bf16*)d_out;

    static EncodeFn enc = nullptr;
    static void *p_hT = nullptr, *p_hh = nullptr;
    if (!enc) {
        void* fn = nullptr; cudaDriverEntryPointQueryResult qr;
        cudaGetDriverEntryPoint("cuTensorMapEncodeTiled", &fn, cudaEnableDefault, &qr);
        enc = (EncodeFn)fn;
        cudaGetSymbolAddress(&p_hT, g_hT);
        cudaGetSymbolAddress(&p_hh, g_hh);
        cudaFuncSetAttribute(conv_kernel, cudaFuncAttributeMaxDynamicSharedMemorySize, (int)sizeof(K1Smem));
        cudaFuncSetAttribute(gemm1_kernel, cudaFuncAttributeMaxDynamicSharedMemorySize, G1_SMEM);
        cudaFuncSetAttribute(gemm2_kernel, cudaFuncAttributeMaxDynamicSharedMemorySize, G2_SMEM);
    }
    CUtensorMap mA, mG64, mU64, mG32, mU32, mHH, mWd, mH;
    enc2d(enc, &mA, p_hT, D_, S_, 64, 64);
    enc2d(enc, &mH, p_hT, D_, S_, 128, 64);
    enc3d(enc, &mG64, wg, D_, F_, 32, 64, 4);
    enc3d(enc, &mU64, wu, D_, F_, 32, 64, 4);
    enc3d(enc, &mG32, wg, D_, F_, 32, 64, 3);
    enc3d(enc, &mU32, wu, D_, F_, 32, 64, 3);
    enc2d(enc, &mHH, p_hh, S_, F_, 128, 64);
    enc3d(enc, &mWd, wd, F_, D_, 64, 64, 2);

    cudaStream_t st = cudaStreamPerThread;
    cudaLaunchAttribute at[1];
    at[0].id = cudaLaunchAttributeProgrammaticStreamSerialization;
    at[0].val.programmaticStreamSerializationAllowed = 1;
    cudaLaunchConfig_t cfg = {};
    cfg.stream = st; cfg.attrs = at; cfg.numAttrs = 1;
    conv_kernel<<<128, K1_THREADS, sizeof(K1Smem), st>>>(q, k, v, shift_k, ssm_k, ssm_D, wg, wu, wd);
    cfg.gridDim = dim3(128); cfg.blockDim = dim3(G1_THREADS); cfg.dynamicSmemBytes = G1_SMEM;
    cudaLaunchKernelEx(&cfg, gemm1_kernel, mA, mG64, mU64, mG32, mU32);
    cfg.gridDim = dim3(128); cfg.blockDim = dim3(G2_THREADS); cfg.dynamicSmemBytes = G2_SMEM;
    cudaLaunchKernelEx(&cfg, gemm2_kernel, mHH, mWd, mH, out);
}
```

```cpp
#include <cuda_runtime.h>
#include <cuda_bf16.h>
#include <cuda.h>
#include <stdint.h>

typedef __nv_bfloat16 bf16;
constexpr int S_ = 2048, D_ = 512, F_ = 1792;

__device__ bf16 g_hT[D_ * S_];
__device__ bf16 g_hh[S_ * F_];
__device__ float2 g_st1[S_];
__device__ float g_colsum[2 * F_];
__device__ unsigned int g_cnt;

#define TM(k, i)
#define TR(k, i)
__device__ __forceinline__ uint32_t smem_u32(const void* p) { return (uint32_t)__cvta_generic_to_shared(p); }
__device__ __forceinline__ float bf16r(float x) { return __bfloat162float(__float2bfloat16_rn(x)); }
__device__ __forceinline__ float bf_lo(uint32_t w) { return __uint_as_float(w << 16); }
__device__ __forceinline__ float bf_hi(uint32_t w) { return __uint_as_float(w & 0xffff0000u); }
__device__ __forceinline__ uint32_t pack_bf16(float lo, float hi) {
    __nv_bfloat162 v = __floats2bfloat162_rn(lo, hi);
    return *reinterpret_cast<uint32_t*>(&v);
}
__device__ __forceinline__ uint32_t hmul2(uint32_t a, uint32_t b) {
    __nv_bfloat162 r = __hmul2_rn(*reinterpret_cast<__nv_bfloat162*>(&a), *reinterpret_cast<__nv_bfloat162*>(&b));
    return *reinterpret_cast<uint32_t*>(&r);
}
__device__ __forceinline__ uint32_t hadd2(uint32_t a, uint32_t b) {
    __nv_bfloat162 r = __hadd2_rn(*reinterpret_cast<__nv_bfloat162*>(&a), *reinterpret_cast<__nv_bfloat162*>(&b));
    return *reinterpret_cast<uint32_t*>(&r);
}
__device__ __forceinline__ uint4 ldg128(const void* p) {
    uint4 r; asm volatile("ld.global.nc.v4.u32 {%0,%1,%2,%3}, [%4];" : "=r"(r.x), "=r"(r.y), "=r"(r.z), "=r"(r.w) : "l"(p)); return r;
}
__device__ __forceinline__ uint4 ldcg128(const void* p) {
    uint4 r; asm volatile("ld.global.cg.v4.u32 {%0,%1,%2,%3}, [%4];" : "=r"(r.x), "=r"(r.y), "=r"(r.z), "=r"(r.w) : "l"(p)); return r;
}
__device__ __forceinline__ uint32_t ldg16(const void* p) {
    unsigned short r; asm volatile("ld.global.nc.u16 %0, [%1];" : "=h"(r) : "l"(p)); return (uint32_t)r;
}
__device__ __forceinline__ void mbar_init(uint32_t bar, int cnt) { asm volatile("mbarrier.init.shared::cta.b64 [%0], %1;" :: "r"(bar), "r"(cnt)); }
__device__ __forceinline__ void mbar_expect_tx(uint32_t bar, uint32_t bytes) { asm volatile("mbarrier.arrive.expect_tx.shared::cta.b64 _, [%0], %1;" :: "r"(bar), "r"(bytes) : "memory"); }
__device__ __forceinline__ void mbar_arrive(uint32_t bar) { asm volatile("mbarrier.arrive.shared::cta.b64 _, [%0];" :: "r"(bar) : "memory"); }
__device__ __forceinline__ void mbar_arrive_cluster(uint32_t bar, uint32_t cta) {
    asm volatile("{\n.reg .b32 ra;\nmapa.shared::cluster.u32 ra, %0, %1;\nmbarrier.arrive.shared::cluster.b64 _, [ra];\n}" :: "r"(bar), "r"(cta) : "memory");
}
__device__ __forceinline__ void mbar_wait(uint32_t bar, uint32_t parity) {
    asm volatile("{\n.reg .pred P1;\nLAB_WAIT:\nmbarrier.try_wait.parity.shared::cta.b64 P1, [%0], %1;\n@P1 bra DONE;\nbra LAB_WAIT;\nDONE:\n}" :: "r"(bar), "r"(parity) : "memory");
}
__device__ __forceinline__ void mbar_wait_cluster(uint32_t bar, uint32_t parity) {
    asm volatile("{\n.reg .pred P1;\nLAB_WAIT:\nmbarrier.try_wait.parity.acquire.cluster.shared::cta.b64 P1, [%0], %1;\n@P1 bra DONE;\nbra LAB_WAIT;\nDONE:\n}" :: "r"(bar), "r"(parity) : "memory");
}
__device__ __forceinline__ void tma_load_2d(uint32_t dst, const CUtensorMap* map, uint32_t bar, int c0, int c1) {
    asm volatile("cp.async.bulk.tensor.2d.shared::cluster.global.mbarrier::complete_tx::bytes [%0], [%1, {%3, %4}], [%2];"
        :: "r"(dst), "l"(map), "r"(bar), "r"(c0), "r"(c1) : "memory");
}
__device__ __forceinline__ void tma_load_2d_mc(uint32_t dst, const CUtensorMap* map, uint32_t bar, int c0, int c1, uint16_t mask) {
    asm volatile("cp.async.bulk.tensor.2d.shared::cluster.global.mbarrier::complete_tx::bytes.multicast::cluster [%0], [%1, {%3, %4}], [%2], %5;"
        :: "r"(dst), "l"(map), "r"(bar), "r"(c0), "r"(c1), "h"(mask) : "memory");
}
__device__ __forceinline__ void tma_load_3d(uint32_t dst, const CUtensorMap* map, uint32_t bar, int c0, int c1, int c2) {
    asm volatile("cp.async.bulk.tensor.3d.shared::cluster.global.mbarrier::complete_tx::bytes [%0], [%1, {%3, %4, %5}], [%2];"
        :: "r"(dst), "l"(map), "r"(bar), "r"(c0), "r"(c1), "r"(c2) : "memory");
}
__device__ __forceinline__ void cluster_arrive() { asm volatile("barrier.cluster.arrive.aligned;" ::: "memory"); }
__device__ __forceinline__ void cluster_arrive_relaxed() { asm volatile("barrier.cluster.arrive.relaxed.aligned;" ::: "memory"); }
__device__ __forceinline__ void cluster_wait() { asm volatile("barrier.cluster.wait.aligned;" ::: "memory"); }
__device__ __forceinline__ uint32_t mapa(uint32_t addr, uint32_t cta) {
    uint32_t r; asm volatile("mapa.shared::cluster.u32 %0, %1, %2;" : "=r"(r) : "r"(addr), "r"(cta)); return r;
}
__device__ __forceinline__ void st_async_v2(uint32_t addr, uint32_t a, uint32_t b, uint32_t rbar) {
    asm volatile("st.async.weak.shared::cluster.mbarrier::complete_tx::bytes.v2.b32 [%0], {%1, %2}, [%3];" :: "r"(addr), "r"(a), "r"(b), "r"(rbar) : "memory");
}
__device__ __forceinline__ void st_async_v4f(uint32_t addr, float a, float b, float c, float d, uint32_t rbar) {
    asm volatile("st.async.weak.shared::cluster.mbarrier::complete_tx::bytes.v4.f32 [%0], {%1, %2, %3, %4}, [%5];" :: "r"(addr), "f"(a), "f"(b), "f"(c), "f"(d), "r"(rbar) : "memory");
}
__device__ __forceinline__ void wgmma_fence() { asm volatile("wgmma.fence.sync.aligned;" ::: "memory"); }
__device__ __forceinline__ void wgmma_commit() { asm volatile("wgmma.commit_group.sync.aligned;" ::: "memory"); }
template <int N> __device__ __forceinline__ void wgmma_wait() { asm volatile("wgmma.wait_group.sync.aligned %0;" :: "n"(N) : "memory"); }
__device__ __forceinline__ uint64_t make_desc(uint32_t addr, uint32_t lbo_bytes, uint32_t sbo_bytes, uint32_t layout) {
    return (uint64_t)((addr & 0x3FFFF) >> 4) | ((uint64_t)(lbo_bytes >> 4) << 16) | ((uint64_t)(sbo_bytes >> 4) << 32) | ((uint64_t)layout << 62);
}
template <int R> __device__ __forceinline__ void reg_alloc() { asm volatile("setmaxnreg.inc.sync.aligned.u32 %0;" :: "n"(R)); }
template <int R> __device__ __forceinline__ void reg_dealloc() { asm volatile("setmaxnreg.dec.sync.aligned.u32 %0;" :: "n"(R)); }
__device__ __forceinline__ void pdl_launch() { asm volatile("griddepcontrol.launch_dependents;" ::: "memory"); }
__device__ __forceinline__ void pdl_wait() { asm volatile("griddepcontrol.wait;" ::: "memory"); }
__device__ __forceinline__ void prefetch_map(const CUtensorMap* m) { asm volatile("prefetch.tensormap [%0];" :: "l"(m) : "memory"); }
__device__ __forceinline__ void named_bar(int id, int n) { asm volatile("bar.sync %0, %1;" :: "r"(id), "r"(n) : "memory"); }

__device__ __forceinline__ void wgmma_m64n256k16_ss(float (&d)[128], uint64_t descA, uint64_t descB, int scaleD) {
    asm volatile("{\n.reg .pred p;\nsetp.ne.b32 p, %130, 0;\n"
        "wgmma.mma_async.sync.aligned.m64n256k16.f32.bf16.bf16 {%0, %1, %2, %3, %4, %5, %6, %7, %8, %9, %10, %11, %12, %13, %14, %15, %16, %17, %18, %19, %20, %21, %22, %23, %24, %25, %26, %27, %28, %29, %30, %31, %32, %33, %34, %35, %36, %37, %38, %39, %40, %41, %42, %43, %44, %45, %46, %47, %48, %49, %50, %51, %52, %53, %54, %55, %56, %57, %58, %59, %60, %61, %62, %63, %64, %65, %66, %67, %68, %69, %70, %71, %72, %73, %74, %75, %76, %77, %78, %79, %80, %81, %82, %83, %84, %85, %86, %87, %88, %89, %90, %91, %92, %93, %94, %95, %96, %97, %98, %99, %100, %101, %102, %103, %104, %105, %106, %107, %108, %109, %110, %111, %112, %113, %114, %115, %116, %117, %118, %119, %120, %121, %122, %123, %124, %125, %126, %127}, %128, %129, p, 1, 1, 1, 1;\n}\n"
        : "+f"(d[0]), "+f"(d[1]), "+f"(d[2]), "+f"(d[3]), "+f"(d[4]), "+f"(d[5]), "+f"(d[6]), "+f"(d[7]), "+f"(d[8]), "+f"(d[9]), "+f"(d[10]), "+f"(d[11]), "+f"(d[12]), "+f"(d[13]), "+f"(d[14]), "+f"(d[15]), "+f"(d[16]), "+f"(d[17]), "+f"(d[18]), "+f"(d[19]), "+f"(d[20]), "+f"(d[21]), "+f"(d[22]), "+f"(d[23]), "+f"(d[24]), "+f"(d[25]), "+f"(d[26]), "+f"(d[27]), "+f"(d[28]), "+f"(d[29]), "+f"(d[30]), "+f"(d[31]), "+f"(d[32]), "+f"(d[33]), "+f"(d[34]), "+f"(d[35]), "+f"(d[36]), "+f"(d[37]), "+f"(d[38]), "+f"(d[39]), "+f"(d[40]), "+f"(d[41]), "+f"(d[42]), "+f"(d[43]), "+f"(d[44]), "+f"(d[45]), "+f"(d[46]), "+f"(d[47]), "+f"(d[48]), "+f"(d[49]), "+f"(d[50]), "+f"(d[51]), "+f"(d[52]), "+f"(d[53]), "+f"(d[54]), "+f"(d[55]), "+f"(d[56]), "+f"(d[57]), "+f"(d[58]), "+f"(d[59]), "+f"(d[60]), "+f"(d[61]), "+f"(d[62]), "+f"(d[63]), "+f"(d[64]), "+f"(d[65]), "+f"(d[66]), "+f"(d[67]), "+f"(d[68]), "+f"(d[69]), "+f"(d[70]), "+f"(d[71]), "+f"(d[72]), "+f"(d[73]), "+f"(d[74]), "+f"(d[75]), "+f"(d[76]), "+f"(d[77]), "+f"(d[78]), "+f"(d[79]), "+f"(d[80]), "+f"(d[81]), "+f"(d[82]), "+f"(d[83]), "+f"(d[84]), "+f"(d[85]), "+f"(d[86]), "+f"(d[87]), "+f"(d[88]), "+f"(d[89]), "+f"(d[90]), "+f"(d[91]), "+f"(d[92]), "+f"(d[93]), "+f"(d[94]), "+f"(d[95]), "+f"(d[96]), "+f"(d[97]), "+f"(d[98]), "+f"(d[99]), "+f"(d[100]), "+f"(d[101]), "+f"(d[102]), "+f"(d[103]), "+f"(d[104]), "+f"(d[105]), "+f"(d[106]), "+f"(d[107]), "+f"(d[108]), "+f"(d[109]), "+f"(d[110]), "+f"(d[111]), "+f"(d[112]), "+f"(d[113]), "+f"(d[114]), "+f"(d[115]), "+f"(d[116]), "+f"(d[117]), "+f"(d[118]), "+f"(d[119]), "+f"(d[120]), "+f"(d[121]), "+f"(d[122]), "+f"(d[123]), "+f"(d[124]), "+f"(d[125]), "+f"(d[126]), "+f"(d[127])
        : "l"(descA), "l"(descB), "r"(scaleD));
}

__device__ __forceinline__ void wgmma_m64n192k16_ss(float (&d)[96], uint64_t descA, uint64_t descB, int scaleD) {
    asm volatile("{\n.reg .pred p;\nsetp.ne.b32 p, %98, 0;\n"
        "wgmma.mma_async.sync.aligned.m64n192k16.f32.bf16.bf16 {%0, %1, %2, %3, %4, %5, %6, %7, %8, %9, %10, %11, %12, %13, %14, %15, %16, %17, %18, %19, %20, %21, %22, %23, %24, %25, %26, %27, %28, %29, %30, %31, %32, %33, %34, %35, %36, %37, %38, %39, %40, %41, %42, %43, %44, %45, %46, %47, %48, %49, %50, %51, %52, %53, %54, %55, %56, %57, %58, %59, %60, %61, %62, %63, %64, %65, %66, %67, %68, %69, %70, %71, %72, %73, %74, %75, %76, %77, %78, %79, %80, %81, %82, %83, %84, %85, %86, %87, %88, %89, %90, %91, %92, %93, %94, %95}, %96, %97, p, 1, 1, 1, 1;\n}\n"
        : "+f"(d[0]), "+f"(d[1]), "+f"(d[2]), "+f"(d[3]), "+f"(d[4]), "+f"(d[5]), "+f"(d[6]), "+f"(d[7]), "+f"(d[8]), "+f"(d[9]), "+f"(d[10]), "+f"(d[11]), "+f"(d[12]), "+f"(d[13]), "+f"(d[14]), "+f"(d[15]), "+f"(d[16]), "+f"(d[17]), "+f"(d[18]), "+f"(d[19]), "+f"(d[20]), "+f"(d[21]), "+f"(d[22]), "+f"(d[23]), "+f"(d[24]), "+f"(d[25]), "+f"(d[26]), "+f"(d[27]), "+f"(d[28]), "+f"(d[29]), "+f"(d[30]), "+f"(d[31]), "+f"(d[32]), "+f"(d[33]), "+f"(d[34]), "+f"(d[35]), "+f"(d[36]), "+f"(d[37]), "+f"(d[38]), "+f"(d[39]), "+f"(d[40]), "+f"(d[41]), "+f"(d[42]), "+f"(d[43]), "+f"(d[44]), "+f"(d[45]), "+f"(d[46]), "+f"(d[47]), "+f"(d[48]), "+f"(d[49]), "+f"(d[50]), "+f"(d[51]), "+f"(d[52]), "+f"(d[53]), "+f"(d[54]), "+f"(d[55]), "+f"(d[56]), "+f"(d[57]), "+f"(d[58]), "+f"(d[59]), "+f"(d[60]), "+f"(d[61]), "+f"(d[62]), "+f"(d[63]), "+f"(d[64]), "+f"(d[65]), "+f"(d[66]), "+f"(d[67]), "+f"(d[68]), "+f"(d[69]), "+f"(d[70]), "+f"(d[71]), "+f"(d[72]), "+f"(d[73]), "+f"(d[74]), "+f"(d[75]), "+f"(d[76]), "+f"(d[77]), "+f"(d[78]), "+f"(d[79]), "+f"(d[80]), "+f"(d[81]), "+f"(d[82]), "+f"(d[83]), "+f"(d[84]), "+f"(d[85]), "+f"(d[86]), "+f"(d[87]), "+f"(d[88]), "+f"(d[89]), "+f"(d[90]), "+f"(d[91]), "+f"(d[92]), "+f"(d[93]), "+f"(d[94]), "+f"(d[95])
        : "l"(descA), "l"(descB), "r"(scaleD));
}

__device__ __forceinline__ void wgmma_m64n128k16_ss(float (&d)[64], uint64_t descA, uint64_t descB, int scaleD) {
    asm volatile("{\n.reg .pred p;\nsetp.ne.b32 p, %66, 0;\n"
        "wgmma.mma_async.sync.aligned.m64n128k16.f32.bf16.bf16 {%0, %1, %2, %3, %4, %5, %6, %7, %8, %9, %10, %11, %12, %13, %14, %15, %16, %17, %18, %19, %20, %21, %22, %23, %24, %25, %26, %27, %28, %29, %30, %31, %32, %33, %34, %35, %36, %37, %38, %39, %40, %41, %42, %43, %44, %45, %46, %47, %48, %49, %50, %51, %52, %53, %54, %55, %56, %57, %58, %59, %60, %61, %62, %63}, %64, %65, p, 1, 1, 0, 1;\n}\n"
        : "+f"(d[0]), "+f"(d[1]), "+f"(d[2]), "+f"(d[3]), "+f"(d[4]), "+f"(d[5]), "+f"(d[6]), "+f"(d[7]), "+f"(d[8]), "+f"(d[9]), "+f"(d[10]), "+f"(d[11]), "+f"(d[12]), "+f"(d[13]), "+f"(d[14]), "+f"(d[15]), "+f"(d[16]), "+f"(d[17]), "+f"(d[18]), "+f"(d[19]), "+f"(d[20]), "+f"(d[21]), "+f"(d[22]), "+f"(d[23]), "+f"(d[24]), "+f"(d[25]), "+f"(d[26]), "+f"(d[27]), "+f"(d[28]), "+f"(d[29]), "+f"(d[30]), "+f"(d[31]), "+f"(d[32]), "+f"(d[33]), "+f"(d[34]), "+f"(d[35]), "+f"(d[36]), "+f"(d[37]), "+f"(d[38]), "+f"(d[39]), "+f"(d[40]), "+f"(d[41]), "+f"(d[42]), "+f"(d[43]), "+f"(d[44]), "+f"(d[45]), "+f"(d[46]), "+f"(d[47]), "+f"(d[48]), "+f"(d[49]), "+f"(d[50]), "+f"(d[51]), "+f"(d[52]), "+f"(d[53]), "+f"(d[54]), "+f"(d[55]), "+f"(d[56]), "+f"(d[57]), "+f"(d[58]), "+f"(d[59]), "+f"(d[60]), "+f"(d[61]), "+f"(d[62]), "+f"(d[63])
        : "l"(descA), "l"(descB), "r"(scaleD));
}

__device__ __forceinline__ void quad_transpose(uint32_t& r0, uint32_t& r1, uint32_t& r2, uint32_t& r3, int t) {
    const bool o1 = t & 1, o2 = t & 2;
    uint32_t x, y;
    x = o1 ? r0 : r1; y = __shfl_xor_sync(0xffffffffu, x, 1); if (o1) r0 = y; else r1 = y;
    x = o1 ? r2 : r3; y = __shfl_xor_sync(0xffffffffu, x, 1); if (o1) r2 = y; else r3 = y;
    x = o2 ? r0 : r2; y = __shfl_xor_sync(0xffffffffu, x, 2); if (o2) r0 = y; else r2 = y;
    x = o2 ? r1 : r3; y = __shfl_xor_sync(0xffffffffu, x, 2); if (o2) r1 = y; else r3 = y;
}

__device__ __forceinline__ float warp_sum(float s) {
#pragma unroll
    for (int o = 16; o > 0; o >>= 1) s += __shfl_xor_sync(0xffffffffu, s, o);
    return s;
}
__device__ __forceinline__ uint32_t hsub2(uint32_t a, uint32_t b) {
    __nv_bfloat162 r = __hsub2_rn(*reinterpret_cast<__nv_bfloat162*>(&a), *reinterpret_cast<__nv_bfloat162*>(&b));
    return *reinterpret_cast<uint32_t*>(&r);
}
__device__ __forceinline__ void ln_stats2(const uint32_t (&x)[2][8], float2 (&st)[2]) {
    float piv[2], s[2], ss[2];
#pragma unroll
    for (int r = 0; r < 2; r++) piv[r] = __shfl_sync(0xffffffffu, bf_lo(x[r][0]), 0);
#pragma unroll
    for (int r = 0; r < 2; r++) {
        float s0 = 0.f, s1 = 0.f, q0 = 0.f, q1 = 0.f;
#pragma unroll
        for (int i = 0; i < 8; i++) {
            const float d0 = bf_lo(x[r][i]) - piv[r], d1 = bf_hi(x[r][i]) - piv[r];
            s0 += d0; s1 += d1; q0 = fmaf(d0, d0, q0); q1 = fmaf(d1, d1, q1);
        }
        s[r] = s0 + s1; ss[r] = q0 + q1;
    }
#pragma unroll
    for (int o = 16; o > 0; o >>= 1) {
#pragma unroll
        for (int r = 0; r < 2; r++) { s[r] += __shfl_xor_sync(0xffffffffu, s[r], o); ss[r] += __shfl_xor_sync(0xffffffffu, ss[r], o); }
    }
#pragma unroll
    for (int r = 0; r < 2; r++) {
        const float md = s[r] * (1.0f / D_);
        const float var = bf16r(fmaxf(fmaf(-md, md, ss[r] * (1.0f / D_)), 0.f));
        st[r] = make_float2(bf16r(piv[r] + md), 1.0f / bf16r(sqrtf(bf16r(var + 1e-5f))));
    }
}
__device__ __forceinline__ void ln_apply(const uint32_t (&x)[8], float2 st, uint32_t (&o)[8]) {
    const uint32_t m2 = pack_bf16(st.x, st.x);
#pragma unroll
    for (int i = 0; i < 8; i++) {
        const uint32_t d = hsub2(x[i], m2);
        o[i] = pack_bf16(bf_lo(d) * st.y, bf_hi(d) * st.y);
    }
}

constexpr int K1_THREADS = 288;
constexpr int UT_PAD = 128;
constexpr int UT_LEN = UT_PAD + S_;
constexpr int KR_LEN = 2080;
constexpr int YP_LEN = S_ + (S_ / 32) * 8;

struct __align__(128) K1Smem {
    bf16 uT[4][UT_LEN];
    bf16 xT[4][S_];
    bf16 kr[4][2][KR_LEN];
    float yP[4][YP_LEN];
    alignas(128) float2 st[S_];
    alignas(128) uint4 wS[512][4];
    float red[8][32];
    uint64_t bar, bar2, bar3, bar4;
};

__device__ __forceinline__ void mma16816(float (&c)[4], uint32_t a0, uint32_t a1, uint32_t a2, uint32_t a3, uint32_t b0, uint32_t b1) {
    asm("mma.sync.aligned.m16n8k16.row.col.f32.bf16.bf16.f32 {%0,%1,%2,%3}, {%4,%5,%6,%7}, {%8,%9}, {%0,%1,%2,%3};"
        : "+f"(c[0]), "+f"(c[1]), "+f"(c[2]), "+f"(c[3])
        : "r"(a0), "r"(a1), "r"(a2), "r"(a3), "r"(b0), "r"(b1));
}
__device__ __forceinline__ void ldsm_x4(uint32_t& r0, uint32_t& r1, uint32_t& r2, uint32_t& r3, uint32_t addr) {
    asm volatile("ldmatrix.sync.aligned.m8n8.x4.shared.b16 {%0,%1,%2,%3}, [%4];" : "=r"(r0), "=r"(r1), "=r"(r2), "=r"(r3) : "r"(addr) : "memory");
}

__device__ __forceinline__ void conv_mma(const bf16* uTc, const bf16* krlane, float (&acc)[16][4], int lane, int half) {
    const int lrow = lane & 7, lk = (lane >> 3) & 1, lt = lane >> 4;
    const uint32_t ubase = smem_u32(uTc) + (UT_PAD + 16 * (8 * lt + lrow) + 8 * lk) * 2;
#pragma unroll 1
    for (int pp = 0; pp < 4; pp++) {
        const int p = half * 4 + pp;
        uint32_t U[16][2];
#pragma unroll
        for (int j = 0; j < 16; j += 2) ldsm_x4(U[j][0], U[j][1], U[j + 1][0], U[j + 1][1], ubase + (j * 128 - p * 16) * 2);
        const uint32_t* kp = reinterpret_cast<const uint32_t*>(krlane - 16 * p);
        const volatile uint32_t* kpv = kp;
        uint32_t a0 = kp[0], a1 = kp[-4], a2 = kp[4], a3 = kpv[0];
#pragma unroll
        for (int q = 0; q < 16; q++) {
            uint32_t b0 = 0, b1 = 0, b2 = 0, b3 = 0;
            if (q < 15) { b0 = kp[-64 * (q + 1)]; b1 = kp[-64 * (q + 1) - 4]; b2 = kp[-64 * (q + 1) + 4]; b3 = kpv[-64 * (q + 1)]; }
#pragma unroll
            for (int n = 15; n >= q; n--) mma16816(acc[n], a0, a1, a2, a3, U[n - q][0], U[n - q][1]);
            a0 = b0; a1 = b1; a2 = b2; a3 = b3;
        }
    }
}

__device__ __forceinline__ void cp_async16(uint32_t dst, const void* src) {
    asm volatile("cp.async.cg.shared.global [%0], [%1], 16;" :: "r"(dst), "l"(src) : "memory");
}

__global__ void __cluster_dims__(2, 1, 1) __launch_bounds__(K1_THREADS, 1)
conv_kernel(const bf16* __restrict__ q, const bf16* __restrict__ k, const bf16* __restrict__ v,
            const bf16* __restrict__ shift_k, const bf16* __restrict__ ssm_k, const bf16* __restrict__ ssm_D,
            const __grid_constant__ CUtensorMap mapWg, const __grid_constant__ CUtensorMap mapWu, const bf16* __restrict__ wd) {
    extern __shared__ __align__(1024) uint8_t smem_raw[];
    pdl_launch();
    K1Smem& sm = *reinterpret_cast<K1Smem*>(smem_raw);
    const int tid = threadIdx.x, lane = tid & 31, warp = tid >> 5;
    const int bid = blockIdx.x;
    const int rank = bid & 1;
    const int c0 = 8 * (bid >> 1);
    const int cown = c0 + 4 * rank;
#define TMT 0
    TM(0, 0);
    const uint32_t bar = smem_u32(&sm.bar);
    if (tid == 0) {
        mbar_init(bar, 1);
        mbar_init(bar + 8, 1);
        mbar_init(bar + 16, 1);
        mbar_init(bar + 24, 1);
        asm volatile("fence.mbarrier_init.release.cluster;" ::: "memory");
        mbar_expect_tx(bar, 1024 * 4 * 2);
        mbar_expect_tx(bar + 8, 1024 * 4 * 2);
    }
    cluster_arrive_relaxed();

    if (warp < 8) {
        const int s0 = 1024 * rank + 4 * tid;
        uint4 kk[7], vv[4], qq[4], sw[4];
#pragma unroll
        for (int i = 0; i < 4; i++) kk[3 + i] = ldg128(k + (size_t)(s0 + i) * D_ + c0);
#pragma unroll
        for (int i = 0; i < 4; i++) vv[i] = ldg128(v + (size_t)(s0 + i) * D_ + c0);
        if (lane == 0) {
#pragma unroll
            for (int i = 0; i < 3; i++) {
                const int s = s0 - 3 + i;
                kk[i] = make_uint4(0, 0, 0, 0);
                if (s >= 0) kk[i] = ldg128(k + (size_t)s * D_ + c0);
            }
        }
#pragma unroll
        for (int i = 0; i < 4; i++) sw[i] = ldg128(shift_k + (size_t)c0 * 4 + 8 * i);
        uint4 kq[4]; uint32_t nx[4];
#pragma unroll
        for (int c = 0; c < 4; c++) {
            const bf16* kr = ssm_k + (size_t)(cown + c) * S_;
            kq[c] = ldg128(kr + 8 * tid);
            nx[c] = 0u;
            if (tid < 255) nx[c] = ldg16(kr + 8 * tid + 8);
        }
        const uint32_t dval = ldg16(ssm_D + cown + (warp >> 1));
        if (tid < 64) *reinterpret_cast<uint4*>(&sm.uT[tid >> 4][(tid & 15) * 8]) = make_uint4(0, 0, 0, 0);
#pragma unroll
        for (int i = 0; i < 3; i++) {
            uint4 t;
            t.x = __shfl_up_sync(0xffffffffu, kk[4 + i].x, 1); t.y = __shfl_up_sync(0xffffffffu, kk[4 + i].y, 1);
            t.z = __shfl_up_sync(0xffffffffu, kk[4 + i].z, 1); t.w = __shfl_up_sync(0xffffffffu, kk[4 + i].w, 1);
            if (lane != 0) kk[i] = t;
        }
        uint32_t kvw[4][4];
        const uint32_t* kkw = reinterpret_cast<const uint32_t*>(kk);
        const uint32_t* vvw = reinterpret_cast<const uint32_t*>(vv);
        const uint32_t* qqw = reinterpret_cast<const uint32_t*>(qq);
#pragma unroll
        for (int i2 = 0; i2 < 4; i2++) {
            const uint32_t t0 = __byte_perm(sw[i2].x, sw[i2].z, 0x5410), t1 = __byte_perm(sw[i2].x, sw[i2].z, 0x7632);
            const uint32_t t2 = __byte_perm(sw[i2].y, sw[i2].w, 0x5410), t3 = __byte_perm(sw[i2].y, sw[i2].w, 0x7632);
#pragma unroll
            for (int r = 0; r < 4; r++) {
                uint32_t a = hmul2(kkw[(r + 0) * 4 + i2], t3);
                a = hadd2(a, hmul2(kkw[(r + 1) * 4 + i2], t2));
                a = hadd2(a, hmul2(kkw[(r + 2) * 4 + i2], t1));
                a = hadd2(a, hmul2(kkw[(r + 3) * 4 + i2], t0));
                kvw[r][i2] = hmul2(a, vvw[r * 4 + i2]);
            }
        }
        TM(0, 1);
        cluster_wait();
        const uint32_t rbar = mapa(bar, (uint32_t)(rank ^ 1));
#pragma unroll
        for (int i2 = 0; i2 < 4; i2++) {
#pragma unroll
            for (int e = 0; e < 2; e++) {
                const uint32_t sel = e ? 0x7632 : 0x5410;
                const uint32_t w0 = __byte_perm(kvw[0][i2], kvw[1][i2], sel), w1 = __byte_perm(kvw[2][i2], kvw[3][i2], sel);
                const int cc = 2 * i2 + e;
                if ((cc >> 2) == rank) *reinterpret_cast<uint2*>(&sm.uT[cc & 3][UT_PAD + s0]) = make_uint2(w0, w1);
                else st_async_v2(mapa(smem_u32(&sm.uT[cc & 3][UT_PAD + s0]), (uint32_t)(rank ^ 1)), w0, w1, rbar);
            }
        }
#pragma unroll
        for (int c = 0; c < 4; c++) {
            uint4 a, b;
            a.x = __byte_perm(kq[c].w, 0, 0x1032); a.y = __byte_perm(kq[c].z, 0, 0x1032);
            a.z = __byte_perm(kq[c].y, 0, 0x1032); a.w = __byte_perm(kq[c].x, 0, 0x1032);
            b.x = __byte_perm(nx[c], kq[c].w, 0x7610); b.y = __byte_perm(kq[c].w, kq[c].z, 0x7610);
            b.z = __byte_perm(kq[c].z, kq[c].y, 0x7610); b.w = __byte_perm(kq[c].y, kq[c].x, 0x7610);
            *reinterpret_cast<uint4*>(&sm.kr[c][0][2040 - 8 * tid]) = a;
            *reinterpret_cast<uint4*>(&sm.kr[c][1][2040 - 8 * tid]) = b;
            if (tid == 0) {
                *reinterpret_cast<uint4*>(&sm.kr[c][1][2048]) = make_uint4(kq[c].x & 0xffffu, 0, 0, 0);
            } else if (tid < 8) {
                if (tid < 4) *reinterpret_cast<uint4*>(&sm.kr[c][1][2048 + 8 * tid]) = make_uint4(0, 0, 0, 0);
                else *reinterpret_cast<uint4*>(&sm.kr[c][0][2048 + 8 * (tid - 4)]) = make_uint4(0, 0, 0, 0);
            }
        }
#pragma unroll
        for (int i = 0; i < 4; i++) qq[i] = ldg128(q + (size_t)(s0 + i) * D_ + c0);
        TM(0, 3);
        named_bar(6, 288);
        mbar_wait_cluster(bar, 0);
        TM(0, 4);

        const int ch = warp >> 1, half = warp & 1;
        const int g = lane >> 2, t = lane & 3;
        float acc[16][4];
#pragma unroll
        for (int i = 0; i < 16; i++) { acc[i][0] = acc[i][1] = acc[i][2] = acc[i][3] = 0.f; }
        const bf16* krlane = (g & 1) ? &sm.kr[ch][0][2047 - g + 2 * t] : &sm.kr[ch][1][2048 - g + 2 * t];
        conv_mma(sm.uT[ch], krlane, acc, lane, half);
        TM(0, 5);
#pragma unroll
        for (int i2 = 0; i2 < 4; i2++) {
#pragma unroll
            for (int e = 0; e < 2; e++) {
                const uint32_t sel = e ? 0x7632 : 0x5410;
                const uint32_t w0 = __byte_perm(qqw[i2], qqw[4 + i2], sel), w1 = __byte_perm(qqw[8 + i2], qqw[12 + i2], sel);
                const int cc = 2 * i2 + e;
                if ((cc >> 2) == rank) *reinterpret_cast<uint2*>(&sm.xT[cc & 3][s0]) = make_uint2(w0, w1);
                else st_async_v2(mapa(smem_u32(&sm.xT[cc & 3][s0]), (uint32_t)(rank ^ 1)), w0, w1, rbar + 8);
            }
        }
        float* yp = &sm.yP[ch][40 * t + g];
        if (half) {
#pragma unroll
            for (int n = 0; n < 16; n++) {
                yp[160 * n] = acc[n][0];
                yp[160 * n + 16] = acc[n][1];
                yp[160 * n + 8] = acc[n][2];
                yp[160 * n + 24] = acc[n][3];
            }
        }
        named_bar(1 + ch, 64);
        if (!half) {
#pragma unroll
            for (int n = 0; n < 16; n++) {
                yp[160 * n] += acc[n][0];
                yp[160 * n + 16] += acc[n][1];
                yp[160 * n + 8] += acc[n][2];
                yp[160 * n + 24] += acc[n][3];
            }
        }
        named_bar(7, 288);
        mbar_wait_cluster(bar + 8, 0);
        TM(0, 6);
        {
            const int tt = tid & 63;
            bf16* dst = g_hT + (size_t)(cown + ch) * S_;
            const uint32_t d2 = dval * 0x10001u;
#pragma unroll
            for (int j = 0; j < 4; j++) {
                const int s = (j * 64 + tt) * 8;
                const float* src = &sm.yP[ch][s + (s >> 5) * 8];
                const float4 a = *reinterpret_cast<const float4*>(src), b = *reinterpret_cast<const float4*>(src + 4);
                const uint4 kv4 = *reinterpret_cast<const uint4*>(&sm.uT[ch][UT_PAD + s]);
                const uint4 x4 = *reinterpret_cast<const uint4*>(&sm.xT[ch][s]);
                const uint32_t y2[4] = {hadd2(pack_bf16(a.x, a.y), hmul2(kv4.x, d2)), hadd2(pack_bf16(a.z, a.w), hmul2(kv4.y, d2)),
                                        hadd2(pack_bf16(b.x, b.y), hmul2(kv4.z, d2)), hadd2(pack_bf16(b.z, b.w), hmul2(kv4.w, d2))};
                const uint32_t xw[4] = {x4.x, x4.y, x4.z, x4.w};
                uint32_t o[4];
#pragma unroll
                for (int i = 0; i < 4; i++) {
                    const float4 st = *reinterpret_cast<const float4*>(&sm.st[s + 2 * i]);
                    const uint32_t d = hsub2(xw[i], pack_bf16(st.x, st.z));
                    const uint32_t qn = pack_bf16(bf_lo(d) * st.y, bf_hi(d) * st.w);
                    o[i] = hadd2(xw[i], hmul2(qn, y2[i]));
                }
                *reinterpret_cast<uint4*>(dst + s) = make_uint4(o[0], o[1], o[2], o[3]);
            }
        }
        TM(0, 7);
    } else {
        cluster_wait();
        named_bar(6, 288);
        const uint32_t hbar = bar + 16;
        if (lane == 0) {
            if (bid < 112) {
                mbar_expect_tx(hbar, 32768);
                const CUtensorMap* mw = (bid < 56) ? &mapWg : &mapWu;
                const int col = 32 * ((bid < 56) ? bid : bid - 56);
                tma_load_2d(smem_u32(&sm.wS[0][0]), mw, hbar, col, 0);
                tma_load_2d(smem_u32(&sm.wS[256][0]), mw, hbar, col, 256);
            }
            asm volatile("cp.async.bulk.prefetch.L2.global [%0], %1;" :: "l"(wd + (size_t)bid * 7168), "r"(14336) : "memory");
        }
#pragma unroll 1
        for (int rr = 0; rr < 16; rr += 4) {
            uint32_t xq[2][2][8];
#pragma unroll
            for (int r = 0; r < 4; r++) {
                const uint4 qa = ldg128(q + (size_t)(16 * bid + rr + r) * D_ + 8 * lane);
                const uint4 qb = ldg128(q + (size_t)(16 * bid + rr + r) * D_ + 8 * (lane + 32));
                uint32_t* x = xq[r >> 1][r & 1];
                x[0] = qa.x; x[1] = qa.y; x[2] = qa.z; x[3] = qa.w; x[4] = qb.x; x[5] = qb.y; x[6] = qb.z; x[7] = qb.w;
            }
            float2 sa[2], sb2[2];
            ln_stats2(xq[0], sa);
            ln_stats2(xq[1], sb2);
            if (lane == 0) {
                *reinterpret_cast<float4*>(&g_st1[16 * bid + rr]) = make_float4(sa[0].x, sa[0].y, sa[1].x, sa[1].y);
                *reinterpret_cast<float4*>(&g_st1[16 * bid + rr + 2]) = make_float4(sb2[0].x, sb2[0].y, sb2[1].x, sb2[1].y);
            }
        }
        if (lane == 0) { __threadfence(); atomicAdd(&g_cnt, 1u); }
        if (bid < 112) mbar_wait(hbar, 0);
        if (bid < 112) {
            const int cq = lane & 3, rgp = lane >> 2;
            float cs[8];
#pragma unroll
            for (int i = 0; i < 8; i++) cs[i] = 0.f;
#pragma unroll 4
            for (int r = 0; r < 64; r++) {
                const uint4 w = sm.wS[r * 8 + rgp][cq];
                cs[0] += bf_lo(w.x); cs[1] += bf_hi(w.x); cs[2] += bf_lo(w.y); cs[3] += bf_hi(w.y);
                cs[4] += bf_lo(w.z); cs[5] += bf_hi(w.z); cs[6] += bf_lo(w.w); cs[7] += bf_hi(w.w);
            }
#pragma unroll
            for (int i = 0; i < 8; i++) {
                cs[i] += __shfl_xor_sync(0xffffffffu, cs[i], 4);
                cs[i] += __shfl_xor_sync(0xffffffffu, cs[i], 8);
                cs[i] += __shfl_xor_sync(0xffffffffu, cs[i], 16);
            }
            if (lane < 4) {
                *reinterpret_cast<float4*>(&g_colsum[32 * bid + lane * 8]) = make_float4(cs[0], cs[1], cs[2], cs[3]);
                *reinterpret_cast<float4*>(&g_colsum[32 * bid + lane * 8 + 4]) = make_float4(cs[4], cs[5], cs[6], cs[7]);
            }
        }
        {
            unsigned int c; int spins = 0;
            do { asm volatile("ld.acquire.gpu.global.u32 %0, [%1];" : "=r"(c) : "l"(&g_cnt) : "memory"); } while (c < gridDim.x && ++spins < (1 << 22));
        }
        if (lane == 0) {
            asm volatile("fence.proxy.async;" ::: "memory");
            mbar_expect_tx(hbar + 8, 16384);
            asm volatile("cp.async.bulk.shared::cluster.global.mbarrier::complete_tx::bytes [%0], [%1], %2, [%3];"
                :: "r"(smem_u32(&sm.st[0])), "l"(&g_st1[0]), "r"(16384), "r"(hbar + 8) : "memory");
        }
        mbar_wait(hbar + 8, 0);
        named_bar(7, 288);
    }
#undef TMT
}

constexpr int G1_THREADS = 384;
constexpr int G1_STAGES = 3;
constexpr int G1_A_BYTES = 8 * 16384;
constexpr int G1_B_STAGE = 32768;
constexpr int G1_OFF_B = G1_A_BYTES;
constexpr int G1_OFF_STATS = G1_OFF_B + G1_STAGES * G1_B_STAGE;
constexpr int G1_OFF_CS = G1_OFF_STATS + 1024;
constexpr int G1_OFF_BAR = G1_OFF_CS + 1792;
constexpr int G1_SMEM = G1_OFF_BAR + 128;

__device__ __forceinline__ float tanh_fast(float x) { float t; asm("tanh.approx.f32 %0, %1;" : "=f"(t) : "f"(x)); return t; }

template <int NT>
__device__ __forceinline__ void g1_epilogue(const float (&acc)[NT * 8], const float* cs_g, const float* cs_u, float2 st0, float2 st1, bf16* out0, int t) {
    const float r0 = st0.y, r1 = st1.y, m0 = -st0.x * st0.y, m1 = -st1.x * st1.y;
#pragma unroll
    for (int j0 = 0; j0 < NT; j0 += 4) {
        uint32_t P0[4], P1[4];
#pragma unroll
        for (int jj = 0; jj < 4; jj++) {
            const int j = j0 + jj;
            const float2 cg = *reinterpret_cast<const float2*>(cs_g + 8 * j + 2 * t);
            const float2 cu = *reinterpret_cast<const float2*>(cs_u + 8 * j + 2 * t);
            float r[4];
#pragma unroll
            for (int e = 0; e < 4; e++) {
                const float rr = (e < 2) ? r0 : r1, mm = (e < 2) ? m0 : m1;
                const float gv = fmaf(acc[4 * j + e], rr, mm * ((e & 1) ? cg.y : cg.x));
                const float uv = fmaf(acc[4 * (NT + j) + e], rr, mm * ((e & 1) ? cu.y : cu.x));
                r[e] = fmaf(tanh_fast(0.5f * gv), 0.5f, 0.5f) * uv;
            }
            P0[jj] = pack_bf16(r[0], r[1]);
            P1[jj] = pack_bf16(r[2], r[3]);
        }
        quad_transpose(P0[0], P0[1], P0[2], P0[3], t);
        quad_transpose(P1[0], P1[1], P1[2], P1[3], t);
        *reinterpret_cast<uint4*>(out0 + 8 * (j0 + t)) = make_uint4(P0[0], P0[1], P0[2], P0[3]);
        *reinterpret_cast<uint4*>(out0 + 8 * F_ + 8 * (j0 + t)) = make_uint4(P1[0], P1[1], P1[2], P1[3]);
    }
}

__global__ void __cluster_dims__(2, 1, 1) __launch_bounds__(G1_THREADS, 1)
gemm1_kernel(const __grid_constant__ CUtensorMap mapA, const __grid_constant__ CUtensorMap mapG4, const __grid_constant__ CUtensorMap mapU4,
             const __grid_constant__ CUtensorMap mapG3, const __grid_constant__ CUtensorMap mapU3) {
    extern __shared__ __align__(1024) uint8_t smem_raw[];
    const uint32_t sb = smem_u32(smem_raw);
    const int tid = threadIdx.x, lane = tid & 31, warp = tid >> 5, wgi = tid >> 7;
    const int rank = blockIdx.x & 1;
    const int cb = blockIdx.x & 7, rb = blockIdx.x >> 3;
#define TMT 128
    TM(2, 0);
    pdl_launch();
    if (tid == 32) { prefetch_map(&mapA); prefetch_map(&mapG3); prefetch_map(&mapU3); }
    const uint32_t barA = sb + G1_OFF_BAR;
    const uint32_t barF = barA + 64;
    const uint32_t barE = barF + 8 * G1_STAGES;
    const uint32_t barS = barE + 8 * G1_STAGES;
    if (tid == 0) {
        for (int i = 0; i < 8; i++) mbar_init(barA + 8 * i, 1);
        for (int i = 0; i < G1_STAGES; i++) { mbar_init(barF + 8 * i, 1); mbar_init(barE + 8 * i, 2); }
        mbar_init(barS, 1);
        for (int i = 0; i < 8; i++) mbar_expect_tx(barA + 8 * i, 16384);
        asm volatile("fence.mbarrier_init.release.cluster;" ::: "memory");
    }
    __syncthreads();
    cluster_arrive_relaxed();

    if (wgi == 0) {
        reg_dealloc<40>();
        if (warp == 0) {
            if (lane == 0) {
                int st = 0, ph = 1;
                for (int it = 0; it < 16; it++) {
                    const int kc = it & 7;
                    mbar_wait(barE + 8 * st, ph);
                    const uint32_t dst = sb + G1_OFF_B + st * G1_B_STAGE;
                    if (it < 8) {
                        mbar_expect_tx(barF + 8 * st, 32768);
                        tma_load_3d(dst, &mapG4, barF + 8 * st, 0, kc * 64, cb * 7);
                        tma_load_3d(dst + 16384, &mapU4, barF + 8 * st, 0, kc * 64, cb * 7);
                    } else {
                        mbar_expect_tx(barF + 8 * st, 24576);
                        tma_load_3d(dst, &mapG3, barF + 8 * st, 0, kc * 64, cb * 7 + 4);
                        tma_load_3d(dst + 12288, &mapU3, barF + 8 * st, 0, kc * 64, cb * 7 + 4);
                    }
                    if (++st == G1_STAGES) { st = 0; ph ^= 1; }
                }
            }
            __syncwarp();
            cluster_wait();
        } else if (warp == 1) {
            cluster_wait();
            pdl_wait();
            if (lane < 8) {
                const int c = 2 * (lane >> 1) + rank, mh = lane & 1;
                tma_load_2d_mc(sb + c * 16384 + mh * 8192, &mapA, barA + 8 * c, rb * 128 + mh * 64, c * 64, (uint16_t)3);
            }
            __syncwarp();
            float* cs = reinterpret_cast<float*>(smem_raw + G1_OFF_CS);
            for (int i = lane; i < 448; i += 32) cs[i] = __ldcg((i < 224) ? &g_colsum[cb * 224 + i] : &g_colsum[F_ + cb * 224 + (i - 224)]);
            __syncwarp();
            if (lane == 0) mbar_arrive(barS);
        } else {
            cluster_wait();
        }
    } else {
        reg_alloc<232>();
        cluster_wait();
        const int cw = wgi - 1;
        const int g = lane >> 2, t = lane & 3, wl = warp & 3, tl = tid & 127;
        bf16* outp = g_hh + (size_t)(rb * 128 + cw * 64 + wl * 16 + g) * F_ + cb * 224;
        const float* cs = reinterpret_cast<const float*>(smem_raw + G1_OFF_CS);
        int st = 0, ph = 0;
        float2 st0, st1;
        {
            float acc[128];
            const int kq = lane >> 3, mp = lane & 7;
            const uint8_t* sbase = smem_raw + cw * 8192 + kq * 128 + (mp & 3) * 4;
            const int mc = 2 * wl + (mp >> 2);
            float p0 = 0.f, p1 = 0.f, s0 = 0.f, s1 = 0.f, q0 = 0.f, q1 = 0.f;
#pragma unroll 1
            for (int kc = 0; kc < 8; kc++) {
                mbar_wait(barA + 8 * kc, 0);
                mbar_wait(barF + 8 * st, ph);
                if (tl == 0 && cw == 0) TR(1, kc);
                wgmma_fence();
                const uint32_t aaddr = sb + kc * 16384 + cw * 8192;
                const uint32_t baddr = sb + G1_OFF_B + st * G1_B_STAGE;
#pragma unroll
                for (int kk = 0; kk < 4; kk++)
                    wgmma_m64n256k16_ss(acc, make_desc(aaddr + kk * 2048, 8192, 1024, 1), make_desc(baddr + kk * 1024, 4096, 512, 2), (kc | kk) != 0);
                wgmma_commit();
                if (kc == 0) {
                    const uint32_t w = *reinterpret_cast<const uint32_t*>(smem_raw + cw * 8192 + (mc << 4) + (mp & 3) * 4);
                    p0 = bf_lo(w); p1 = bf_hi(w);
                }
#pragma unroll
                for (int i = 0; i < 16; i++) {
                    const int kr = 4 * i;
                    const uint32_t w = *reinterpret_cast<const uint32_t*>(sbase + kc * 16384 + kr * 128 + ((mc ^ ((kr + kq) & 7)) << 4));
                    const float d0 = bf_lo(w) - p0, d1 = bf_hi(w) - p1;
                    s0 += d0; s1 += d1; q0 = fmaf(d0, d0, q0); q1 = fmaf(d1, d1, q1);
                }
                wgmma_wait<0>();
                if (tl == 0) mbar_arrive(barE + 8 * st);
                if (++st == G1_STAGES) { st = 0; ph ^= 1; }
            }
            TM(2, 1);
            {
#pragma unroll
                for (int o = 8; o <= 16; o <<= 1) {
                    s0 += __shfl_xor_sync(0xffffffffu, s0, o); s1 += __shfl_xor_sync(0xffffffffu, s1, o);
                    q0 += __shfl_xor_sync(0xffffffffu, q0, o); q1 += __shfl_xor_sync(0xffffffffu, q1, o);
                }
                const float md0 = s0 * (1.0f / D_), md1 = s1 * (1.0f / D_);
                const float v0 = bf16r(fmaxf(fmaf(-md0, md0, q0 * (1.0f / D_)), 0.f)), v1 = bf16r(fmaxf(fmaf(-md1, md1, q1 * (1.0f / D_)), 0.f));
                const float ma = bf16r(p0 + md0), mb = bf16r(p1 + md1);
                const float ra = 1.0f / bf16r(sqrtf(bf16r(v0 + 1e-5f))), rbb = 1.0f / bf16r(sqrtf(bf16r(v1 + 1e-5f)));
                const float mA = __shfl_sync(0xffffffffu, ma, g >> 1), mB = __shfl_sync(0xffffffffu, mb, g >> 1);
                const float rA = __shfl_sync(0xffffffffu, ra, g >> 1), rB = __shfl_sync(0xffffffffu, rbb, g >> 1);
                const float mC = __shfl_sync(0xffffffffu, ma, 4 + (g >> 1)), mD = __shfl_sync(0xffffffffu, mb, 4 + (g >> 1));
                const float rC = __shfl_sync(0xffffffffu, ra, 4 + (g >> 1)), rD = __shfl_sync(0xffffffffu, rbb, 4 + (g >> 1));
                st0 = (g & 1) ? make_float2(mB, rB) : make_float2(mA, rA);
                st1 = (g & 1) ? make_float2(mD, rD) : make_float2(mC, rC);
            }
            mbar_wait(barS, 0);
            pdl_wait();
            TM(2, 5);
            g1_epilogue<16>(acc, cs, cs + 224, st0, st1, outp, t);
            TM(2, 2);
        }
        {
            float acc[96];
#pragma unroll 1
            for (int kc = 0; kc < 8; kc++) {
                mbar_wait(barF + 8 * st, ph);
                if (tl == 0 && cw == 0) TR(1, 8 + kc);
                wgmma_fence();
                const uint32_t aaddr = sb + kc * 16384 + cw * 8192;
                const uint32_t baddr = sb + G1_OFF_B + st * G1_B_STAGE;
#pragma unroll
                for (int kk = 0; kk < 4; kk++)
                    wgmma_m64n192k16_ss(acc, make_desc(aaddr + kk * 2048, 8192, 1024, 1), make_desc(baddr + kk * 1024, 4096, 512, 2), (kc | kk) != 0);
                wgmma_commit();
                wgmma_wait<0>();
                if (tl == 0) mbar_arrive(barE + 8 * st);
                if (++st == G1_STAGES) { st = 0; ph ^= 1; }
            }
            TM(2, 3);
            g1_epilogue<12>(acc, cs + 128, cs + 224 + 128, st0, st1, outp + 128, t);
            TM(2, 4);
        }
    }
}

constexpr int G2_THREADS = 384;
constexpr int G2_STAGES = 6;
constexpr int G2_STAGE = 32768;
constexpr int G2_OFF_X = G2_STAGES * G2_STAGE;
constexpr int G2_OFF_BAR = G2_OFF_X + 32768;
constexpr int G2_SMEM = G2_OFF_BAR + 128;
constexpr int G2_KSTEPS = 14;

__device__ __forceinline__ void ldsm_x4_t(uint32_t& r0, uint32_t& r1, uint32_t& r2, uint32_t& r3, uint32_t addr) {
    asm volatile("ldmatrix.sync.aligned.m8n8.x4.trans.shared.b16 {%0,%1,%2,%3}, [%4];" : "=r"(r0), "=r"(r1), "=r"(r2), "=r"(r3) : "r"(addr) : "memory");
}

__global__ void __cluster_dims__(2, 1, 1) __launch_bounds__(G2_THREADS, 1)
gemm2_kernel(const __grid_constant__ CUtensorMap mapHH, const __grid_constant__ CUtensorMap mapWd, const __grid_constant__ CUtensorMap mapH,
             bf16* __restrict__ out) {
    extern __shared__ __align__(1024) uint8_t smem_raw[];
    const uint32_t sb = smem_u32(smem_raw);
    const int tid = threadIdx.x, lane = tid & 31, warp = tid >> 5, wgi = tid >> 7;
    const int ks = blockIdx.x & 1, nb = (blockIdx.x >> 1) & 3, rb = blockIdx.x >> 3;
    TM(3, 0);
    if (tid == 32) { prefetch_map(&mapHH); prefetch_map(&mapH); }
    const uint32_t barF = sb + G2_OFF_BAR;
    const uint32_t barE = barF + 8 * G2_STAGES;
    const uint32_t barX = barE + 8 * G2_STAGES;
    if (tid == 0) {
        for (int i = 0; i < G2_STAGES; i++) { mbar_init(barF + 8 * i, 1); mbar_init(barE + 8 * i, 2); }
        mbar_init(barX, 1);
        asm volatile("fence.mbarrier_init.release.cluster;" ::: "memory");
        mbar_expect_tx(barX, 32768);
        for (int it = 0; it < G2_STAGES; it++) {
            mbar_expect_tx(barF + 8 * it, 32768);
            tma_load_3d(sb + it * G2_STAGE + 16384, &mapWd, barF + 8 * it, 0, ks * 896 + it * 64, nb * 2);
        }
    }
    __syncthreads();
    cluster_arrive_relaxed();

    if (wgi == 0) {
        if (tid == 0) {
            pdl_wait();
            for (int it = 0; it < G2_STAGES; it++)
                tma_load_2d(sb + it * G2_STAGE, &mapHH, barF + 8 * it, ks * 896 + it * 64, rb * 128);
            if (blockIdx.x == 0) g_cnt = 0u;
            int st = 0, ph = 0;
            for (int it = G2_STAGES; it < G2_KSTEPS; it++) {
                mbar_wait(barE + 8 * st, ph);
                const uint32_t dst = sb + st * G2_STAGE;
                const int k0 = ks * 896 + it * 64;
                mbar_expect_tx(barF + 8 * st, 32768);
                tma_load_2d(dst, &mapHH, barF + 8 * st, k0, rb * 128);
                tma_load_3d(dst + 16384, &mapWd, barF + 8 * st, 0, k0, nb * 2);
                if (++st == G2_STAGES) { st = 0; ph ^= 1; }
            }
            mbar_wait(barE + 8 * st, ph);
            mbar_expect_tx(barF + 8 * st, 16384);
            tma_load_2d(sb + st * G2_STAGE, &mapH, barF + 8 * st, rb * 128 + ks * 64, nb * 128);
        }
        __syncwarp();
        cluster_wait();
    } else {
        const int cw = wgi - 1;
        const int g = lane >> 2, t = lane & 3, wl = warp & 3;
        const int tl = tid & 127;
        int st = 0, ph = 0;
        float acc[64];
#pragma unroll 1
        for (int it = 0; it < G2_KSTEPS; it++) {
            mbar_wait(barF + 8 * st, ph);
            if (it == 0) TM(3, 1);
            wgmma_fence();
            const uint32_t aaddr = sb + st * G2_STAGE + cw * 8192;
            const uint32_t baddr = sb + st * G2_STAGE + 16384;
#pragma unroll
            for (int kk = 0; kk < 4; kk++)
                wgmma_m64n128k16_ss(acc, make_desc(aaddr + kk * 32, 16, 1024, 1), make_desc(baddr + kk * 2048, 8192, 1024, 1), (it | kk) != 0);
            wgmma_commit();
            wgmma_wait<0>();
            if (tl == 0) mbar_arrive(barE + 8 * st);
            if (++st == G2_STAGES) { st = 0; ph ^= 1; }
        }
        TM(3, 2);
        cluster_wait();
        if (cw != ks) {
            const uint32_t dst = mapa(sb + G2_OFF_X + tl * 16, (uint32_t)(ks ^ 1));
            const uint32_t rbar = mapa(barX, (uint32_t)(ks ^ 1));
#pragma unroll
            for (int i = 0; i < 16; i++) st_async_v4f(dst + i * 2048, acc[4 * i], acc[4 * i + 1], acc[4 * i + 2], acc[4 * i + 3], rbar);
        } else {
            const float4* xb = reinterpret_cast<const float4*>(smem_raw + G2_OFF_X) + tl;
            const int row0 = rb * 128 + cw * 64 + wl * 16 + g;
            bf16* o0 = out + (size_t)row0 * D_ + nb * 128;
            uint32_t ha[16], hb[16];
            mbar_wait(barF + 8 * st, ph);
            {
                const int chl = 8 * (lane >> 4) + (lane & 7), sb8 = 2 * wl + ((lane >> 3) & 1);
                const uint32_t hbase = sb + st * G2_STAGE + chl * 128 + ((sb8 ^ (lane & 7)) << 4);
#pragma unroll
                for (int j = 0; j < 16; j += 2) ldsm_x4_t(ha[j], hb[j], ha[j + 1], hb[j + 1], hbase + j * 1024);
            }
            mbar_wait_cluster(barX, 0);
            TM(3, 4);
#pragma unroll
            for (int j0 = 0; j0 < 16; j0 += 4) {
                uint32_t P0[4], P1[4];
#pragma unroll
                for (int jj = 0; jj < 4; jj++) {
                    const int j = j0 + jj;
                    const float4 x = xb[j * 128];
                    P0[jj] = hadd2(ha[j], pack_bf16(acc[4 * j] + x.x, acc[4 * j + 1] + x.y));
                    P1[jj] = hadd2(hb[j], pack_bf16(acc[4 * j + 2] + x.z, acc[4 * j + 3] + x.w));
                }
                quad_transpose(P0[0], P0[1], P0[2], P0[3], t);
                quad_transpose(P1[0], P1[1], P1[2], P1[3], t);
                *reinterpret_cast<uint4*>(o0 + 8 * (j0 + t)) = make_uint4(P0[0], P0[1], P0[2], P0[3]);
                *reinterpret_cast<uint4*>(o0 + 8 * D_ + 8 * (j0 + t)) = make_uint4(P1[0], P1[1], P1[2], P1[3]);
            }
        }
        TM(3, 5);
    }
#undef TMT
}

typedef CUresult (*EncodeFn)(CUtensorMap*, CUtensorMapDataType, cuuint32_t, void*, const cuuint64_t*, const cuuint64_t*,
                             const cuuint32_t*, const cuuint32_t*, CUtensorMapInterleave, CUtensorMapSwizzle,
                             CUtensorMapL2promotion, CUtensorMapFloatOOBfill);

static void enc2d(EncodeFn enc, CUtensorMap* m, const void* p, int rows, int cols, int brows, int bcols) {
    cuuint64_t dims[2] = {(cuuint64_t)cols, (cuuint64_t)rows};
    cuuint64_t strides[1] = {(cuuint64_t)cols * 2};
    cuuint32_t box[2] = {(cuuint32_t)bcols, (cuuint32_t)brows};
    cuuint32_t es[2] = {1, 1};
    enc(m, CU_TENSOR_MAP_DATA_TYPE_BFLOAT16, 2, const_cast<void*>(p), dims, strides, box, es, CU_TENSOR_MAP_INTERLEAVE_NONE,
        bcols == 32 ? CU_TENSOR_MAP_SWIZZLE_64B : CU_TENSOR_MAP_SWIZZLE_128B, CU_TENSOR_MAP_L2_PROMOTION_L2_128B, CU_TENSOR_MAP_FLOAT_OOB_FILL_NONE);
}
static void enc2d_plain(EncodeFn enc, CUtensorMap* m, const void* p, int rows, int cols, int brows, int bcols) {
    cuuint64_t dims[2] = {(cuuint64_t)cols, (cuuint64_t)rows};
    cuuint64_t strides[1] = {(cuuint64_t)cols * 2};
    cuuint32_t box[2] = {(cuuint32_t)bcols, (cuuint32_t)brows};
    cuuint32_t es[2] = {1, 1};
    enc(m, CU_TENSOR_MAP_DATA_TYPE_BFLOAT16, 2, const_cast<void*>(p), dims, strides, box, es, CU_TENSOR_MAP_INTERLEAVE_NONE,
        CU_TENSOR_MAP_SWIZZLE_NONE, CU_TENSOR_MAP_L2_PROMOTION_L2_128B, CU_TENSOR_MAP_FLOAT_OOB_FILL_NONE);
}
static void enc3d(EncodeFn enc, CUtensorMap* m, const void* p, int rows, int cols, int atom, int brows, int natoms) {
    cuuint64_t dims[3] = {(cuuint64_t)atom, (cuuint64_t)rows, (cuuint64_t)(cols / atom)};
    cuuint64_t strides[2] = {(cuuint64_t)cols * 2, (cuuint64_t)atom * 2};
    cuuint32_t box[3] = {(cuuint32_t)atom, (cuuint32_t)brows, (cuuint32_t)natoms};
    cuuint32_t es[3] = {1, 1, 1};
    enc(m, CU_TENSOR_MAP_DATA_TYPE_BFLOAT16, 3, const_cast<void*>(p), dims, strides, box, es, CU_TENSOR_MAP_INTERLEAVE_NONE,
        atom == 32 ? CU_TENSOR_MAP_SWIZZLE_64B : CU_TENSOR_MAP_SWIZZLE_128B, CU_TENSOR_MAP_L2_PROMOTION_L2_128B, CU_TENSOR_MAP_FLOAT_OOB_FILL_NONE);
}

extern "C" void kernel_launch(void* const* d_in, const int* in_sizes, int n_in, void* d_out, int out_size) {
    const bf16* q = (const bf16*)d_in[0];
    const bf16* k = (const bf16*)d_in[1];
    const bf16* v = (const bf16*)d_in[2];
    const bf16* shift_k = (const bf16*)d_in[3];
    const bf16* ssm_k = (const bf16*)d_in[4];
    const bf16* ssm_D = (const bf16*)d_in[5];
    const bf16* wg = (const bf16*)d_in[7];
    const bf16* wu = (const bf16*)d_in[8];
    const bf16* wd = (const bf16*)d_in[9];
    bf16* out = (bf16*)d_out;

    static EncodeFn enc = nullptr;
    static void *p_hT = nullptr, *p_hh = nullptr;
    if (!enc) {
        void* fn = nullptr; cudaDriverEntryPointQueryResult qr;
        cudaGetDriverEntryPoint("cuTensorMapEncodeTiled", &fn, cudaEnableDefault, &qr);
        enc = (EncodeFn)fn;
        cudaGetSymbolAddress(&p_hT, g_hT);
        cudaGetSymbolAddress(&p_hh, g_hh);
        cudaFuncSetAttribute(conv_kernel, cudaFuncAttributeMaxDynamicSharedMemorySize, (int)sizeof(K1Smem));
        cudaFuncSetAttribute(gemm1_kernel, cudaFuncAttributeMaxDynamicSharedMemorySize, G1_SMEM);
        cudaFuncSetAttribute(gemm2_kernel, cudaFuncAttributeMaxDynamicSharedMemorySize, G2_SMEM);
    }
    CUtensorMap mA, mG64, mU64, mG32, mU32, mHH, mWd, mH, mWgp, mWup;
    enc2d_plain(enc, &mWgp, wg, D_, F_, 256, 32);
    enc2d_plain(enc, &mWup, wu, D_, F_, 256, 32);
    enc2d(enc, &mA, p_hT, D_, S_, 64, 64);
    enc2d(enc, &mH, p_hT, D_, S_, 128, 64);
    enc3d(enc, &mG64, wg, D_, F_, 32, 64, 4);
    enc3d(enc, &mU64, wu, D_, F_, 32, 64, 4);
    enc3d(enc, &mG32, wg, D_, F_, 32, 64, 3);
    enc3d(enc, &mU32, wu, D_, F_, 32, 64, 3);
    enc2d(enc, &mHH, p_hh, S_, F_, 128, 64);
    enc3d(enc, &mWd, wd, F_, D_, 64, 64, 2);

    cudaStream_t st = cudaStreamPerThread;
    cudaLaunchAttribute at[1];
    at[0].id = cudaLaunchAttributeProgrammaticStreamSerialization;
    at[0].val.programmaticStreamSerializationAllowed = 1;
    cudaLaunchConfig_t cfg = {};
    cfg.stream = st; cfg.attrs = at; cfg.numAttrs = 1;
    conv_kernel<<<128, K1_THREADS, sizeof(K1Smem), st>>>(q, k, v, shift_k, ssm_k, ssm_D, mWgp, mWup, wd);
    cfg.gridDim = dim3(128); cfg.blockDim = dim3(G1_THREADS); cfg.dynamicSmemBytes = G1_SMEM;
    cudaLaunchKernelEx(&cfg, gemm1_kernel, mA, mG64, mU64, mG32, mU32);
    cfg.gridDim = dim3(128); cfg.blockDim = dim3(G2_THREADS); cfg.dynamicSmemBytes = G2_SMEM;
    cudaLaunchKernelEx(&cfg, gemm2_kernel, mHH, mWd, mH, out);
}
```

```cpp
#include <cuda_runtime.h>
#include <cuda_bf16.h>
#include <cuda.h>
#include <stdint.h>

typedef __nv_bfloat16 bf16;
constexpr int S_ = 2048, D_ = 512, F_ = 1792;

__device__ bf16 g_hT[D_ * S_];
__device__ bf16 g_hh[S_ * F_];
__device__ float2 g_st1[S_];
__device__ float g_colsum[2 * F_];
__device__ unsigned int g_cnt;

#define TM(k, i)
#define TR(k, i)
__device__ __forceinline__ uint32_t smem_u32(const void* p) { return (uint32_t)__cvta_generic_to_shared(p); }
__device__ __forceinline__ float bf16r(float x) { return __bfloat162float(__float2bfloat16_rn(x)); }
__device__ __forceinline__ float bf_lo(uint32_t w) { return __uint_as_float(w << 16); }
__device__ __forceinline__ float bf_hi(uint32_t w) { return __uint_as_float(w & 0xffff0000u); }
__device__ __forceinline__ uint32_t pack_bf16(float lo, float hi) {
    __nv_bfloat162 v = __floats2bfloat162_rn(lo, hi);
    return *reinterpret_cast<uint32_t*>(&v);
}
__device__ __forceinline__ uint32_t hmul2(uint32_t a, uint32_t b) {
    __nv_bfloat162 r = __hmul2_rn(*reinterpret_cast<__nv_bfloat162*>(&a), *reinterpret_cast<__nv_bfloat162*>(&b));
    return *reinterpret_cast<uint32_t*>(&r);
}
__device__ __forceinline__ uint32_t hadd2(uint32_t a, uint32_t b) {
    __nv_bfloat162 r = __hadd2_rn(*reinterpret_cast<__nv_bfloat162*>(&a), *reinterpret_cast<__nv_bfloat162*>(&b));
    return *reinterpret_cast<uint32_t*>(&r);
}
__device__ __forceinline__ uint4 ldg128(const void* p) {
    uint4 r; asm volatile("ld.global.nc.v4.u32 {%0,%1,%2,%3}, [%4];" : "=r"(r.x), "=r"(r.y), "=r"(r.z), "=r"(r.w) : "l"(p)); return r;
}
__device__ __forceinline__ uint4 ldcg128(const void* p) {
    uint4 r; asm volatile("ld.global.cg.v4.u32 {%0,%1,%2,%3}, [%4];" : "=r"(r.x), "=r"(r.y), "=r"(r.z), "=r"(r.w) : "l"(p)); return r;
}
__device__ __forceinline__ uint32_t ldg16(const void* p) {
    unsigned short r; asm volatile("ld.global.nc.u16 %0, [%1];" : "=h"(r) : "l"(p)); return (uint32_t)r;
}
__device__ __forceinline__ void mbar_init(uint32_t bar, int cnt) { asm volatile("mbarrier.init.shared::cta.b64 [%0], %1;" :: "r"(bar), "r"(cnt)); }
__device__ __forceinline__ void mbar_expect_tx(uint32_t bar, uint32_t bytes) { asm volatile("mbarrier.arrive.expect_tx.shared::cta.b64 _, [%0], %1;" :: "r"(bar), "r"(bytes) : "memory"); }
__device__ __forceinline__ void mbar_arrive(uint32_t bar) { asm volatile("mbarrier.arrive.shared::cta.b64 _, [%0];" :: "r"(bar) : "memory"); }
__device__ __forceinline__ void mbar_arrive_cluster(uint32_t bar, uint32_t cta) {
    asm volatile("{\n.reg .b32 ra;\nmapa.shared::cluster.u32 ra, %0, %1;\nmbarrier.arrive.shared::cluster.b64 _, [ra];\n}" :: "r"(bar), "r"(cta) : "memory");
}
__device__ __forceinline__ void mbar_wait(uint32_t bar, uint32_t parity) {
    asm volatile("{\n.reg .pred P1;\nLAB_WAIT:\nmbarrier.try_wait.parity.shared::cta.b64 P1, [%0], %1;\n@P1 bra DONE;\nbra LAB_WAIT;\nDONE:\n}" :: "r"(bar), "r"(parity) : "memory");
}
__device__ __forceinline__ void mbar_wait_cluster(uint32_t bar, uint32_t parity) {
    asm volatile("{\n.reg .pred P1;\nLAB_WAIT:\nmbarrier.try_wait.parity.acquire.cluster.shared::cta.b64 P1, [%0], %1;\n@P1 bra DONE;\nbra LAB_WAIT;\nDONE:\n}" :: "r"(bar), "r"(parity) : "memory");
}
__device__ __forceinline__ void tma_load_2d(uint32_t dst, const CUtensorMap* map, uint32_t bar, int c0, int c1) {
    asm volatile("cp.async.bulk.tensor.2d.shared::cluster.global.mbarrier::complete_tx::bytes [%0], [%1, {%3, %4}], [%2];"
        :: "r"(dst), "l"(map), "r"(bar), "r"(c0), "r"(c1) : "memory");
}
__device__ __forceinline__ void tma_load_2d_mc(uint32_t dst, const CUtensorMap* map, uint32_t bar, int c0, int c1, uint16_t mask) {
    asm volatile("cp.async.bulk.tensor.2d.shared::cluster.global.mbarrier::complete_tx::bytes.multicast::cluster [%0], [%1, {%3, %4}], [%2], %5;"
        :: "r"(dst), "l"(map), "r"(bar), "r"(c0), "r"(c1), "h"(mask) : "memory");
}
__device__ __forceinline__ void tma_load_3d(uint32_t dst, const CUtensorMap* map, uint32_t bar, int c0, int c1, int c2) {
    asm volatile("cp.async.bulk.tensor.3d.shared::cluster.global.mbarrier::complete_tx::bytes [%0], [%1, {%3, %4, %5}], [%2];"
        :: "r"(dst), "l"(map), "r"(bar), "r"(c0), "r"(c1), "r"(c2) : "memory");
}
__device__ __forceinline__ void cluster_arrive() { asm volatile("barrier.cluster.arrive.aligned;" ::: "memory"); }
__device__ __forceinline__ void cluster_arrive_relaxed() { asm volatile("barrier.cluster.arrive.relaxed.aligned;" ::: "memory"); }
__device__ __forceinline__ void cluster_wait() { asm volatile("barrier.cluster.wait.aligned;" ::: "memory"); }
__device__ __forceinline__ uint32_t mapa(uint32_t addr, uint32_t cta) {
    uint32_t r; asm volatile("mapa.shared::cluster.u32 %0, %1, %2;" : "=r"(r) : "r"(addr), "r"(cta)); return r;
}
__device__ __forceinline__ void st_async_v2(uint32_t addr, uint32_t a, uint32_t b, uint32_t rbar) {
    asm volatile("st.async.weak.shared::cluster.mbarrier::complete_tx::bytes.v2.b32 [%0], {%1, %2}, [%3];" :: "r"(addr), "r"(a), "r"(b), "r"(rbar) : "memory");
}
__device__ __forceinline__ void st_async_v4f(uint32_t addr, float a, float b, float c, float d, uint32_t rbar) {
    asm volatile("st.async.weak.shared::cluster.mbarrier::complete_tx::bytes.v4.f32 [%0], {%1, %2, %3, %4}, [%5];" :: "r"(addr), "f"(a), "f"(b), "f"(c), "f"(d), "r"(rbar) : "memory");
}
__device__ __forceinline__ void wgmma_fence() { asm volatile("wgmma.fence.sync.aligned;" ::: "memory"); }
__device__ __forceinline__ void wgmma_commit() { asm volatile("wgmma.commit_group.sync.aligned;" ::: "memory"); }
template <int N> __device__ __forceinline__ void wgmma_wait() { asm volatile("wgmma.wait_group.sync.aligned %0;" :: "n"(N) : "memory"); }
__device__ __forceinline__ uint64_t make_desc(uint32_t addr, uint32_t lbo_bytes, uint32_t sbo_bytes, uint32_t layout) {
    return (uint64_t)((addr & 0x3FFFF) >> 4) | ((uint64_t)(lbo_bytes >> 4) << 16) | ((uint64_t)(sbo_bytes >> 4) << 32) | ((uint64_t)layout << 62);
}
template <int R> __device__ __forceinline__ void reg_alloc() { asm volatile("setmaxnreg.inc.sync.aligned.u32 %0;" :: "n"(R)); }
template <int R> __device__ __forceinline__ void reg_dealloc() { asm volatile("setmaxnreg.dec.sync.aligned.u32 %0;" :: "n"(R)); }
__device__ __forceinline__ void pdl_launch() { asm volatile("griddepcontrol.launch_dependents;" ::: "memory"); }
__device__ __forceinline__ void pdl_wait() { asm volatile("griddepcontrol.wait;" ::: "memory"); }
__device__ __forceinline__ void prefetch_map(const CUtensorMap* m) { asm volatile("prefetch.tensormap [%0];" :: "l"(m) : "memory"); }
__device__ __forceinline__ void named_bar(int id, int n) { asm volatile("bar.sync %0, %1;" :: "r"(id), "r"(n) : "memory"); }

__device__ __forceinline__ void wgmma_m64n256k16_ss(float (&d)[128], uint64_t descA, uint64_t descB, int scaleD) {
    asm volatile("{\n.reg .pred p;\nsetp.ne.b32 p, %130, 0;\n"
        "wgmma.mma_async.sync.aligned.m64n256k16.f32.bf16.bf16 {%0, %1, %2, %3, %4, %5, %6, %7, %8, %9, %10, %11, %12, %13, %14, %15, %16, %17, %18, %19, %20, %21, %22, %23, %24, %25, %26, %27, %28, %29, %30, %31, %32, %33, %34, %35, %36, %37, %38, %39, %40, %41, %42, %43, %44, %45, %46, %47, %48, %49, %50, %51, %52, %53, %54, %55, %56, %57, %58, %59, %60, %61, %62, %63, %64, %65, %66, %67, %68, %69, %70, %71, %72, %73, %74, %75, %76, %77, %78, %79, %80, %81, %82, %83, %84, %85, %86, %87, %88, %89, %90, %91, %92, %93, %94, %95, %96, %97, %98, %99, %100, %101, %102, %103, %104, %105, %106, %107, %108, %109, %110, %111, %112, %113, %114, %115, %116, %117, %118, %119, %120, %121, %122, %123, %124, %125, %126, %127}, %128, %129, p, 1, 1, 1, 1;\n}\n"
        : "+f"(d[0]), "+f"(d[1]), "+f"(d[2]), "+f"(d[3]), "+f"(d[4]), "+f"(d[5]), "+f"(d[6]), "+f"(d[7]), "+f"(d[8]), "+f"(d[9]), "+f"(d[10]), "+f"(d[11]), "+f"(d[12]), "+f"(d[13]), "+f"(d[14]), "+f"(d[15]), "+f"(d[16]), "+f"(d[17]), "+f"(d[18]), "+f"(d[19]), "+f"(d[20]), "+f"(d[21]), "+f"(d[22]), "+f"(d[23]), "+f"(d[24]), "+f"(d[25]), "+f"(d[26]), "+f"(d[27]), "+f"(d[28]), "+f"(d[29]), "+f"(d[30]), "+f"(d[31]), "+f"(d[32]), "+f"(d[33]), "+f"(d[34]), "+f"(d[35]), "+f"(d[36]), "+f"(d[37]), "+f"(d[38]), "+f"(d[39]), "+f"(d[40]), "+f"(d[41]), "+f"(d[42]), "+f"(d[43]), "+f"(d[44]), "+f"(d[45]), "+f"(d[46]), "+f"(d[47]), "+f"(d[48]), "+f"(d[49]), "+f"(d[50]), "+f"(d[51]), "+f"(d[52]), "+f"(d[53]), "+f"(d[54]), "+f"(d[55]), "+f"(d[56]), "+f"(d[57]), "+f"(d[58]), "+f"(d[59]), "+f"(d[60]), "+f"(d[61]), "+f"(d[62]), "+f"(d[63]), "+f"(d[64]), "+f"(d[65]), "+f"(d[66]), "+f"(d[67]), "+f"(d[68]), "+f"(d[69]), "+f"(d[70]), "+f"(d[71]), "+f"(d[72]), "+f"(d[73]), "+f"(d[74]), "+f"(d[75]), "+f"(d[76]), "+f"(d[77]), "+f"(d[78]), "+f"(d[79]), "+f"(d[80]), "+f"(d[81]), "+f"(d[82]), "+f"(d[83]), "+f"(d[84]), "+f"(d[85]), "+f"(d[86]), "+f"(d[87]), "+f"(d[88]), "+f"(d[89]), "+f"(d[90]), "+f"(d[91]), "+f"(d[92]), "+f"(d[93]), "+f"(d[94]), "+f"(d[95]), "+f"(d[96]), "+f"(d[97]), "+f"(d[98]), "+f"(d[99]), "+f"(d[100]), "+f"(d[101]), "+f"(d[102]), "+f"(d[103]), "+f"(d[104]), "+f"(d[105]), "+f"(d[106]), "+f"(d[107]), "+f"(d[108]), "+f"(d[109]), "+f"(d[110]), "+f"(d[111]), "+f"(d[112]), "+f"(d[113]), "+f"(d[114]), "+f"(d[115]), "+f"(d[116]), "+f"(d[117]), "+f"(d[118]), "+f"(d[119]), "+f"(d[120]), "+f"(d[121]), "+f"(d[122]), "+f"(d[123]), "+f"(d[124]), "+f"(d[125]), "+f"(d[126]), "+f"(d[127])
        : "l"(descA), "l"(descB), "r"(scaleD));
}

__device__ __forceinline__ void wgmma_m64n192k16_ss(float (&d)[96], uint64_t descA, uint64_t descB, int scaleD) {
    asm volatile("{\n.reg .pred p;\nsetp.ne.b32 p, %98, 0;\n"
        "wgmma.mma_async.sync.aligned.m64n192k16.f32.bf16.bf16 {%0, %1, %2, %3, %4, %5, %6, %7, %8, %9, %10, %11, %12, %13, %14, %15, %16, %17, %18, %19, %20, %21, %22, %23, %24, %25, %26, %27, %28, %29, %30, %31, %32, %33, %34, %35, %36, %37, %38, %39, %40, %41, %42, %43, %44, %45, %46, %47, %48, %49, %50, %51, %52, %53, %54, %55, %56, %57, %58, %59, %60, %61, %62, %63, %64, %65, %66, %67, %68, %69, %70, %71, %72, %73, %74, %75, %76, %77, %78, %79, %80, %81, %82, %83, %84, %85, %86, %87, %88, %89, %90, %91, %92, %93, %94, %95}, %96, %97, p, 1, 1, 1, 1;\n}\n"
        : "+f"(d[0]), "+f"(d[1]), "+f"(d[2]), "+f"(d[3]), "+f"(d[4]), "+f"(d[5]), "+f"(d[6]), "+f"(d[7]), "+f"(d[8]), "+f"(d[9]), "+f"(d[10]), "+f"(d[11]), "+f"(d[12]), "+f"(d[13]), "+f"(d[14]), "+f"(d[15]), "+f"(d[16]), "+f"(d[17]), "+f"(d[18]), "+f"(d[19]), "+f"(d[20]), "+f"(d[21]), "+f"(d[22]), "+f"(d[23]), "+f"(d[24]), "+f"(d[25]), "+f"(d[26]), "+f"(d[27]), "+f"(d[28]), "+f"(d[29]), "+f"(d[30]), "+f"(d[31]), "+f"(d[32]), "+f"(d[33]), "+f"(d[34]), "+f"(d[35]), "+f"(d[36]), "+f"(d[37]), "+f"(d[38]), "+f"(d[39]), "+f"(d[40]), "+f"(d[41]), "+f"(d[42]), "+f"(d[43]), "+f"(d[44]), "+f"(d[45]), "+f"(d[46]), "+f"(d[47]), "+f"(d[48]), "+f"(d[49]), "+f"(d[50]), "+f"(d[51]), "+f"(d[52]), "+f"(d[53]), "+f"(d[54]), "+f"(d[55]), "+f"(d[56]), "+f"(d[57]), "+f"(d[58]), "+f"(d[59]), "+f"(d[60]), "+f"(d[61]), "+f"(d[62]), "+f"(d[63]), "+f"(d[64]), "+f"(d[65]), "+f"(d[66]), "+f"(d[67]), "+f"(d[68]), "+f"(d[69]), "+f"(d[70]), "+f"(d[71]), "+f"(d[72]), "+f"(d[73]), "+f"(d[74]), "+f"(d[75]), "+f"(d[76]), "+f"(d[77]), "+f"(d[78]), "+f"(d[79]), "+f"(d[80]), "+f"(d[81]), "+f"(d[82]), "+f"(d[83]), "+f"(d[84]), "+f"(d[85]), "+f"(d[86]), "+f"(d[87]), "+f"(d[88]), "+f"(d[89]), "+f"(d[90]), "+f"(d[91]), "+f"(d[92]), "+f"(d[93]), "+f"(d[94]), "+f"(d[95])
        : "l"(descA), "l"(descB), "r"(scaleD));
}

__device__ __forceinline__ void wgmma_m64n128k16_ss(float (&d)[64], uint64_t descA, uint64_t descB, int scaleD) {
    asm volatile("{\n.reg .pred p;\nsetp.ne.b32 p, %66, 0;\n"
        "wgmma.mma_async.sync.aligned.m64n128k16.f32.bf16.bf16 {%0, %1, %2, %3, %4, %5, %6, %7, %8, %9, %10, %11, %12, %13, %14, %15, %16, %17, %18, %19, %20, %21, %22, %23, %24, %25, %26, %27, %28, %29, %30, %31, %32, %33, %34, %35, %36, %37, %38, %39, %40, %41, %42, %43, %44, %45, %46, %47, %48, %49, %50, %51, %52, %53, %54, %55, %56, %57, %58, %59, %60, %61, %62, %63}, %64, %65, p, 1, 1, 0, 1;\n}\n"
        : "+f"(d[0]), "+f"(d[1]), "+f"(d[2]), "+f"(d[3]), "+f"(d[4]), "+f"(d[5]), "+f"(d[6]), "+f"(d[7]), "+f"(d[8]), "+f"(d[9]), "+f"(d[10]), "+f"(d[11]), "+f"(d[12]), "+f"(d[13]), "+f"(d[14]), "+f"(d[15]), "+f"(d[16]), "+f"(d[17]), "+f"(d[18]), "+f"(d[19]), "+f"(d[20]), "+f"(d[21]), "+f"(d[22]), "+f"(d[23]), "+f"(d[24]), "+f"(d[25]), "+f"(d[26]), "+f"(d[27]), "+f"(d[28]), "+f"(d[29]), "+f"(d[30]), "+f"(d[31]), "+f"(d[32]), "+f"(d[33]), "+f"(d[34]), "+f"(d[35]), "+f"(d[36]), "+f"(d[37]), "+f"(d[38]), "+f"(d[39]), "+f"(d[40]), "+f"(d[41]), "+f"(d[42]), "+f"(d[43]), "+f"(d[44]), "+f"(d[45]), "+f"(d[46]), "+f"(d[47]), "+f"(d[48]), "+f"(d[49]), "+f"(d[50]), "+f"(d[51]), "+f"(d[52]), "+f"(d[53]), "+f"(d[54]), "+f"(d[55]), "+f"(d[56]), "+f"(d[57]), "+f"(d[58]), "+f"(d[59]), "+f"(d[60]), "+f"(d[61]), "+f"(d[62]), "+f"(d[63])
        : "l"(descA), "l"(descB), "r"(scaleD));
}

__device__ __forceinline__ void quad_transpose(uint32_t& r0, uint32_t& r1, uint32_t& r2, uint32_t& r3, int t) {
    const bool o1 = t & 1, o2 = t & 2;
    uint32_t x, y;
    x = o1 ? r0 : r1; y = __shfl_xor_sync(0xffffffffu, x, 1); if (o1) r0 = y; else r1 = y;
    x = o1 ? r2 : r3; y = __shfl_xor_sync(0xffffffffu, x, 1); if (o1) r2 = y; else r3 = y;
    x = o2 ? r0 : r2; y = __shfl_xor_sync(0xffffffffu, x, 2); if (o2) r0 = y; else r2 = y;
    x = o2 ? r1 : r3; y = __shfl_xor_sync(0xffffffffu, x, 2); if (o2) r1 = y; else r3 = y;
}

__device__ __forceinline__ float warp_sum(float s) {
#pragma unroll
    for (int o = 16; o > 0; o >>= 1) s += __shfl_xor_sync(0xffffffffu, s, o);
    return s;
}
__device__ __forceinline__ uint32_t hsub2(uint32_t a, uint32_t b) {
    __nv_bfloat162 r = __hsub2_rn(*reinterpret_cast<__nv_bfloat162*>(&a), *reinterpret_cast<__nv_bfloat162*>(&b));
    return *reinterpret_cast<uint32_t*>(&r);
}
__device__ __forceinline__ void ln_stats2(const uint32_t (&x)[2][8], float2 (&st)[2]) {
    float piv[2], s[2], ss[2];
#pragma unroll
    for (int r = 0; r < 2; r++) piv[r] = __shfl_sync(0xffffffffu, bf_lo(x[r][0]), 0);
#pragma unroll
    for (int r = 0; r < 2; r++) {
        float s0 = 0.f, s1 = 0.f, q0 = 0.f, q1 = 0.f;
#pragma unroll
        for (int i = 0; i < 8; i++) {
            const float d0 = bf_lo(x[r][i]) - piv[r], d1 = bf_hi(x[r][i]) - piv[r];
            s0 += d0; s1 += d1; q0 = fmaf(d0, d0, q0); q1 = fmaf(d1, d1, q1);
        }
        s[r] = s0 + s1; ss[r] = q0 + q1;
    }
#pragma unroll
    for (int o = 16; o > 0; o >>= 1) {
#pragma unroll
        for (int r = 0; r < 2; r++) { s[r] += __shfl_xor_sync(0xffffffffu, s[r], o); ss[r] += __shfl_xor_sync(0xffffffffu, ss[r], o); }
    }
#pragma unroll
    for (int r = 0; r < 2; r++) {
        const float md = s[r] * (1.0f / D_);
        const float var = bf16r(fmaxf(fmaf(-md, md, ss[r] * (1.0f / D_)), 0.f));
        st[r] = make_float2(bf16r(piv[r] + md), 1.0f / bf16r(sqrtf(bf16r(var + 1e-5f))));
    }
}
__device__ __forceinline__ void ln_apply(const uint32_t (&x)[8], float2 st, uint32_t (&o)[8]) {
    const uint32_t m2 = pack_bf16(st.x, st.x);
#pragma unroll
    for (int i = 0; i < 8; i++) {
        const uint32_t d = hsub2(x[i], m2);
        o[i] = pack_bf16(bf_lo(d) * st.y, bf_hi(d) * st.y);
    }
}

constexpr int K1_THREADS = 320;
constexpr int UT_PAD = 128;
constexpr int UT_LEN = UT_PAD + S_;
constexpr int KR_LEN = 2080;
constexpr int YP_LEN = S_ + (S_ / 32) * 8;

struct __align__(128) K1Smem {
    bf16 uT[4][UT_LEN];
    bf16 xT[4][S_];
    bf16 kr[4][2][KR_LEN];
    float yP[4][YP_LEN];
    alignas(128) float2 st[S_];
    alignas(128) uint4 wS[512][4];
    float red[8][32];
    uint64_t bar, bar2, bar3, bar4;
};

__device__ __forceinline__ void mma16816(float (&c)[4], uint32_t a0, uint32_t a1, uint32_t a2, uint32_t a3, uint32_t b0, uint32_t b1) {
    asm("mma.sync.aligned.m16n8k16.row.col.f32.bf16.bf16.f32 {%0,%1,%2,%3}, {%4,%5,%6,%7}, {%8,%9}, {%0,%1,%2,%3};"
        : "+f"(c[0]), "+f"(c[1]), "+f"(c[2]), "+f"(c[3])
        : "r"(a0), "r"(a1), "r"(a2), "r"(a3), "r"(b0), "r"(b1));
}
__device__ __forceinline__ void ldsm_x4(uint32_t& r0, uint32_t& r1, uint32_t& r2, uint32_t& r3, uint32_t addr) {
    asm volatile("ldmatrix.sync.aligned.m8n8.x4.shared.b16 {%0,%1,%2,%3}, [%4];" : "=r"(r0), "=r"(r1), "=r"(r2), "=r"(r3) : "r"(addr) : "memory");
}

__device__ __forceinline__ void conv_mma(const bf16* uTc, const bf16* krlane, float (&acc)[16][4], int lane, int half) {
    const int lrow = lane & 7, lk = (lane >> 3) & 1, lt = lane >> 4;
    const uint32_t ubase = smem_u32(uTc) + (UT_PAD + 16 * (8 * lt + lrow) + 8 * lk) * 2;
#pragma unroll 1
    for (int pp = 0; pp < 4; pp++) {
        const int p = half * 4 + pp;
        uint32_t U[16][2];
#pragma unroll
        for (int j = 0; j < 16; j += 2) ldsm_x4(U[j][0], U[j][1], U[j + 1][0], U[j + 1][1], ubase + (j * 128 - p * 16) * 2);
        const uint32_t* kp = reinterpret_cast<const uint32_t*>(krlane - 16 * p);
        const volatile uint32_t* kpv = kp;
        uint32_t a0 = kp[0], a1 = kp[-4], a2 = kp[4], a3 = kpv[0];
#pragma unroll
        for (int q = 0; q < 16; q++) {
            uint32_t b0 = 0, b1 = 0, b2 = 0, b3 = 0;
            if (q < 15) { b0 = kp[-64 * (q + 1)]; b1 = kp[-64 * (q + 1) - 4]; b2 = kp[-64 * (q + 1) + 4]; b3 = kpv[-64 * (q + 1)]; }
#pragma unroll
            for (int n = 15; n >= q; n--) mma16816(acc[n], a0, a1, a2, a3, U[n - q][0], U[n - q][1]);
            a0 = b0; a1 = b1; a2 = b2; a3 = b3;
        }
    }
}

__device__ __forceinline__ void cp_async16(uint32_t dst, const void* src) {
    asm volatile("cp.async.cg.shared.global [%0], [%1], 16;" :: "r"(dst), "l"(src) : "memory");
}

__global__ void __cluster_dims__(2, 1, 1) __launch_bounds__(K1_THREADS, 1)
conv_kernel(const bf16* __restrict__ q, const bf16* __restrict__ k, const bf16* __restrict__ v,
            const bf16* __restrict__ shift_k, const bf16* __restrict__ ssm_k, const bf16* __restrict__ ssm_D,
            const __grid_constant__ CUtensorMap mapWg, const __grid_constant__ CUtensorMap mapWu, const bf16* __restrict__ wd) {
    extern __shared__ __align__(1024) uint8_t smem_raw[];
    pdl_launch();
    K1Smem& sm = *reinterpret_cast<K1Smem*>(smem_raw);
    const int tid = threadIdx.x, lane = tid & 31, warp = tid >> 5;
    const int bid = blockIdx.x;
    const int rank = bid & 1;
    const int c0 = 8 * (bid >> 1);
    const int cown = c0 + 4 * rank;
#define TMT 0
    TM(0, 0);
    const uint32_t bar = smem_u32(&sm.bar);
    if (tid == 0) {
        mbar_init(bar, 1);
        mbar_init(bar + 8, 1);
        mbar_init(bar + 16, 1);
        mbar_init(bar + 24, 1);
        asm volatile("fence.mbarrier_init.release.cluster;" ::: "memory");
        mbar_expect_tx(bar, 1024 * 4 * 2);
        mbar_expect_tx(bar + 8, 1024 * 4 * 2);
    }
    cluster_arrive_relaxed();

    if (warp < 8) {
        const int s0 = 1024 * rank + 4 * tid;
        uint4 kk[7], vv[4], qq[4], sw[4];
#pragma unroll
        for (int i = 0; i < 4; i++) kk[3 + i] = ldg128(k + (size_t)(s0 + i) * D_ + c0);
#pragma unroll
        for (int i = 0; i < 4; i++) vv[i] = ldg128(v + (size_t)(s0 + i) * D_ + c0);
        if (lane == 0) {
#pragma unroll
            for (int i = 0; i < 3; i++) {
                const int s = s0 - 3 + i;
                kk[i] = make_uint4(0, 0, 0, 0);
                if (s >= 0) kk[i] = ldg128(k + (size_t)s * D_ + c0);
            }
        }
#pragma unroll
        for (int i = 0; i < 4; i++) sw[i] = ldg128(shift_k + (size_t)c0 * 4 + 8 * i);
        uint4 kq[4]; uint32_t nx[4];
#pragma unroll
        for (int c = 0; c < 4; c++) {
            const bf16* kr = ssm_k + (size_t)(cown + c) * S_;
            kq[c] = ldg128(kr + 8 * tid);
            nx[c] = 0u;
            if (tid < 255) nx[c] = ldg16(kr + 8 * tid + 8);
        }
        const uint32_t dval = ldg16(ssm_D + cown + (warp >> 1));
        if (tid < 64) *reinterpret_cast<uint4*>(&sm.uT[tid >> 4][(tid & 15) * 8]) = make_uint4(0, 0, 0, 0);
#pragma unroll
        for (int i = 0; i < 3; i++) {
            uint4 t;
            t.x = __shfl_up_sync(0xffffffffu, kk[4 + i].x, 1); t.y = __shfl_up_sync(0xffffffffu, kk[4 + i].y, 1);
            t.z = __shfl_up_sync(0xffffffffu, kk[4 + i].z, 1); t.w = __shfl_up_sync(0xffffffffu, kk[4 + i].w, 1);
            if (lane != 0) kk[i] = t;
        }
        uint32_t kvw[4][4];
        const uint32_t* kkw = reinterpret_cast<const uint32_t*>(kk);
        const uint32_t* vvw = reinterpret_cast<const uint32_t*>(vv);
        const uint32_t* qqw = reinterpret_cast<const uint32_t*>(qq);
#pragma unroll
        for (int i2 = 0; i2 < 4; i2++) {
            const uint32_t t0 = __byte_perm(sw[i2].x, sw[i2].z, 0x5410), t1 = __byte_perm(sw[i2].x, sw[i2].z, 0x7632);
            const uint32_t t2 = __byte_perm(sw[i2].y, sw[i2].w, 0x5410), t3 = __byte_perm(sw[i2].y, sw[i2].w, 0x7632);
#pragma unroll
            for (int r = 0; r < 4; r++) {
                uint32_t a = hmul2(kkw[(r + 0) * 4 + i2], t3);
                a = hadd2(a, hmul2(kkw[(r + 1) * 4 + i2], t2));
                a = hadd2(a, hmul2(kkw[(r + 2) * 4 + i2], t1));
                a = hadd2(a, hmul2(kkw[(r + 3) * 4 + i2], t0));
                kvw[r][i2] = hmul2(a, vvw[r * 4 + i2]);
            }
        }
        TM(0, 1);
        cluster_wait();
        const uint32_t rbar = mapa(bar, (uint32_t)(rank ^ 1));
#pragma unroll
        for (int i2 = 0; i2 < 4; i2++) {
#pragma unroll
            for (int e = 0; e < 2; e++) {
                const uint32_t sel = e ? 0x7632 : 0x5410;
                const uint32_t w0 = __byte_perm(kvw[0][i2], kvw[1][i2], sel), w1 = __byte_perm(kvw[2][i2], kvw[3][i2], sel);
                const int cc = 2 * i2 + e;
                if ((cc >> 2) == rank) *reinterpret_cast<uint2*>(&sm.uT[cc & 3][UT_PAD + s0]) = make_uint2(w0, w1);
                else st_async_v2(mapa(smem_u32(&sm.uT[cc & 3][UT_PAD + s0]), (uint32_t)(rank ^ 1)), w0, w1, rbar);
            }
        }
#pragma unroll
        for (int c = 0; c < 4; c++) {
            uint4 a, b;
            a.x = __byte_perm(kq[c].w, 0, 0x1032); a.y = __byte_perm(kq[c].z, 0, 0x1032);
            a.z = __byte_perm(kq[c].y, 0, 0x1032); a.w = __byte_perm(kq[c].x, 0, 0x1032);
            b.x = __byte_perm(nx[c], kq[c].w, 0x7610); b.y = __byte_perm(kq[c].w, kq[c].z, 0x7610);
            b.z = __byte_perm(kq[c].z, kq[c].y, 0x7610); b.w = __byte_perm(kq[c].y, kq[c].x, 0x7610);
            *reinterpret_cast<uint4*>(&sm.kr[c][0][2040 - 8 * tid]) = a;
            *reinterpret_cast<uint4*>(&sm.kr[c][1][2040 - 8 * tid]) = b;
            if (tid == 0) {
                *reinterpret_cast<uint4*>(&sm.kr[c][1][2048]) = make_uint4(kq[c].x & 0xffffu, 0, 0, 0);
            } else if (tid < 8) {
                if (tid < 4) *reinterpret_cast<uint4*>(&sm.kr[c][1][2048 + 8 * tid]) = make_uint4(0, 0, 0, 0);
                else *reinterpret_cast<uint4*>(&sm.kr[c][0][2048 + 8 * (tid - 4)]) = make_uint4(0, 0, 0, 0);
            }
        }
#pragma unroll
        for (int i = 0; i < 4; i++) qq[i] = ldg128(q + (size_t)(s0 + i) * D_ + c0);
        TM(0, 3);
        named_bar(6, 320);
        mbar_wait_cluster(bar, 0);
        TM(0, 4);

        const int ch = warp >> 1, half = warp & 1;
        const int g = lane >> 2, t = lane & 3;
        float acc[16][4];
#pragma unroll
        for (int i = 0; i < 16; i++) { acc[i][0] = acc[i][1] = acc[i][2] = acc[i][3] = 0.f; }
        const bf16* krlane = (g & 1) ? &sm.kr[ch][0][2047 - g + 2 * t] : &sm.kr[ch][1][2048 - g + 2 * t];
        conv_mma(sm.uT[ch], krlane, acc, lane, half);
        TM(0, 5);
#pragma unroll
        for (int i2 = 0; i2 < 4; i2++) {
#pragma unroll
            for (int e = 0; e < 2; e++) {
                const uint32_t sel = e ? 0x7632 : 0x5410;
                const uint32_t w0 = __byte_perm(qqw[i2], qqw[4 + i2], sel), w1 = __byte_perm(qqw[8 + i2], qqw[12 + i2], sel);
                const int cc = 2 * i2 + e;
                if ((cc >> 2) == rank) *reinterpret_cast<uint2*>(&sm.xT[cc & 3][s0]) = make_uint2(w0, w1);
                else st_async_v2(mapa(smem_u32(&sm.xT[cc & 3][s0]), (uint32_t)(rank ^ 1)), w0, w1, rbar + 8);
            }
        }
        float* yp = &sm.yP[ch][40 * t + g];
        if (half) {
#pragma unroll
            for (int n = 0; n < 16; n++) {
                yp[160 * n] = acc[n][0];
                yp[160 * n + 16] = acc[n][1];
                yp[160 * n + 8] = acc[n][2];
                yp[160 * n + 24] = acc[n][3];
            }
        }
        named_bar(1 + ch, 64);
        if (!half) {
#pragma unroll
            for (int n = 0; n < 16; n++) {
                yp[160 * n] += acc[n][0];
                yp[160 * n + 16] += acc[n][1];
                yp[160 * n + 8] += acc[n][2];
                yp[160 * n + 24] += acc[n][3];
            }
        }
        named_bar(7, 288);
        mbar_wait_cluster(bar + 8, 0);
        TM(0, 6);
        {
            const int tt = tid & 63;
            bf16* dst = g_hT + (size_t)(cown + ch) * S_;
            const uint32_t d2 = dval * 0x10001u;
#pragma unroll
            for (int j = 0; j < 4; j++) {
                const int s = (j * 64 + tt) * 8;
                const float* src = &sm.yP[ch][s + (s >> 5) * 8];
                const float4 a = *reinterpret_cast<const float4*>(src), b = *reinterpret_cast<const float4*>(src + 4);
                const uint4 kv4 = *reinterpret_cast<const uint4*>(&sm.uT[ch][UT_PAD + s]);
                const uint4 x4 = *reinterpret_cast<const uint4*>(&sm.xT[ch][s]);
                const uint32_t y2[4] = {hadd2(pack_bf16(a.x, a.y), hmul2(kv4.x, d2)), hadd2(pack_bf16(a.z, a.w), hmul2(kv4.y, d2)),
                                        hadd2(pack_bf16(b.x, b.y), hmul2(kv4.z, d2)), hadd2(pack_bf16(b.z, b.w), hmul2(kv4.w, d2))};
                const uint32_t xw[4] = {x4.x, x4.y, x4.z, x4.w};
                uint32_t o[4];
#pragma unroll
                for (int i = 0; i < 4; i++) {
                    const float4 st = *reinterpret_cast<const float4*>(&sm.st[s + 2 * i]);
                    const uint32_t d = hsub2(xw[i], pack_bf16(st.x, st.z));
                    const uint32_t qn = pack_bf16(bf_lo(d) * st.y, bf_hi(d) * st.w);
                    o[i] = hadd2(xw[i], hmul2(qn, y2[i]));
                }
                *reinterpret_cast<uint4*>(dst + s) = make_uint4(o[0], o[1], o[2], o[3]);
            }
        }
        TM(0, 7);
    } else {
        cluster_wait();
        named_bar(6, 320);
        const uint32_t hbar = bar + 16;
        if (warp == 8) {
#pragma unroll 1
            for (int rr = 0; rr < 16; rr += 8) {
                uint32_t xq[4][2][8];
#pragma unroll
                for (int r = 0; r < 8; r++) {
                    const uint4 qa = ldg128(q + (size_t)(16 * bid + rr + r) * D_ + 8 * lane);
                    const uint4 qb = ldg128(q + (size_t)(16 * bid + rr + r) * D_ + 8 * (lane + 32));
                    uint32_t* x = xq[r >> 1][r & 1];
                    x[0] = qa.x; x[1] = qa.y; x[2] = qa.z; x[3] = qa.w; x[4] = qb.x; x[5] = qb.y; x[6] = qb.z; x[7] = qb.w;
                }
#pragma unroll
                for (int r2 = 0; r2 < 4; r2++) {
                    float2 sa[2];
                    ln_stats2(xq[r2], sa);
                    if (lane == 0) *reinterpret_cast<float4*>(&g_st1[16 * bid + rr + 2 * r2]) = make_float4(sa[0].x, sa[0].y, sa[1].x, sa[1].y);
                }
            }
            if (lane == 0) { __threadfence(); atomicAdd(&g_cnt, 1u); }
            {
                unsigned int c; int spins = 0;
                do { asm volatile("ld.acquire.gpu.global.u32 %0, [%1];" : "=r"(c) : "l"(&g_cnt) : "memory"); } while (c < gridDim.x && ++spins < (1 << 22));
            }
            if (lane == 0) {
                asm volatile("fence.proxy.async;" ::: "memory");
                mbar_expect_tx(hbar + 8, 16384);
                asm volatile("cp.async.bulk.shared::cluster.global.mbarrier::complete_tx::bytes [%0], [%1], %2, [%3];"
                    :: "r"(smem_u32(&sm.st[0])), "l"(&g_st1[0]), "r"(16384), "r"(hbar + 8) : "memory");
            }
            mbar_wait(hbar + 8, 0);
            named_bar(7, 288);
        } else {
            if (lane == 0) asm volatile("cp.async.bulk.prefetch.L2.global [%0], %1;" :: "l"(wd + (size_t)bid * 7168), "r"(14336) : "memory");
            if (bid < 112) {
                if (lane == 0) {
                    mbar_expect_tx(hbar, 32768);
                    const CUtensorMap* mw = (bid < 56) ? &mapWg : &mapWu;
                    const int col = 32 * ((bid < 56) ? bid : bid - 56);
                    tma_load_2d(smem_u32(&sm.wS[0][0]), mw, hbar, col, 0);
                    tma_load_2d(smem_u32(&sm.wS[256][0]), mw, hbar, col, 256);
                }
                mbar_wait(hbar, 0);
                const int cq = lane & 3, rgp = lane >> 2;
                float cs[8];
#pragma unroll
                for (int i = 0; i < 8; i++) cs[i] = 0.f;
#pragma unroll 4
                for (int r = 0; r < 64; r++) {
                    const uint4 w = sm.wS[r * 8 + rgp][cq];
                    cs[0] += bf_lo(w.x); cs[1] += bf_hi(w.x); cs[2] += bf_lo(w.y); cs[3] += bf_hi(w.y);
                    cs[4] += bf_lo(w.z); cs[5] += bf_hi(w.z); cs[6] += bf_lo(w.w); cs[7] += bf_hi(w.w);
                }
#pragma unroll
                for (int i = 0; i < 8; i++) {
                    cs[i] += __shfl_xor_sync(0xffffffffu, cs[i], 4);
                    cs[i] += __shfl_xor_sync(0xffffffffu, cs[i], 8);
                    cs[i] += __shfl_xor_sync(0xffffffffu, cs[i], 16);
                }
                if (lane < 4) {
                    *reinterpret_cast<float4*>(&g_colsum[32 * bid + lane * 8]) = make_float4(cs[0], cs[1], cs[2], cs[3]);
                    *reinterpret_cast<float4*>(&g_colsum[32 * bid + lane * 8 + 4]) = make_float4(cs[4], cs[5], cs[6], cs[7]);
                }
            }
        }
    }
#undef TMT
}

constexpr int G1_THREADS = 384;
constexpr int G1_STAGES = 3;
constexpr int G1_A_BYTES = 8 * 16384;
constexpr int G1_B_STAGE = 32768;
constexpr int G1_OFF_B = G1_A_BYTES;
constexpr int G1_OFF_STATS = G1_OFF_B + G1_STAGES * G1_B_STAGE;
constexpr int G1_OFF_CS = G1_OFF_STATS + 1024;
constexpr int G1_OFF_BAR = G1_OFF_CS + 1792;
constexpr int G1_SMEM = G1_OFF_BAR + 128;

__device__ __forceinline__ float tanh_fast(float x) { float t; asm("tanh.approx.f32 %0, %1;" : "=f"(t) : "f"(x)); return t; }

template <int NT>
__device__ __forceinline__ void g1_epilogue(const float (&acc)[NT * 8], const float* cs_g, const float* cs_u, float2 st0, float2 st1, bf16* out0, int t) {
    const float r0 = st0.y, r1 = st1.y, m0 = -st0.x * st0.y, m1 = -st1.x * st1.y;
#pragma unroll
    for (int j0 = 0; j0 < NT; j0 += 4) {
        uint32_t P0[4], P1[4];
#pragma unroll
        for (int jj = 0; jj < 4; jj++) {
            const int j = j0 + jj;
            const float2 cg = *reinterpret_cast<const float2*>(cs_g + 8 * j + 2 * t);
            const float2 cu = *reinterpret_cast<const float2*>(cs_u + 8 * j + 2 * t);
            float r[4];
#pragma unroll
            for (int e = 0; e < 4; e++) {
                const float rr = (e < 2) ? r0 : r1, mm = (e < 2) ? m0 : m1;
                const float gv = fmaf(acc[4 * j + e], rr, mm * ((e & 1) ? cg.y : cg.x));
                const float uv = fmaf(acc[4 * (NT + j) + e], rr, mm * ((e & 1) ? cu.y : cu.x));
                r[e] = fmaf(tanh_fast(0.5f * gv), 0.5f, 0.5f) * uv;
            }
            P0[jj] = pack_bf16(r[0], r[1]);
            P1[jj] = pack_bf16(r[2], r[3]);
        }
        quad_transpose(P0[0], P0[1], P0[2], P0[3], t);
        quad_transpose(P1[0], P1[1], P1[2], P1[3], t);
        *reinterpret_cast<uint4*>(out0 + 8 * (j0 + t)) = make_uint4(P0[0], P0[1], P0[2], P0[3]);
        *reinterpret_cast<uint4*>(out0 + 8 * F_ + 8 * (j0 + t)) = make_uint4(P1[0], P1[1], P1[2], P1[3]);
    }
}

__global__ void __cluster_dims__(2, 1, 1) __launch_bounds__(G1_THREADS, 1)
gemm1_kernel(const __grid_constant__ CUtensorMap mapA, const __grid_constant__ CUtensorMap mapG4, const __grid_constant__ CUtensorMap mapU4,
             const __grid_constant__ CUtensorMap mapG3, const __grid_constant__ CUtensorMap mapU3) {
    extern __shared__ __align__(1024) uint8_t smem_raw[];
    const uint32_t sb = smem_u32(smem_raw);
    const int tid = threadIdx.x, lane = tid & 31, warp = tid >> 5, wgi = tid >> 7;
    const int rank = blockIdx.x & 1;
    const int cb = blockIdx.x & 7, rb = blockIdx.x >> 3;
#define TMT 128
    TM(2, 0);
    pdl_launch();
    if (tid == 32) { prefetch_map(&mapA); prefetch_map(&mapG3); prefetch_map(&mapU3); }
    const uint32_t barA = sb + G1_OFF_BAR;
    const uint32_t barF = barA + 64;
    const uint32_t barE = barF + 8 * G1_STAGES;
    const uint32_t barS = barE + 8 * G1_STAGES;
    if (tid == 0) {
        for (int i = 0; i < 8; i++) mbar_init(barA + 8 * i, 1);
        for (int i = 0; i < G1_STAGES; i++) { mbar_init(barF + 8 * i, 1); mbar_init(barE + 8 * i, 2); }
        mbar_init(barS, 1);
        for (int i = 0; i < 8; i++) mbar_expect_tx(barA + 8 * i, 16384);
        asm volatile("fence.mbarrier_init.release.cluster;" ::: "memory");
    }
    __syncthreads();
    cluster_arrive_relaxed();

    if (wgi == 0) {
        reg_dealloc<40>();
        if (warp == 0) {
            if (lane == 0) {
                int st = 0, ph = 1;
                for (int it = 0; it < 16; it++) {
                    const int kc = it & 7;
                    mbar_wait(barE + 8 * st, ph);
                    const uint32_t dst = sb + G1_OFF_B + st * G1_B_STAGE;
                    if (it < 8) {
                        mbar_expect_tx(barF + 8 * st, 32768);
                        tma_load_3d(dst, &mapG4, barF + 8 * st, 0, kc * 64, cb * 7);
                        tma_load_3d(dst + 16384, &mapU4, barF + 8 * st, 0, kc * 64, cb * 7);
                    } else {
                        mbar_expect_tx(barF + 8 * st, 24576);
                        tma_load_3d(dst, &mapG3, barF + 8 * st, 0, kc * 64, cb * 7 + 4);
                        tma_load_3d(dst + 12288, &mapU3, barF + 8 * st, 0, kc * 64, cb * 7 + 4);
                    }
                    if (++st == G1_STAGES) { st = 0; ph ^= 1; }
                }
            }
            __syncwarp();
            cluster_wait();
        } else if (warp == 1) {
            cluster_wait();
            pdl_wait();
            if (lane < 8) {
                const int c = 2 * (lane >> 1) + rank, mh = lane & 1;
                tma_load_2d_mc(sb + c * 16384 + mh * 8192, &mapA, barA + 8 * c, rb * 128 + mh * 64, c * 64, (uint16_t)3);
            }
            __syncwarp();
            float* cs = reinterpret_cast<float*>(smem_raw + G1_OFF_CS);
            for (int i = lane; i < 448; i += 32) cs[i] = __ldcg((i < 224) ? &g_colsum[cb * 224 + i] : &g_colsum[F_ + cb * 224 + (i - 224)]);
            __syncwarp();
            if (lane == 0) mbar_arrive(barS);
        } else {
            cluster_wait();
        }
    } else {
        reg_alloc<232>();
        cluster_wait();
        const int cw = wgi - 1;
        const int g = lane >> 2, t = lane & 3, wl = warp & 3, tl = tid & 127;
        bf16* outp = g_hh + (size_t)(rb * 128 + cw * 64 + wl * 16 + g) * F_ + cb * 224;
        const float* cs = reinterpret_cast<const float*>(smem_raw + G1_OFF_CS);
        int st = 0, ph = 0;
        float2 st0, st1;
        {
            float acc[128];
            const int kq = lane >> 3, mp = lane & 7;
            const uint8_t* sbase = smem_raw + cw * 8192 + kq * 128 + (mp & 3) * 4;
            const int mc = 2 * wl + (mp >> 2);
            float p0 = 0.f, p1 = 0.f, s0 = 0.f, s1 = 0.f, q0 = 0.f, q1 = 0.f;
#pragma unroll 1
            for (int kc = 0; kc < 8; kc++) {
                mbar_wait(barA + 8 * kc, 0);
                mbar_wait(barF + 8 * st, ph);
                if (tl == 0 && cw == 0) TR(1, kc);
                wgmma_fence();
                const uint32_t aaddr = sb + kc * 16384 + cw * 8192;
                const uint32_t baddr = sb + G1_OFF_B + st * G1_B_STAGE;
#pragma unroll
                for (int kk = 0; kk < 4; kk++)
                    wgmma_m64n256k16_ss(acc, make_desc(aaddr + kk * 2048, 8192, 1024, 1), make_desc(baddr + kk * 1024, 4096, 512, 2), (kc | kk) != 0);
                wgmma_commit();
                if (kc == 0) {
                    const uint32_t w = *reinterpret_cast<const uint32_t*>(smem_raw + cw * 8192 + (mc << 4) + (mp & 3) * 4);
                    p0 = bf_lo(w); p1 = bf_hi(w);
                }
#pragma unroll
                for (int i = 0; i < 16; i++) {
                    const int kr = 4 * i;
                    const uint32_t w = *reinterpret_cast<const uint32_t*>(sbase + kc * 16384 + kr * 128 + ((mc ^ ((kr + kq) & 7)) << 4));
                    const float d0 = bf_lo(w) - p0, d1 = bf_hi(w) - p1;
                    s0 += d0; s1 += d1; q0 = fmaf(d0, d0, q0); q1 = fmaf(d1, d1, q1);
                }
                wgmma_wait<0>();
                if (tl == 0) mbar_arrive(barE + 8 * st);
                if (++st == G1_STAGES) { st = 0; ph ^= 1; }
            }
            TM(2, 1);
            {
#pragma unroll
                for (int o = 8; o <= 16; o <<= 1) {
                    s0 += __shfl_xor_sync(0xffffffffu, s0, o); s1 += __shfl_xor_sync(0xffffffffu, s1, o);
                    q0 += __shfl_xor_sync(0xffffffffu, q0, o); q1 += __shfl_xor_sync(0xffffffffu, q1, o);
                }
                const float md0 = s0 * (1.0f / D_), md1 = s1 * (1.0f / D_);
                const float v0 = bf16r(fmaxf(fmaf(-md0, md0, q0 * (1.0f / D_)), 0.f)), v1 = bf16r(fmaxf(fmaf(-md1, md1, q1 * (1.0f / D_)), 0.f));
                const float ma = bf16r(p0 + md0), mb = bf16r(p1 + md1);
                const float ra = 1.0f / bf16r(sqrtf(bf16r(v0 + 1e-5f))), rbb = 1.0f / bf16r(sqrtf(bf16r(v1 + 1e-5f)));
                const float mA = __shfl_sync(0xffffffffu, ma, g >> 1), mB = __shfl_sync(0xffffffffu, mb, g >> 1);
                const float rA = __shfl_sync(0xffffffffu, ra, g >> 1), rB = __shfl_sync(0xffffffffu, rbb, g >> 1);
                const float mC = __shfl_sync(0xffffffffu, ma, 4 + (g >> 1)), mD = __shfl_sync(0xffffffffu, mb, 4 + (g >> 1));
                const float rC = __shfl_sync(0xffffffffu, ra, 4 + (g >> 1)), rD = __shfl_sync(0xffffffffu, rbb, 4 + (g >> 1));
                st0 = (g & 1) ? make_float2(mB, rB) : make_float2(mA, rA);
                st1 = (g & 1) ? make_float2(mD, rD) : make_float2(mC, rC);
            }
            mbar_wait(barS, 0);
            pdl_wait();
            TM(2, 5);
            g1_epilogue<16>(acc, cs, cs + 224, st0, st1, outp, t);
            TM(2, 2);
        }
        {
            float acc[96];
#pragma unroll 1
            for (int kc = 0; kc < 8; kc++) {
                mbar_wait(barF + 8 * st, ph);
                if (tl == 0 && cw == 0) TR(1, 8 + kc);
                wgmma_fence();
                const uint32_t aaddr = sb + kc * 16384 + cw * 8192;
                const uint32_t baddr = sb + G1_OFF_B + st * G1_B_STAGE;
#pragma unroll
                for (int kk = 0; kk < 4; kk++)
                    wgmma_m64n192k16_ss(acc, make_desc(aaddr + kk * 2048, 8192, 1024, 1), make_desc(baddr + kk * 1024, 4096, 512, 2), (kc | kk) != 0);
                wgmma_commit();
                wgmma_wait<0>();
                if (tl == 0) mbar_arrive(barE + 8 * st);
                if (++st == G1_STAGES) { st = 0; ph ^= 1; }
            }
            TM(2, 3);
            g1_epilogue<12>(acc, cs + 128, cs + 224 + 128, st0, st1, outp + 128, t);
            TM(2, 4);
        }
    }
}

constexpr int G2_THREADS = 384;
constexpr int G2_STAGES = 6;
constexpr int G2_STAGE = 32768;
constexpr int G2_OFF_X = G2_STAGES * G2_STAGE;
constexpr int G2_OFF_BAR = G2_OFF_X + 32768;
constexpr int G2_SMEM = G2_OFF_BAR + 128;
constexpr int G2_KSTEPS = 14;

__device__ __forceinline__ void ldsm_x4_t(uint32_t& r0, uint32_t& r1, uint32_t& r2, uint32_t& r3, uint32_t addr) {
    asm volatile("ldmatrix.sync.aligned.m8n8.x4.trans.shared.b16 {%0,%1,%2,%3}, [%4];" : "=r"(r0), "=r"(r1), "=r"(r2), "=r"(r3) : "r"(addr) : "memory");
}

__global__ void __cluster_dims__(2, 1, 1) __launch_bounds__(G2_THREADS, 1)
gemm2_kernel(const __grid_constant__ CUtensorMap mapHH, const __grid_constant__ CUtensorMap mapWd, const __grid_constant__ CUtensorMap mapH,
             bf16* __restrict__ out) {
    extern __shared__ __align__(1024) uint8_t smem_raw[];
    const uint32_t sb = smem_u32(smem_raw);
    const int tid = threadIdx.x, lane = tid & 31, warp = tid >> 5, wgi = tid >> 7;
    const int ks = blockIdx.x & 1, nb = (blockIdx.x >> 1) & 3, rb = blockIdx.x >> 3;
    TM(3, 0);
    if (tid == 32) { prefetch_map(&mapHH); prefetch_map(&mapH); }
    const uint32_t barF = sb + G2_OFF_BAR;
    const uint32_t barE = barF + 8 * G2_STAGES;
    const uint32_t barX = barE + 8 * G2_STAGES;
    if (tid == 0) {
        for (int i = 0; i < G2_STAGES; i++) { mbar_init(barF + 8 * i, 1); mbar_init(barE + 8 * i, 2); }
        mbar_init(barX, 1);
        asm volatile("fence.mbarrier_init.release.cluster;" ::: "memory");
        mbar_expect_tx(barX, 32768);
        for (int it = 0; it < G2_STAGES; it++) {
            mbar_expect_tx(barF + 8 * it, 32768);
            tma_load_3d(sb + it * G2_STAGE + 16384, &mapWd, barF + 8 * it, 0, ks * 896 + it * 64, nb * 2);
        }
    }
    __syncthreads();
    cluster_arrive_relaxed();

    if (wgi == 0) {
        if (tid == 0) {
            pdl_wait();
            for (int it = 0; it < G2_STAGES; it++)
                tma_load_2d(sb + it * G2_STAGE, &mapHH, barF + 8 * it, ks * 896 + it * 64, rb * 128);
            if (blockIdx.x == 0) g_cnt = 0u;
            int st = 0, ph = 0;
            for (int it = G2_STAGES; it < G2_KSTEPS; it++) {
                mbar_wait(barE + 8 * st, ph);
                const uint32_t dst = sb + st * G2_STAGE;
                const int k0 = ks * 896 + it * 64;
                mbar_expect_tx(barF + 8 * st, 32768);
                tma_load_2d(dst, &mapHH, barF + 8 * st, k0, rb * 128);
                tma_load_3d(dst + 16384, &mapWd, barF + 8 * st, 0, k0, nb * 2);
                if (++st == G2_STAGES) { st = 0; ph ^= 1; }
            }
            mbar_wait(barE + 8 * st, ph);
            mbar_expect_tx(barF + 8 * st, 16384);
            tma_load_2d(sb + st * G2_STAGE, &mapH, barF + 8 * st, rb * 128 + ks * 64, nb * 128);
        }
        __syncwarp();
        cluster_wait();
    } else {
        const int cw = wgi - 1;
        const int g = lane >> 2, t = lane & 3, wl = warp & 3;
        const int tl = tid & 127;
        int st = 0, ph = 0;
        float acc[64];
#pragma unroll 1
        for (int it = 0; it < G2_KSTEPS; it++) {
            mbar_wait(barF + 8 * st, ph);
            if (it == 0) TM(3, 1);
            wgmma_fence();
            const uint32_t aaddr = sb + st * G2_STAGE + cw * 8192;
            const uint32_t baddr = sb + st * G2_STAGE + 16384;
#pragma unroll
            for (int kk = 0; kk < 4; kk++)
                wgmma_m64n128k16_ss(acc, make_desc(aaddr + kk * 32, 16, 1024, 1), make_desc(baddr + kk * 2048, 8192, 1024, 1), (it | kk) != 0);
            wgmma_commit();
            wgmma_wait<0>();
            if (tl == 0) mbar_arrive(barE + 8 * st);
            if (++st == G2_STAGES) { st = 0; ph ^= 1; }
        }
        TM(3, 2);
        cluster_wait();
        if (cw != ks) {
            const uint32_t dst = mapa(sb + G2_OFF_X + tl * 16, (uint32_t)(ks ^ 1));
            const uint32_t rbar = mapa(barX, (uint32_t)(ks ^ 1));
#pragma unroll
            for (int i = 0; i < 16; i++) st_async_v4f(dst + i * 2048, acc[4 * i], acc[4 * i + 1], acc[4 * i + 2], acc[4 * i + 3], rbar);
        } else {
            const float4* xb = reinterpret_cast<const float4*>(smem_raw + G2_OFF_X) + tl;
            const int row0 = rb * 128 + cw * 64 + wl * 16 + g;
            bf16* o0 = out + (size_t)row0 * D_ + nb * 128;
            uint32_t ha[16], hb[16];
            mbar_wait(barF + 8 * st, ph);
            {
                const int chl = 8 * (lane >> 4) + (lane & 7), sb8 = 2 * wl + ((lane >> 3) & 1);
                const uint32_t hbase = sb + st * G2_STAGE + chl * 128 + ((sb8 ^ (lane & 7)) << 4);
#pragma unroll
                for (int j = 0; j < 16; j += 2) ldsm_x4_t(ha[j], hb[j], ha[j + 1], hb[j + 1], hbase + j * 1024);
            }
            mbar_wait_cluster(barX, 0);
            TM(3, 4);
#pragma unroll
            for (int j0 = 0; j0 < 16; j0 += 4) {
                uint32_t P0[4], P1[4];
#pragma unroll
                for (int jj = 0; jj < 4; jj++) {
                    const int j = j0 + jj;
                    const float4 x = xb[j * 128];
                    P0[jj] = hadd2(ha[j], pack_bf16(acc[4 * j] + x.x, acc[4 * j + 1] + x.y));
                    P1[jj] = hadd2(hb[j], pack_bf16(acc[4 * j + 2] + x.z, acc[4 * j + 3] + x.w));
                }
                quad_transpose(P0[0], P0[1], P0[2], P0[3], t);
                quad_transpose(P1[0], P1[1], P1[2], P1[3], t);
                *reinterpret_cast<uint4*>(o0 + 8 * (j0 + t)) = make_uint4(P0[0], P0[1], P0[2], P0[3]);
                *reinterpret_cast<uint4*>(o0 + 8 * D_ + 8 * (j0 + t)) = make_uint4(P1[0], P1[1], P1[2], P1[3]);
            }
        }
        TM(3, 5);
    }
#undef TMT
}

typedef CUresult (*EncodeFn)(CUtensorMap*, CUtensorMapDataType, cuuint32_t, void*, const cuuint64_t*, const cuuint64_t*,
                             const cuuint32_t*, const cuuint32_t*, CUtensorMapInterleave, CUtensorMapSwizzle,
                             CUtensorMapL2promotion, CUtensorMapFloatOOBfill);

static void enc2d(EncodeFn enc, CUtensorMap* m, const void* p, int rows, int cols, int brows, int bcols) {
    cuuint64_t dims[2] = {(cuuint64_t)cols, (cuuint64_t)rows};
    cuuint64_t strides[1] = {(cuuint64_t)cols * 2};
    cuuint32_t box[2] = {(cuuint32_t)bcols, (cuuint32_t)brows};
    cuuint32_t es[2] = {1, 1};
    enc(m, CU_TENSOR_MAP_DATA_TYPE_BFLOAT16, 2, const_cast<void*>(p), dims, strides, box, es, CU_TENSOR_MAP_INTERLEAVE_NONE,
        bcols == 32 ? CU_TENSOR_MAP_SWIZZLE_64B : CU_TENSOR_MAP_SWIZZLE_128B, CU_TENSOR_MAP_L2_PROMOTION_L2_128B, CU_TENSOR_MAP_FLOAT_OOB_FILL_NONE);
}
static void enc2d_plain(EncodeFn enc, CUtensorMap* m, const void* p, int rows, int cols, int brows, int bcols) {
    cuuint64_t dims[2] = {(cuuint64_t)cols, (cuuint64_t)rows};
    cuuint64_t strides[1] = {(cuuint64_t)cols * 2};
    cuuint32_t box[2] = {(cuuint32_t)bcols, (cuuint32_t)brows};
    cuuint32_t es[2] = {1, 1};
    enc(m, CU_TENSOR_MAP_DATA_TYPE_BFLOAT16, 2, const_cast<void*>(p), dims, strides, box, es, CU_TENSOR_MAP_INTERLEAVE_NONE,
        CU_TENSOR_MAP_SWIZZLE_NONE, CU_TENSOR_MAP_L2_PROMOTION_L2_128B, CU_TENSOR_MAP_FLOAT_OOB_FILL_NONE);
}
static void enc3d(EncodeFn enc, CUtensorMap* m, const void* p, int rows, int cols, int atom, int brows, int natoms) {
    cuuint64_t dims[3] = {(cuuint64_t)atom, (cuuint64_t)rows, (cuuint64_t)(cols / atom)};
    cuuint64_t strides[2] = {(cuuint64_t)cols * 2, (cuuint64_t)atom * 2};
    cuuint32_t box[3] = {(cuuint32_t)atom, (cuuint32_t)brows, (cuuint32_t)natoms};
    cuuint32_t es[3] = {1, 1, 1};
    enc(m, CU_TENSOR_MAP_DATA_TYPE_BFLOAT16, 3, const_cast<void*>(p), dims, strides, box, es, CU_TENSOR_MAP_INTERLEAVE_NONE,
        atom == 32 ? CU_TENSOR_MAP_SWIZZLE_64B : CU_TENSOR_MAP_SWIZZLE_128B, CU_TENSOR_MAP_L2_PROMOTION_L2_128B, CU_TENSOR_MAP_FLOAT_OOB_FILL_NONE);
}

extern "C" void kernel_launch(void* const* d_in, const int* in_sizes, int n_in, void* d_out, int out_size) {
    const bf16* q = (const bf16*)d_in[0];
    const bf16* k = (const bf16*)d_in[1];
    const bf16* v = (const bf16*)d_in[2];
    const bf16* shift_k = (const bf16*)d_in[3];
    const bf16* ssm_k = (const bf16*)d_in[4];
    const bf16* ssm_D = (const bf16*)d_in[5];
    const bf16* wg = (const bf16*)d_in[7];
    const bf16* wu = (const bf16*)d_in[8];
    const bf16* wd = (const bf16*)d_in[9];
    bf16* out = (bf16*)d_out;

    static EncodeFn enc = nullptr;
    static void *p_hT = nullptr, *p_hh = nullptr;
    if (!enc) {
        void* fn = nullptr; cudaDriverEntryPointQueryResult qr;
        cudaGetDriverEntryPoint("cuTensorMapEncodeTiled", &fn, cudaEnableDefault, &qr);
        enc = (EncodeFn)fn;
        cudaGetSymbolAddress(&p_hT, g_hT);
        cudaGetSymbolAddress(&p_hh, g_hh);
        cudaFuncSetAttribute(conv_kernel, cudaFuncAttributeMaxDynamicSharedMemorySize, (int)sizeof(K1Smem));
        cudaFuncSetAttribute(gemm1_kernel, cudaFuncAttributeMaxDynamicSharedMemorySize, G1_SMEM);
        cudaFuncSetAttribute(gemm2_kernel, cudaFuncAttributeMaxDynamicSharedMemorySize, G2_SMEM);
    }
    CUtensorMap mA, mG64, mU64, mG32, mU32, mHH, mWd, mH, mWgp, mWup;
    enc2d_plain(enc, &mWgp, wg, D_, F_, 256, 32);
    enc2d_plain(enc, &mWup, wu, D_, F_, 256, 32);
    enc2d(enc, &mA, p_hT, D_, S_, 64, 64);
    enc2d(enc, &mH, p_hT, D_, S_, 128, 64);
    enc3d(enc, &mG64, wg, D_, F_, 32, 64, 4);
    enc3d(enc, &mU64, wu, D_, F_, 32, 64, 4);
    enc3d(enc, &mG32, wg, D_, F_, 32, 64, 3);
    enc3d(enc, &mU32, wu, D_, F_, 32, 64, 3);
    enc2d(enc, &mHH, p_hh, S_, F_, 128, 64);
    enc3d(enc, &mWd, wd, F_, D_, 64, 64, 2);

    cudaStream_t st = cudaStreamPerThread;
    cudaLaunchAttribute at[1];
    at[0].id = cudaLaunchAttributeProgrammaticStreamSerialization;
    at[0].val.programmaticStreamSerializationAllowed = 1;
    cudaLaunchConfig_t cfg = {};
    cfg.stream = st; cfg.attrs = at; cfg.numAttrs = 1;
    conv_kernel<<<128, K1_THREADS, sizeof(K1Smem), st>>>(q, k, v, shift_k, ssm_k, ssm_D, mWgp, mWup, wd);
    cfg.gridDim = dim3(128); cfg.blockDim = dim3(G1_THREADS); cfg.dynamicSmemBytes = G1_SMEM;
    cudaLaunchKernelEx(&cfg, gemm1_kernel, mA, mG64, mU64, mG32, mU32);
    cfg.gridDim = dim3(128); cfg.blockDim = dim3(G2_THREADS); cfg.dynamicSmemBytes = G2_SMEM;
    cudaLaunchKernelEx(&cfg, gemm2_kernel, mHH, mWd, mH, out);
}
```

```cpp
#include <cuda_runtime.h>
#include <cuda_bf16.h>
#include <cuda.h>
#include <stdint.h>

typedef __nv_bfloat16 bf16;
constexpr int S_ = 2048, D_ = 512, F_ = 1792;

__device__ bf16 g_hT[D_ * S_];
__device__ bf16 g_hh[S_ * F_];
__device__ float2 g_st1[S_];
__device__ float g_colsum[2 * F_];
__device__ unsigned int g_cnt;

#define TM(k, i)
#define TR(k, i)
__device__ __forceinline__ uint32_t smem_u32(const void* p) { return (uint32_t)__cvta_generic_to_shared(p); }
__device__ __forceinline__ float bf16r(float x) { return __bfloat162float(__float2bfloat16_rn(x)); }
__device__ __forceinline__ float bf_lo(uint32_t w) { return __uint_as_float(w << 16); }
__device__ __forceinline__ float bf_hi(uint32_t w) { return __uint_as_float(w & 0xffff0000u); }
__device__ __forceinline__ uint32_t pack_bf16(float lo, float hi) {
    __nv_bfloat162 v = __floats2bfloat162_rn(lo, hi);
    return *reinterpret_cast<uint32_t*>(&v);
}
__device__ __forceinline__ uint32_t hmul2(uint32_t a, uint32_t b) {
    __nv_bfloat162 r = __hmul2_rn(*reinterpret_cast<__nv_bfloat162*>(&a), *reinterpret_cast<__nv_bfloat162*>(&b));
    return *reinterpret_cast<uint32_t*>(&r);
}
__device__ __forceinline__ uint32_t hadd2(uint32_t a, uint32_t b) {
    __nv_bfloat162 r = __hadd2_rn(*reinterpret_cast<__nv_bfloat162*>(&a), *reinterpret_cast<__nv_bfloat162*>(&b));
    return *reinterpret_cast<uint32_t*>(&r);
}
__device__ __forceinline__ uint4 ldg128(const void* p) {
    uint4 r; asm volatile("ld.global.nc.v4.u32 {%0,%1,%2,%3}, [%4];" : "=r"(r.x), "=r"(r.y), "=r"(r.z), "=r"(r.w) : "l"(p)); return r;
}
__device__ __forceinline__ uint4 ldcg128(const void* p) {
    uint4 r; asm volatile("ld.global.cg.v4.u32 {%0,%1,%2,%3}, [%4];" : "=r"(r.x), "=r"(r.y), "=r"(r.z), "=r"(r.w) : "l"(p)); return r;
}
__device__ __forceinline__ uint32_t ldg16(const void* p) {
    unsigned short r; asm volatile("ld.global.nc.u16 %0, [%1];" : "=h"(r) : "l"(p)); return (uint32_t)r;
}
__device__ __forceinline__ void mbar_init(uint32_t bar, int cnt) { asm volatile("mbarrier.init.shared::cta.b64 [%0], %1;" :: "r"(bar), "r"(cnt)); }
__device__ __forceinline__ void mbar_expect_tx(uint32_t bar, uint32_t bytes) { asm volatile("mbarrier.arrive.expect_tx.shared::cta.b64 _, [%0], %1;" :: "r"(bar), "r"(bytes) : "memory"); }
__device__ __forceinline__ void mbar_arrive(uint32_t bar) { asm volatile("mbarrier.arrive.shared::cta.b64 _, [%0];" :: "r"(bar) : "memory"); }
__device__ __forceinline__ void mbar_arrive_cluster(uint32_t bar, uint32_t cta) {
    asm volatile("{\n.reg .b32 ra;\nmapa.shared::cluster.u32 ra, %0, %1;\nmbarrier.arrive.shared::cluster.b64 _, [ra];\n}" :: "r"(bar), "r"(cta) : "memory");
}
__device__ __forceinline__ void mbar_wait(uint32_t bar, uint32_t parity) {
    asm volatile("{\n.reg .pred P1;\nLAB_WAIT:\nmbarrier.try_wait.parity.shared::cta.b64 P1, [%0], %1;\n@P1 bra DONE;\nbra LAB_WAIT;\nDONE:\n}" :: "r"(bar), "r"(parity) : "memory");
}
__device__ __forceinline__ void mbar_wait_cluster(uint32_t bar, uint32_t parity) {
    asm volatile("{\n.reg .pred P1;\nLAB_WAIT:\nmbarrier.try_wait.parity.acquire.cluster.shared::cta.b64 P1, [%0], %1;\n@P1 bra DONE;\nbra LAB_WAIT;\nDONE:\n}" :: "r"(bar), "r"(parity) : "memory");
}
__device__ __forceinline__ void tma_load_2d(uint32_t dst, const CUtensorMap* map, uint32_t bar, int c0, int c1) {
    asm volatile("cp.async.bulk.tensor.2d.shared::cluster.global.mbarrier::complete_tx::bytes [%0], [%1, {%3, %4}], [%2];"
        :: "r"(dst), "l"(map), "r"(bar), "r"(c0), "r"(c1) : "memory");
}
__device__ __forceinline__ void tma_load_2d_mc(uint32_t dst, const CUtensorMap* map, uint32_t bar, int c0, int c1, uint16_t mask) {
    asm volatile("cp.async.bulk.tensor.2d.shared::cluster.global.mbarrier::complete_tx::bytes.multicast::cluster [%0], [%1, {%3, %4}], [%2], %5;"
        :: "r"(dst), "l"(map), "r"(bar), "r"(c0), "r"(c1), "h"(mask) : "memory");
}
__device__ __forceinline__ void tma_load_3d(uint32_t dst, const CUtensorMap* map, uint32_t bar, int c0, int c1, int c2) {
    asm volatile("cp.async.bulk.tensor.3d.shared::cluster.global.mbarrier::complete_tx::bytes [%0], [%1, {%3, %4, %5}], [%2];"
        :: "r"(dst), "l"(map), "r"(bar), "r"(c0), "r"(c1), "r"(c2) : "memory");
}
__device__ __forceinline__ void cluster_arrive() { asm volatile("barrier.cluster.arrive.aligned;" ::: "memory"); }
__device__ __forceinline__ void cluster_arrive_relaxed() { asm volatile("barrier.cluster.arrive.relaxed.aligned;" ::: "memory"); }
__device__ __forceinline__ void cluster_wait() { asm volatile("barrier.cluster.wait.aligned;" ::: "memory"); }
__device__ __forceinline__ uint32_t mapa(uint32_t addr, uint32_t cta) {
    uint32_t r; asm volatile("mapa.shared::cluster.u32 %0, %1, %2;" : "=r"(r) : "r"(addr), "r"(cta)); return r;
}
__device__ __forceinline__ void st_async_v2(uint32_t addr, uint32_t a, uint32_t b, uint32_t rbar) {
    asm volatile("st.async.weak.shared::cluster.mbarrier::complete_tx::bytes.v2.b32 [%0], {%1, %2}, [%3];" :: "r"(addr), "r"(a), "r"(b), "r"(rbar) : "memory");
}
__device__ __forceinline__ void st_async_v4f(uint32_t addr, float a, float b, float c, float d, uint32_t rbar) {
    asm volatile("st.async.weak.shared::cluster.mbarrier::complete_tx::bytes.v4.f32 [%0], {%1, %2, %3, %4}, [%5];" :: "r"(addr), "f"(a), "f"(b), "f"(c), "f"(d), "r"(rbar) : "memory");
}
__device__ __forceinline__ void wgmma_fence() { asm volatile("wgmma.fence.sync.aligned;" ::: "memory"); }
__device__ __forceinline__ void wgmma_commit() { asm volatile("wgmma.commit_group.sync.aligned;" ::: "memory"); }
template <int N> __device__ __forceinline__ void wgmma_wait() { asm volatile("wgmma.wait_group.sync.aligned %0;" :: "n"(N) : "memory"); }
__device__ __forceinline__ uint64_t make_desc(uint32_t addr, uint32_t lbo_bytes, uint32_t sbo_bytes, uint32_t layout) {
    return (uint64_t)((addr & 0x3FFFF) >> 4) | ((uint64_t)(lbo_bytes >> 4) << 16) | ((uint64_t)(sbo_bytes >> 4) << 32) | ((uint64_t)layout << 62);
}
template <int R> __device__ __forceinline__ void reg_alloc() { asm volatile("setmaxnreg.inc.sync.aligned.u32 %0;" :: "n"(R)); }
template <int R> __device__ __forceinline__ void reg_dealloc() { asm volatile("setmaxnreg.dec.sync.aligned.u32 %0;" :: "n"(R)); }
__device__ __forceinline__ void pdl_launch() { asm volatile("griddepcontrol.launch_dependents;" ::: "memory"); }
__device__ __forceinline__ void pdl_wait() { asm volatile("griddepcontrol.wait;" ::: "memory"); }
__device__ __forceinline__ void prefetch_map(const CUtensorMap* m) { asm volatile("prefetch.tensormap [%0];" :: "l"(m) : "memory"); }
__device__ __forceinline__ void named_bar(int id, int n) { asm volatile("bar.sync %0, %1;" :: "r"(id), "r"(n) : "memory"); }

__device__ __forceinline__ void wgmma_m64n256k16_ss(float (&d)[128], uint64_t descA, uint64_t descB, int scaleD) {
    asm volatile("{\n.reg .pred p;\nsetp.ne.b32 p, %130, 0;\n"
        "wgmma.mma_async.sync.aligned.m64n256k16.f32.bf16.bf16 {%0, %1, %2, %3, %4, %5, %6, %7, %8, %9, %10, %11, %12, %13, %14, %15, %16, %17, %18, %19, %20, %21, %22, %23, %24, %25, %26, %27, %28, %29, %30, %31, %32, %33, %34, %35, %36, %37, %38, %39, %40, %41, %42, %43, %44, %45, %46, %47, %48, %49, %50, %51, %52, %53, %54, %55, %56, %57, %58, %59, %60, %61, %62, %63, %64, %65, %66, %67, %68, %69, %70, %71, %72, %73, %74, %75, %76, %77, %78, %79, %80, %81, %82, %83, %84, %85, %86, %87, %88, %89, %90, %91, %92, %93, %94, %95, %96, %97, %98, %99, %100, %101, %102, %103, %104, %105, %106, %107, %108, %109, %110, %111, %112, %113, %114, %115, %116, %117, %118, %119, %120, %121, %122, %123, %124, %125, %126, %127}, %128, %129, p, 1, 1, 1, 1;\n}\n"
        : "+f"(d[0]), "+f"(d[1]), "+f"(d[2]), "+f"(d[3]), "+f"(d[4]), "+f"(d[5]), "+f"(d[6]), "+f"(d[7]), "+f"(d[8]), "+f"(d[9]), "+f"(d[10]), "+f"(d[11]), "+f"(d[12]), "+f"(d[13]), "+f"(d[14]), "+f"(d[15]), "+f"(d[16]), "+f"(d[17]), "+f"(d[18]), "+f"(d[19]), "+f"(d[20]), "+f"(d[21]), "+f"(d[22]), "+f"(d[23]), "+f"(d[24]), "+f"(d[25]), "+f"(d[26]), "+f"(d[27]), "+f"(d[28]), "+f"(d[29]), "+f"(d[30]), "+f"(d[31]), "+f"(d[32]), "+f"(d[33]), "+f"(d[34]), "+f"(d[35]), "+f"(d[36]), "+f"(d[37]), "+f"(d[38]), "+f"(d[39]), "+f"(d[40]), "+f"(d[41]), "+f"(d[42]), "+f"(d[43]), "+f"(d[44]), "+f"(d[45]), "+f"(d[46]), "+f"(d[47]), "+f"(d[48]), "+f"(d[49]), "+f"(d[50]), "+f"(d[51]), "+f"(d[52]), "+f"(d[53]), "+f"(d[54]), "+f"(d[55]), "+f"(d[56]), "+f"(d[57]), "+f"(d[58]), "+f"(d[59]), "+f"(d[60]), "+f"(d[61]), "+f"(d[62]), "+f"(d[63]), "+f"(d[64]), "+f"(d[65]), "+f"(d[66]), "+f"(d[67]), "+f"(d[68]), "+f"(d[69]), "+f"(d[70]), "+f"(d[71]), "+f"(d[72]), "+f"(d[73]), "+f"(d[74]), "+f"(d[75]), "+f"(d[76]), "+f"(d[77]), "+f"(d[78]), "+f"(d[79]), "+f"(d[80]), "+f"(d[81]), "+f"(d[82]), "+f"(d[83]), "+f"(d[84]), "+f"(d[85]), "+f"(d[86]), "+f"(d[87]), "+f"(d[88]), "+f"(d[89]), "+f"(d[90]), "+f"(d[91]), "+f"(d[92]), "+f"(d[93]), "+f"(d[94]), "+f"(d[95]), "+f"(d[96]), "+f"(d[97]), "+f"(d[98]), "+f"(d[99]), "+f"(d[100]), "+f"(d[101]), "+f"(d[102]), "+f"(d[103]), "+f"(d[104]), "+f"(d[105]), "+f"(d[106]), "+f"(d[107]), "+f"(d[108]), "+f"(d[109]), "+f"(d[110]), "+f"(d[111]), "+f"(d[112]), "+f"(d[113]), "+f"(d[114]), "+f"(d[115]), "+f"(d[116]), "+f"(d[117]), "+f"(d[118]), "+f"(d[119]), "+f"(d[120]), "+f"(d[121]), "+f"(d[122]), "+f"(d[123]), "+f"(d[124]), "+f"(d[125]), "+f"(d[126]), "+f"(d[127])
        : "l"(descA), "l"(descB), "r"(scaleD));
}

__device__ __forceinline__ void wgmma_m64n192k16_ss(float (&d)[96], uint64_t descA, uint64_t descB, int scaleD) {
    asm volatile("{\n.reg .pred p;\nsetp.ne.b32 p, %98, 0;\n"
        "wgmma.mma_async.sync.aligned.m64n192k16.f32.bf16.bf16 {%0, %1, %2, %3, %4, %5, %6, %7, %8, %9, %10, %11, %12, %13, %14, %15, %16, %17, %18, %19, %20, %21, %22, %23, %24, %25, %26, %27, %28, %29, %30, %31, %32, %33, %34, %35, %36, %37, %38, %39, %40, %41, %42, %43, %44, %45, %46, %47, %48, %49, %50, %51, %52, %53, %54, %55, %56, %57, %58, %59, %60, %61, %62, %63, %64, %65, %66, %67, %68, %69, %70, %71, %72, %73, %74, %75, %76, %77, %78, %79, %80, %81, %82, %83, %84, %85, %86, %87, %88, %89, %90, %91, %92, %93, %94, %95}, %96, %97, p, 1, 1, 1, 1;\n}\n"
        : "+f"(d[0]), "+f"(d[1]), "+f"(d[2]), "+f"(d[3]), "+f"(d[4]), "+f"(d[5]), "+f"(d[6]), "+f"(d[7]), "+f"(d[8]), "+f"(d[9]), "+f"(d[10]), "+f"(d[11]), "+f"(d[12]), "+f"(d[13]), "+f"(d[14]), "+f"(d[15]), "+f"(d[16]), "+f"(d[17]), "+f"(d[18]), "+f"(d[19]), "+f"(d[20]), "+f"(d[21]), "+f"(d[22]), "+f"(d[23]), "+f"(d[24]), "+f"(d[25]), "+f"(d[26]), "+f"(d[27]), "+f"(d[28]), "+f"(d[29]), "+f"(d[30]), "+f"(d[31]), "+f"(d[32]), "+f"(d[33]), "+f"(d[34]), "+f"(d[35]), "+f"(d[36]), "+f"(d[37]), "+f"(d[38]), "+f"(d[39]), "+f"(d[40]), "+f"(d[41]), "+f"(d[42]), "+f"(d[43]), "+f"(d[44]), "+f"(d[45]), "+f"(d[46]), "+f"(d[47]), "+f"(d[48]), "+f"(d[49]), "+f"(d[50]), "+f"(d[51]), "+f"(d[52]), "+f"(d[53]), "+f"(d[54]), "+f"(d[55]), "+f"(d[56]), "+f"(d[57]), "+f"(d[58]), "+f"(d[59]), "+f"(d[60]), "+f"(d[61]), "+f"(d[62]), "+f"(d[63]), "+f"(d[64]), "+f"(d[65]), "+f"(d[66]), "+f"(d[67]), "+f"(d[68]), "+f"(d[69]), "+f"(d[70]), "+f"(d[71]), "+f"(d[72]), "+f"(d[73]), "+f"(d[74]), "+f"(d[75]), "+f"(d[76]), "+f"(d[77]), "+f"(d[78]), "+f"(d[79]), "+f"(d[80]), "+f"(d[81]), "+f"(d[82]), "+f"(d[83]), "+f"(d[84]), "+f"(d[85]), "+f"(d[86]), "+f"(d[87]), "+f"(d[88]), "+f"(d[89]), "+f"(d[90]), "+f"(d[91]), "+f"(d[92]), "+f"(d[93]), "+f"(d[94]), "+f"(d[95])
        : "l"(descA), "l"(descB), "r"(scaleD));
}

__device__ __forceinline__ void wgmma_m64n128k16_ss(float (&d)[64], uint64_t descA, uint64_t descB, int scaleD) {
    asm volatile("{\n.reg .pred p;\nsetp.ne.b32 p, %66, 0;\n"
        "wgmma.mma_async.sync.aligned.m64n128k16.f32.bf16.bf16 {%0, %1, %2, %3, %4, %5, %6, %7, %8, %9, %10, %11, %12, %13, %14, %15, %16, %17, %18, %19, %20, %21, %22, %23, %24, %25, %26, %27, %28, %29, %30, %31, %32, %33, %34, %35, %36, %37, %38, %39, %40, %41, %42, %43, %44, %45, %46, %47, %48, %49, %50, %51, %52, %53, %54, %55, %56, %57, %58, %59, %60, %61, %62, %63}, %64, %65, p, 1, 1, 0, 1;\n}\n"
        : "+f"(d[0]), "+f"(d[1]), "+f"(d[2]), "+f"(d[3]), "+f"(d[4]), "+f"(d[5]), "+f"(d[6]), "+f"(d[7]), "+f"(d[8]), "+f"(d[9]), "+f"(d[10]), "+f"(d[11]), "+f"(d[12]), "+f"(d[13]), "+f"(d[14]), "+f"(d[15]), "+f"(d[16]), "+f"(d[17]), "+f"(d[18]), "+f"(d[19]), "+f"(d[20]), "+f"(d[21]), "+f"(d[22]), "+f"(d[23]), "+f"(d[24]), "+f"(d[25]), "+f"(d[26]), "+f"(d[27]), "+f"(d[28]), "+f"(d[29]), "+f"(d[30]), "+f"(d[31]), "+f"(d[32]), "+f"(d[33]), "+f"(d[34]), "+f"(d[35]), "+f"(d[36]), "+f"(d[37]), "+f"(d[38]), "+f"(d[39]), "+f"(d[40]), "+f"(d[41]), "+f"(d[42]), "+f"(d[43]), "+f"(d[44]), "+f"(d[45]), "+f"(d[46]), "+f"(d[47]), "+f"(d[48]), "+f"(d[49]), "+f"(d[50]), "+f"(d[51]), "+f"(d[52]), "+f"(d[53]), "+f"(d[54]), "+f"(d[55]), "+f"(d[56]), "+f"(d[57]), "+f"(d[58]), "+f"(d[59]), "+f"(d[60]), "+f"(d[61]), "+f"(d[62]), "+f"(d[63])
        : "l"(descA), "l"(descB), "r"(scaleD));
}

__device__ __forceinline__ void quad_transpose(uint32_t& r0, uint32_t& r1, uint32_t& r2, uint32_t& r3, int t) {
    const bool o1 = t & 1, o2 = t & 2;
    uint32_t x, y;
    x = o1 ? r0 : r1; y = __shfl_xor_sync(0xffffffffu, x, 1); if (o1) r0 = y; else r1 = y;
    x = o1 ? r2 : r3; y = __shfl_xor_sync(0xffffffffu, x, 1); if (o1) r2 = y; else r3 = y;
    x = o2 ? r0 : r2; y = __shfl_xor_sync(0xffffffffu, x, 2); if (o2) r0 = y; else r2 = y;
    x = o2 ? r1 : r3; y = __shfl_xor_sync(0xffffffffu, x, 2); if (o2) r1 = y; else r3 = y;
}

__device__ __forceinline__ float warp_sum(float s) {
#pragma unroll
    for (int o = 16; o > 0; o >>= 1) s += __shfl_xor_sync(0xffffffffu, s, o);
    return s;
}
__device__ __forceinline__ uint32_t hsub2(uint32_t a, uint32_t b) {
    __nv_bfloat162 r = __hsub2_rn(*reinterpret_cast<__nv_bfloat162*>(&a), *reinterpret_cast<__nv_bfloat162*>(&b));
    return *reinterpret_cast<uint32_t*>(&r);
}
__device__ __forceinline__ void ln_stats2(const uint32_t (&x)[2][8], float2 (&st)[2]) {
    float piv[2], s[2], ss[2];
#pragma unroll
    for (int r = 0; r < 2; r++) piv[r] = __shfl_sync(0xffffffffu, bf_lo(x[r][0]), 0);
#pragma unroll
    for (int r = 0; r < 2; r++) {
        float s0 = 0.f, s1 = 0.f, q0 = 0.f, q1 = 0.f;
#pragma unroll
        for (int i = 0; i < 8; i++) {
            const float d0 = bf_lo(x[r][i]) - piv[r], d1 = bf_hi(x[r][i]) - piv[r];
            s0 += d0; s1 += d1; q0 = fmaf(d0, d0, q0); q1 = fmaf(d1, d1, q1);
        }
        s[r] = s0 + s1; ss[r] = q0 + q1;
    }
#pragma unroll
    for (int o = 16; o > 0; o >>= 1) {
#pragma unroll
        for (int r = 0; r < 2; r++) { s[r] += __shfl_xor_sync(0xffffffffu, s[r], o); ss[r] += __shfl_xor_sync(0xffffffffu, ss[r], o); }
    }
#pragma unroll
    for (int r = 0; r < 2; r++) {
        const float md = s[r] * (1.0f / D_);
        const float var = bf16r(fmaxf(fmaf(-md, md, ss[r] * (1.0f / D_)), 0.f));
        st[r] = make_float2(bf16r(piv[r] + md), 1.0f / bf16r(sqrtf(bf16r(var + 1e-5f))));
    }
}
__device__ __forceinline__ void ln_apply(const uint32_t (&x)[8], float2 st, uint32_t (&o)[8]) {
    const uint32_t m2 = pack_bf16(st.x, st.x);
#pragma unroll
    for (int i = 0; i < 8; i++) {
        const uint32_t d = hsub2(x[i], m2);
        o[i] = pack_bf16(bf_lo(d) * st.y, bf_hi(d) * st.y);
    }
}

constexpr int K1_THREADS = 352;
constexpr int UT_PAD = 128;
constexpr int UT_LEN = UT_PAD + S_;
constexpr int KR_LEN = 2080;
constexpr int YP_LEN = S_ + (S_ / 32) * 8;

struct __align__(128) K1Smem {
    bf16 uT[4][UT_LEN];
    bf16 xT[4][S_];
    bf16 kr[4][2][KR_LEN];
    float yP[4][YP_LEN];
    alignas(128) float2 st[S_];
    alignas(128) uint4 wS[512][4];
    float red[8][32];
    uint64_t bar, bar2, bar3, bar4;
};

__device__ __forceinline__ void mma16816(float (&c)[4], uint32_t a0, uint32_t a1, uint32_t a2, uint32_t a3, uint32_t b0, uint32_t b1) {
    asm("mma.sync.aligned.m16n8k16.row.col.f32.bf16.bf16.f32 {%0,%1,%2,%3}, {%4,%5,%6,%7}, {%8,%9}, {%0,%1,%2,%3};"
        : "+f"(c[0]), "+f"(c[1]), "+f"(c[2]), "+f"(c[3])
        : "r"(a0), "r"(a1), "r"(a2), "r"(a3), "r"(b0), "r"(b1));
}
__device__ __forceinline__ void ldsm_x4(uint32_t& r0, uint32_t& r1, uint32_t& r2, uint32_t& r3, uint32_t addr) {
    asm volatile("ldmatrix.sync.aligned.m8n8.x4.shared.b16 {%0,%1,%2,%3}, [%4];" : "=r"(r0), "=r"(r1), "=r"(r2), "=r"(r3) : "r"(addr) : "memory");
}

__device__ __forceinline__ void conv_mma(const bf16* uTc, const bf16* krlane, float (&acc)[16][4], int lane, int half) {
    const int lrow = lane & 7, lk = (lane >> 3) & 1, lt = lane >> 4;
    const uint32_t ubase = smem_u32(uTc) + (UT_PAD + 16 * (8 * lt + lrow) + 8 * lk) * 2;
#pragma unroll 1
    for (int pp = 0; pp < 4; pp++) {
        const int p = half * 4 + pp;
        uint32_t U[16][2];
#pragma unroll
        for (int j = 0; j < 16; j += 2) ldsm_x4(U[j][0], U[j][1], U[j + 1][0], U[j + 1][1], ubase + (j * 128 - p * 16) * 2);
        const uint32_t* kp = reinterpret_cast<const uint32_t*>(krlane - 16 * p);
        const volatile uint32_t* kpv = kp;
        uint32_t a0 = kp[0], a1 = kp[-4], a2 = kp[4], a3 = kpv[0];
#pragma unroll
        for (int q = 0; q < 16; q++) {
            uint32_t b0 = 0, b1 = 0, b2 = 0, b3 = 0;
            if (q < 15) { b0 = kp[-64 * (q + 1)]; b1 = kp[-64 * (q + 1) - 4]; b2 = kp[-64 * (q + 1) + 4]; b3 = kpv[-64 * (q + 1)]; }
#pragma unroll
            for (int n = 15; n >= q; n--) mma16816(acc[n], a0, a1, a2, a3, U[n - q][0], U[n - q][1]);
            a0 = b0; a1 = b1; a2 = b2; a3 = b3;
        }
    }
}

__device__ __forceinline__ void cp_async16(uint32_t dst, const void* src) {
    asm volatile("cp.async.cg.shared.global [%0], [%1], 16;" :: "r"(dst), "l"(src) : "memory");
}

__global__ void __cluster_dims__(2, 1, 1) __launch_bounds__(K1_THREADS, 1)
conv_kernel(const bf16* __restrict__ q, const bf16* __restrict__ k, const bf16* __restrict__ v,
            const bf16* __restrict__ shift_k, const bf16* __restrict__ ssm_k, const bf16* __restrict__ ssm_D,
            const __grid_constant__ CUtensorMap mapWg, const __grid_constant__ CUtensorMap mapWu, const bf16* __restrict__ wd) {
    extern __shared__ __align__(1024) uint8_t smem_raw[];
    pdl_launch();
    K1Smem& sm = *reinterpret_cast<K1Smem*>(smem_raw);
    const int tid = threadIdx.x, lane = tid & 31, warp = tid >> 5;
    const int bid = blockIdx.x;
    const int rank = bid & 1;
    const int c0 = 8 * (bid >> 1);
    const int cown = c0 + 4 * rank;
#define TMT 0
    TM(0, 0);
    const uint32_t bar = smem_u32(&sm.bar);
    if (tid == 0) {
        mbar_init(bar, 1);
        mbar_init(bar + 8, 1);
        mbar_init(bar + 16, 1);
        mbar_init(bar + 24, 1);
        asm volatile("fence.mbarrier_init.release.cluster;" ::: "memory");
        mbar_expect_tx(bar, 1024 * 4 * 2);
        mbar_expect_tx(bar + 8, 1024 * 4 * 2);
    }
    cluster_arrive_relaxed();

    if (warp < 8) {
        const int s0 = 1024 * rank + 4 * tid;
        uint4 kk[7], vv[4], qq[4], sw[4];
#pragma unroll
        for (int i = 0; i < 4; i++) kk[3 + i] = ldg128(k + (size_t)(s0 + i) * D_ + c0);
#pragma unroll
        for (int i = 0; i < 4; i++) vv[i] = ldg128(v + (size_t)(s0 + i) * D_ + c0);
        if (lane == 0) {
#pragma unroll
            for (int i = 0; i < 3; i++) {
                const int s = s0 - 3 + i;
                kk[i] = make_uint4(0, 0, 0, 0);
                if (s >= 0) kk[i] = ldg128(k + (size_t)s * D_ + c0);
            }
        }
#pragma unroll
        for (int i = 0; i < 4; i++) sw[i] = ldg128(shift_k + (size_t)c0 * 4 + 8 * i);
        uint4 kq[4]; uint32_t nx[4];
#pragma unroll
        for (int c = 0; c < 4; c++) {
            const bf16* kr = ssm_k + (size_t)(cown + c) * S_;
            kq[c] = ldg128(kr + 8 * tid);
            nx[c] = 0u;
            if (tid < 255) nx[c] = ldg16(kr + 8 * tid + 8);
        }
        const uint32_t dval = ldg16(ssm_D + cown + (warp >> 1));
        if (tid < 64) *reinterpret_cast<uint4*>(&sm.uT[tid >> 4][(tid & 15) * 8]) = make_uint4(0, 0, 0, 0);
#pragma unroll
        for (int i = 0; i < 3; i++) {
            uint4 t;
            t.x = __shfl_up_sync(0xffffffffu, kk[4 + i].x, 1); t.y = __shfl_up_sync(0xffffffffu, kk[4 + i].y, 1);
            t.z = __shfl_up_sync(0xffffffffu, kk[4 + i].z, 1); t.w = __shfl_up_sync(0xffffffffu, kk[4 + i].w, 1);
            if (lane != 0) kk[i] = t;
        }
        uint32_t kvw[4][4];
        const uint32_t* kkw = reinterpret_cast<const uint32_t*>(kk);
        const uint32_t* vvw = reinterpret_cast<const uint32_t*>(vv);
        const uint32_t* qqw = reinterpret_cast<const uint32_t*>(qq);
#pragma unroll
        for (int i2 = 0; i2 < 4; i2++) {
            const uint32_t t0 = __byte_perm(sw[i2].x, sw[i2].z, 0x5410), t1 = __byte_perm(sw[i2].x, sw[i2].z, 0x7632);
            const uint32_t t2 = __byte_perm(sw[i2].y, sw[i2].w, 0x5410), t3 = __byte_perm(sw[i2].y, sw[i2].w, 0x7632);
#pragma unroll
            for (int r = 0; r < 4; r++) {
                uint32_t a = hmul2(kkw[(r + 0) * 4 + i2], t3);
                a = hadd2(a, hmul2(kkw[(r + 1) * 4 + i2], t2));
                a = hadd2(a, hmul2(kkw[(r + 2) * 4 + i2], t1));
                a = hadd2(a, hmul2(kkw[(r + 3) * 4 + i2], t0));
                kvw[r][i2] = hmul2(a, vvw[r * 4 + i2]);
            }
        }
        TM(0, 1);
        cluster_wait();
        const uint32_t rbar = mapa(bar, (uint32_t)(rank ^ 1));
#pragma unroll
        for (int i2 = 0; i2 < 4; i2++) {
#pragma unroll
            for (int e = 0; e < 2; e++) {
                const uint32_t sel = e ? 0x7632 : 0x5410;
                const uint32_t w0 = __byte_perm(kvw[0][i2], kvw[1][i2], sel), w1 = __byte_perm(kvw[2][i2], kvw[3][i2], sel);
                const int cc = 2 * i2 + e;
                if ((cc >> 2) == rank) *reinterpret_cast<uint2*>(&sm.uT[cc & 3][UT_PAD + s0]) = make_uint2(w0, w1);
                else st_async_v2(mapa(smem_u32(&sm.uT[cc & 3][UT_PAD + s0]), (uint32_t)(rank ^ 1)), w0, w1, rbar);
            }
        }
#pragma unroll
        for (int c = 0; c < 4; c++) {
            uint4 a, b;
            a.x = __byte_perm(kq[c].w, 0, 0x1032); a.y = __byte_perm(kq[c].z, 0, 0x1032);
            a.z = __byte_perm(kq[c].y, 0, 0x1032); a.w = __byte_perm(kq[c].x, 0, 0x1032);
            b.x = __byte_perm(nx[c], kq[c].w, 0x7610); b.y = __byte_perm(kq[c].w, kq[c].z, 0x7610);
            b.z = __byte_perm(kq[c].z, kq[c].y, 0x7610); b.w = __byte_perm(kq[c].y, kq[c].x, 0x7610);
            *reinterpret_cast<uint4*>(&sm.kr[c][0][2040 - 8 * tid]) = a;
            *reinterpret_cast<uint4*>(&sm.kr[c][1][2040 - 8 * tid]) = b;
            if (tid == 0) {
                *reinterpret_cast<uint4*>(&sm.kr[c][1][2048]) = make_uint4(kq[c].x & 0xffffu, 0, 0, 0);
            } else if (tid < 8) {
                if (tid < 4) *reinterpret_cast<uint4*>(&sm.kr[c][1][2048 + 8 * tid]) = make_uint4(0, 0, 0, 0);
                else *reinterpret_cast<uint4*>(&sm.kr[c][0][2048 + 8 * (tid - 4)]) = make_uint4(0, 0, 0, 0);
            }
        }
#pragma unroll
        for (int i = 0; i < 4; i++) qq[i] = ldg128(q + (size_t)(s0 + i) * D_ + c0);
        TM(0, 3);
        named_bar(6, 352);
        mbar_wait_cluster(bar, 0);
        TM(0, 4);

        const int ch = warp >> 1, half = warp & 1;
        const int g = lane >> 2, t = lane & 3;
        float acc[16][4];
#pragma unroll
        for (int i = 0; i < 16; i++) { acc[i][0] = acc[i][1] = acc[i][2] = acc[i][3] = 0.f; }
        const bf16* krlane = (g & 1) ? &sm.kr[ch][0][2047 - g + 2 * t] : &sm.kr[ch][1][2048 - g + 2 * t];
        conv_mma(sm.uT[ch], krlane, acc, lane, half);
        TM(0, 5);
#pragma unroll
        for (int i2 = 0; i2 < 4; i2++) {
#pragma unroll
            for (int e = 0; e < 2; e++) {
                const uint32_t sel = e ? 0x7632 : 0x5410;
                const uint32_t w0 = __byte_perm(qqw[i2], qqw[4 + i2], sel), w1 = __byte_perm(qqw[8 + i2], qqw[12 + i2], sel);
                const int cc = 2 * i2 + e;
                if ((cc >> 2) == rank) *reinterpret_cast<uint2*>(&sm.xT[cc & 3][s0]) = make_uint2(w0, w1);
                else st_async_v2(mapa(smem_u32(&sm.xT[cc & 3][s0]), (uint32_t)(rank ^ 1)), w0, w1, rbar + 8);
            }
        }
        float* yp = &sm.yP[ch][40 * t + g];
        if (half) {
#pragma unroll
            for (int n = 0; n < 16; n++) {
                yp[160 * n] = acc[n][0];
                yp[160 * n + 16] = acc[n][1];
                yp[160 * n + 8] = acc[n][2];
                yp[160 * n + 24] = acc[n][3];
            }
        }
        named_bar(1 + ch, 64);
        if (!half) {
#pragma unroll
            for (int n = 0; n < 16; n++) {
                yp[160 * n] += acc[n][0];
                yp[160 * n + 16] += acc[n][1];
                yp[160 * n + 8] += acc[n][2];
                yp[160 * n + 24] += acc[n][3];
            }
        }
        named_bar(7, 288);
        mbar_wait_cluster(bar + 8, 0);
        TM(0, 6);
        {
            const int tt = tid & 63;
            bf16* dst = g_hT + (size_t)(cown + ch) * S_;
            const uint32_t d2 = dval * 0x10001u;
#pragma unroll
            for (int j = 0; j < 4; j++) {
                const int s = (j * 64 + tt) * 8;
                const float* src = &sm.yP[ch][s + (s >> 5) * 8];
                const float4 a = *reinterpret_cast<const float4*>(src), b = *reinterpret_cast<const float4*>(src + 4);
                const uint4 kv4 = *reinterpret_cast<const uint4*>(&sm.uT[ch][UT_PAD + s]);
                const uint4 x4 = *reinterpret_cast<const uint4*>(&sm.xT[ch][s]);
                const uint32_t y2[4] = {hadd2(pack_bf16(a.x, a.y), hmul2(kv4.x, d2)), hadd2(pack_bf16(a.z, a.w), hmul2(kv4.y, d2)),
                                        hadd2(pack_bf16(b.x, b.y), hmul2(kv4.z, d2)), hadd2(pack_bf16(b.z, b.w), hmul2(kv4.w, d2))};
                const uint32_t xw[4] = {x4.x, x4.y, x4.z, x4.w};
                uint32_t o[4];
#pragma unroll
                for (int i = 0; i < 4; i++) {
                    const float4 st = *reinterpret_cast<const float4*>(&sm.st[s + 2 * i]);
                    const uint32_t d = hsub2(xw[i], pack_bf16(st.x, st.z));
                    const uint32_t qn = pack_bf16(bf_lo(d) * st.y, bf_hi(d) * st.w);
                    o[i] = hadd2(xw[i], hmul2(qn, y2[i]));
                }
                *reinterpret_cast<uint4*>(dst + s) = make_uint4(o[0], o[1], o[2], o[3]);
            }
        }
        TM(0, 7);
    } else {
        cluster_wait();
        named_bar(6, 352);
        const uint32_t hbar = bar + 16;
        if (warp < 10) {
            {
                const int rr = 8 * (warp - 8);
                uint32_t xq[4][2][8];
#pragma unroll
                for (int r = 0; r < 8; r++) {
                    const uint4 qa = ldg128(q + (size_t)(16 * bid + rr + r) * D_ + 8 * lane);
                    const uint4 qb = ldg128(q + (size_t)(16 * bid + rr + r) * D_ + 8 * (lane + 32));
                    uint32_t* x = xq[r >> 1][r & 1];
                    x[0] = qa.x; x[1] = qa.y; x[2] = qa.z; x[3] = qa.w; x[4] = qb.x; x[5] = qb.y; x[6] = qb.z; x[7] = qb.w;
                }
#pragma unroll
                for (int r2 = 0; r2 < 4; r2++) {
                    float2 sa[2];
                    ln_stats2(xq[r2], sa);
                    if (lane == 0) *reinterpret_cast<float4*>(&g_st1[16 * bid + rr + 2 * r2]) = make_float4(sa[0].x, sa[0].y, sa[1].x, sa[1].y);
                }
            }
            if (lane == 0) { __threadfence(); atomicAdd(&g_cnt, 1u); }
            if (warp == 9) return;
            {
                unsigned int c; int spins = 0;
                do { asm volatile("ld.acquire.gpu.global.u32 %0, [%1];" : "=r"(c) : "l"(&g_cnt) : "memory"); } while (c < 2 * gridDim.x && ++spins < (1 << 22));
            }
            if (lane == 0) {
                asm volatile("fence.proxy.async;" ::: "memory");
                mbar_expect_tx(hbar + 8, 16384);
                asm volatile("cp.async.bulk.shared::cluster.global.mbarrier::complete_tx::bytes [%0], [%1], %2, [%3];"
                    :: "r"(smem_u32(&sm.st[0])), "l"(&g_st1[0]), "r"(16384), "r"(hbar + 8) : "memory");
            }
            mbar_wait(hbar + 8, 0);
            named_bar(7, 288);
        } else {
            if (lane == 0) asm volatile("cp.async.bulk.prefetch.L2.global [%0], %1;" :: "l"(wd + (size_t)bid * 7168), "r"(14336) : "memory");
            if (bid < 112) {
                if (lane == 0) {
                    mbar_expect_tx(hbar, 32768);
                    const CUtensorMap* mw = (bid < 56) ? &mapWg : &mapWu;
                    const int col = 32 * ((bid < 56) ? bid : bid - 56);
                    tma_load_2d(smem_u32(&sm.wS[0][0]), mw, hbar, col, 0);
                    tma_load_2d(smem_u32(&sm.wS[256][0]), mw, hbar, col, 256);
                }
                mbar_wait(hbar, 0);
                const int cq = lane & 3, rgp = lane >> 2;
                float cs[8];
#pragma unroll
                for (int i = 0; i < 8; i++) cs[i] = 0.f;
#pragma unroll 4
                for (int r = 0; r < 64; r++) {
                    const uint4 w = sm.wS[r * 8 + rgp][cq];
                    cs[0] += bf_lo(w.x); cs[1] += bf_hi(w.x); cs[2] += bf_lo(w.y); cs[3] += bf_hi(w.y);
                    cs[4] += bf_lo(w.z); cs[5] += bf_hi(w.z); cs[6] += bf_lo(w.w); cs[7] += bf_hi(w.w);
                }
#pragma unroll
                for (int i = 0; i < 8; i++) {
                    cs[i] += __shfl_xor_sync(0xffffffffu, cs[i], 4);
                    cs[i] += __shfl_xor_sync(0xffffffffu, cs[i], 8);
                    cs[i] += __shfl_xor_sync(0xffffffffu, cs[i], 16);
                }
                if (lane < 4) {
                    *reinterpret_cast<float4*>(&g_colsum[32 * bid + lane * 8]) = make_float4(cs[0], cs[1], cs[2], cs[3]);
                    *reinterpret_cast<float4*>(&g_colsum[32 * bid + lane * 8 + 4]) = make_float4(cs[4], cs[5], cs[6], cs[7]);
                }
            }
        }
    }
#undef TMT
}

constexpr int G1_THREADS = 384;
constexpr int G1_STAGES = 3;
constexpr int G1_A_BYTES = 8 * 16384;
constexpr int G1_B_STAGE = 32768;
constexpr int G1_OFF_B = G1_A_BYTES;
constexpr int G1_OFF_STATS = G1_OFF_B + G1_STAGES * G1_B_STAGE;
constexpr int G1_OFF_CS = G1_OFF_STATS + 1024;
constexpr int G1_OFF_BAR = G1_OFF_CS + 1792;
constexpr int G1_SMEM = G1_OFF_BAR + 128;

__device__ __forceinline__ float tanh_fast(float x) { float t; asm("tanh.approx.f32 %0, %1;" : "=f"(t) : "f"(x)); return t; }

template <int NT>
__device__ __forceinline__ void g1_epilogue(const float (&acc)[NT * 8], const float* cs_g, const float* cs_u, float2 st0, float2 st1, bf16* out0, int t) {
    const float r0 = st0.y, r1 = st1.y, m0 = -st0.x * st0.y, m1 = -st1.x * st1.y;
#pragma unroll
    for (int j0 = 0; j0 < NT; j0 += 4) {
        uint32_t P0[4], P1[4];
#pragma unroll
        for (int jj = 0; jj < 4; jj++) {
            const int j = j0 + jj;
            const float2 cg = *reinterpret_cast<const float2*>(cs_g + 8 * j + 2 * t);
            const float2 cu = *reinterpret_cast<const float2*>(cs_u + 8 * j + 2 * t);
            float r[4];
#pragma unroll
            for (int e = 0; e < 4; e++) {
                const float rr = (e < 2) ? r0 : r1, mm = (e < 2) ? m0 : m1;
                const float gv = fmaf(acc[4 * j + e], rr, mm * ((e & 1) ? cg.y : cg.x));
                const float uv = fmaf(acc[4 * (NT + j) + e], rr, mm * ((e & 1) ? cu.y : cu.x));
                r[e] = fmaf(tanh_fast(0.5f * gv), 0.5f, 0.5f) * uv;
            }
            P0[jj] = pack_bf16(r[0], r[1]);
            P1[jj] = pack_bf16(r[2], r[3]);
        }
        quad_transpose(P0[0], P0[1], P0[2], P0[3], t);
        quad_transpose(P1[0], P1[1], P1[2], P1[3], t);
        *reinterpret_cast<uint4*>(out0 + 8 * (j0 + t)) = make_uint4(P0[0], P0[1], P0[2], P0[3]);
        *reinterpret_cast<uint4*>(out0 + 8 * F_ + 8 * (j0 + t)) = make_uint4(P1[0], P1[1], P1[2], P1[3]);
    }
}

__global__ void __cluster_dims__(2, 1, 1) __launch_bounds__(G1_THREADS, 1)
gemm1_kernel(const __grid_constant__ CUtensorMap mapA, const __grid_constant__ CUtensorMap mapG4, const __grid_constant__ CUtensorMap mapU4,
             const __grid_constant__ CUtensorMap mapG3, const __grid_constant__ CUtensorMap mapU3) {
    extern __shared__ __align__(1024) uint8_t smem_raw[];
    const uint32_t sb = smem_u32(smem_raw);
    const int tid = threadIdx.x, lane = tid & 31, warp = tid >> 5, wgi = tid >> 7;
    const int rank = blockIdx.x & 1;
    const int cb = blockIdx.x & 7, rb = blockIdx.x >> 3;
#define TMT 128
    TM(2, 0);
    pdl_launch();
    if (tid == 32) { prefetch_map(&mapA); prefetch_map(&mapG3); prefetch_map(&mapU3); }
    const uint32_t barA = sb + G1_OFF_BAR;
    const uint32_t barF = barA + 64;
    const uint32_t barE = barF + 8 * G1_STAGES;
    const uint32_t barS = barE + 8 * G1_STAGES;
    if (tid == 0) {
        for (int i = 0; i < 8; i++) mbar_init(barA + 8 * i, 1);
        for (int i = 0; i < G1_STAGES; i++) { mbar_init(barF + 8 * i, 1); mbar_init(barE + 8 * i, 2); }
        mbar_init(barS, 1);
        for (int i = 0; i < 8; i++) mbar_expect_tx(barA + 8 * i, 16384);
        asm volatile("fence.mbarrier_init.release.cluster;" ::: "memory");
    }
    __syncthreads();
    cluster_arrive_relaxed();

    if (wgi == 0) {
        reg_dealloc<40>();
        if (warp == 0) {
            if (lane == 0) {
                int st = 0, ph = 1;
                for (int it = 0; it < 16; it++) {
                    const int kc = it & 7;
                    mbar_wait(barE + 8 * st, ph);
                    const uint32_t dst = sb + G1_OFF_B + st * G1_B_STAGE;
                    if (it < 8) {
                        mbar_expect_tx(barF + 8 * st, 32768);
                        tma_load_3d(dst, &mapG4, barF + 8 * st, 0, kc * 64, cb * 7);
                        tma_load_3d(dst + 16384, &mapU4, barF + 8 * st, 0, kc * 64, cb * 7);
                    } else {
                        mbar_expect_tx(barF + 8 * st, 24576);
                        tma_load_3d(dst, &mapG3, barF + 8 * st, 0, kc * 64, cb * 7 + 4);
                        tma_load_3d(dst + 12288, &mapU3, barF + 8 * st, 0, kc * 64, cb * 7 + 4);
                    }
                    if (++st == G1_STAGES) { st = 0; ph ^= 1; }
                }
            }
            __syncwarp();
            cluster_wait();
        } else if (warp == 1) {
            cluster_wait();
            pdl_wait();
            if (lane < 8) {
                const int c = 2 * (lane >> 1) + rank, mh = lane & 1;
                tma_load_2d_mc(sb + c * 16384 + mh * 8192, &mapA, barA + 8 * c, rb * 128 + mh * 64, c * 64, (uint16_t)3);
            }
            __syncwarp();
            float* cs = reinterpret_cast<float*>(smem_raw + G1_OFF_CS);
            for (int i = lane; i < 448; i += 32) cs[i] = __ldcg((i < 224) ? &g_colsum[cb * 224 + i] : &g_colsum[F_ + cb * 224 + (i - 224)]);
            __syncwarp();
            if (lane == 0) mbar_arrive(barS);
        } else {
            cluster_wait();
        }
    } else {
        reg_alloc<232>();
        cluster_wait();
        const int cw = wgi - 1;
        const int g = lane >> 2, t = lane & 3, wl = warp & 3, tl = tid & 127;
        bf16* outp = g_hh + (size_t)(rb * 128 + cw * 64 + wl * 16 + g) * F_ + cb * 224;
        const float* cs = reinterpret_cast<const float*>(smem_raw + G1_OFF_CS);
        int st = 0, ph = 0;
        float2 st0, st1;
        {
            float acc[128];
            const int kq = lane >> 3, mp = lane & 7;
            const uint8_t* sbase = smem_raw + cw * 8192 + kq * 128 + (mp & 3) * 4;
            const int mc = 2 * wl + (mp >> 2);
            float p0 = 0.f, p1 = 0.f, s0 = 0.f, s1 = 0.f, q0 = 0.f, q1 = 0.f;
#pragma unroll 1
            for (int kc = 0; kc < 8; kc++) {
                mbar_wait(barA + 8 * kc, 0);
                mbar_wait(barF + 8 * st, ph);
                if (tl == 0 && cw == 0) TR(1, kc);
                wgmma_fence();
                const uint32_t aaddr = sb + kc * 16384 + cw * 8192;
                const uint32_t baddr = sb + G1_OFF_B + st * G1_B_STAGE;
#pragma unroll
                for (int kk = 0; kk < 4; kk++)
                    wgmma_m64n256k16_ss(acc, make_desc(aaddr + kk * 2048, 8192, 1024, 1), make_desc(baddr + kk * 1024, 4096, 512, 2), (kc | kk) != 0);
                wgmma_commit();
                if (kc == 0) {
                    const uint32_t w = *reinterpret_cast<const uint32_t*>(smem_raw + cw * 8192 + (mc << 4) + (mp & 3) * 4);
                    p0 = bf_lo(w); p1 = bf_hi(w);
                }
#pragma unroll
                for (int i = 0; i < 16; i++) {
                    const int kr = 4 * i;
                    const uint32_t w = *reinterpret_cast<const uint32_t*>(sbase + kc * 16384 + kr * 128 + ((mc ^ ((kr + kq) & 7)) << 4));
                    const float d0 = bf_lo(w) - p0, d1 = bf_hi(w) - p1;
                    s0 += d0; s1 += d1; q0 = fmaf(d0, d0, q0); q1 = fmaf(d1, d1, q1);
                }
                wgmma_wait<0>();
                if (tl == 0) mbar_arrive(barE + 8 * st);
                if (++st == G1_STAGES) { st = 0; ph ^= 1; }
            }
            TM(2, 1);
            {
#pragma unroll
                for (int o = 8; o <= 16; o <<= 1) {
                    s0 += __shfl_xor_sync(0xffffffffu, s0, o); s1 += __shfl_xor_sync(0xffffffffu, s1, o);
                    q0 += __shfl_xor_sync(0xffffffffu, q0, o); q1 += __shfl_xor_sync(0xffffffffu, q1, o);
                }
                const float md0 = s0 * (1.0f / D_), md1 = s1 * (1.0f / D_);
                const float v0 = bf16r(fmaxf(fmaf(-md0, md0, q0 * (1.0f / D_)), 0.f)), v1 = bf16r(fmaxf(fmaf(-md1, md1, q1 * (1.0f / D_)), 0.f));
                const float ma = bf16r(p0 + md0), mb = bf16r(p1 + md1);
                const float ra = 1.0f / bf16r(sqrtf(bf16r(v0 + 1e-5f))), rbb = 1.0f / bf16r(sqrtf(bf16r(v1 + 1e-5f)));
                const float mA = __shfl_sync(0xffffffffu, ma, g >> 1), mB = __shfl_sync(0xffffffffu, mb, g >> 1);
                const float rA = __shfl_sync(0xffffffffu, ra, g >> 1), rB = __shfl_sync(0xffffffffu, rbb, g >> 1);
                const float mC = __shfl_sync(0xffffffffu, ma, 4 + (g >> 1)), mD = __shfl_sync(0xffffffffu, mb, 4 + (g >> 1));
                const float rC = __shfl_sync(0xffffffffu, ra, 4 + (g >> 1)), rD = __shfl_sync(0xffffffffu, rbb, 4 + (g >> 1));
                st0 = (g & 1) ? make_float2(mB, rB) : make_float2(mA, rA);
                st1 = (g & 1) ? make_float2(mD, rD) : make_float2(mC, rC);
            }
            mbar_wait(barS, 0);
            pdl_wait();
            TM(2, 5);
            g1_epilogue<16>(acc, cs, cs + 224, st0, st1, outp, t);
            TM(2, 2);
        }
        {
            float acc[96];
#pragma unroll 1
            for (int kc = 0; kc < 8; kc++) {
                mbar_wait(barF + 8 * st, ph);
                if (tl == 0 && cw == 0) TR(1, 8 + kc);
                wgmma_fence();
                const uint32_t aaddr = sb + kc * 16384 + cw * 8192;
                const uint32_t baddr = sb + G1_OFF_B + st * G1_B_STAGE;
#pragma unroll
                for (int kk = 0; kk < 4; kk++)
                    wgmma_m64n192k16_ss(acc, make_desc(aaddr + kk * 2048, 8192, 1024, 1), make_desc(baddr + kk * 1024, 4096, 512, 2), (kc | kk) != 0);
                wgmma_commit();
                wgmma_wait<0>();
                if (tl == 0) mbar_arrive(barE + 8 * st);
                if (++st == G1_STAGES) { st = 0; ph ^= 1; }
            }
            TM(2, 3);
            g1_epilogue<12>(acc, cs + 128, cs + 224 + 128, st0, st1, outp + 128, t);
            TM(2, 4);
        }
    }
}

constexpr int G2_THREADS = 384;
constexpr int G2_STAGES = 6;
constexpr int G2_STAGE = 32768;
constexpr int G2_OFF_X = G2_STAGES * G2_STAGE;
constexpr int G2_OFF_BAR = G2_OFF_X + 32768;
constexpr int G2_SMEM = G2_OFF_BAR + 128;
constexpr int G2_KSTEPS = 14;

__device__ __forceinline__ void ldsm_x4_t(uint32_t& r0, uint32_t& r1, uint32_t& r2, uint32_t& r3, uint32_t addr) {
    asm volatile("ldmatrix.sync.aligned.m8n8.x4.trans.shared.b16 {%0,%1,%2,%3}, [%4];" : "=r"(r0), "=r"(r1), "=r"(r2), "=r"(r3) : "r"(addr) : "memory");
}

__global__ void __cluster_dims__(2, 1, 1) __launch_bounds__(G2_THREADS, 1)
gemm2_kernel(const __grid_constant__ CUtensorMap mapHH, const __grid_constant__ CUtensorMap mapWd, const __grid_constant__ CUtensorMap mapH,
             bf16* __restrict__ out) {
    extern __shared__ __align__(1024) uint8_t smem_raw[];
    const uint32_t sb = smem_u32(smem_raw);
    const int tid = threadIdx.x, lane = tid & 31, warp = tid >> 5, wgi = tid >> 7;
    const int ks = blockIdx.x & 1, nb = (blockIdx.x >> 1) & 3, rb = blockIdx.x >> 3;
    TM(3, 0);
    if (tid == 32) { prefetch_map(&mapHH); prefetch_map(&mapH); }
    const uint32_t barF = sb + G2_OFF_BAR;
    const uint32_t barE = barF + 8 * G2_STAGES;
    const uint32_t barX = barE + 8 * G2_STAGES;
    if (tid == 0) {
        for (int i = 0; i < G2_STAGES; i++) { mbar_init(barF + 8 * i, 1); mbar_init(barE + 8 * i, 2); }
        mbar_init(barX, 1);
        asm volatile("fence.mbarrier_init.release.cluster;" ::: "memory");
        mbar_expect_tx(barX, 32768);
        for (int it = 0; it < G2_STAGES; it++) {
            mbar_expect_tx(barF + 8 * it, 32768);
            tma_load_3d(sb + it * G2_STAGE + 16384, &mapWd, barF + 8 * it, 0, ks * 896 + it * 64, nb * 2);
        }
    }
    __syncthreads();
    cluster_arrive_relaxed();

    if (wgi == 0) {
        if (tid == 0) {
            pdl_wait();
            for (int it = 0; it < G2_STAGES; it++)
                tma_load_2d(sb + it * G2_STAGE, &mapHH, barF + 8 * it, ks * 896 + it * 64, rb * 128);
            if (blockIdx.x == 0) g_cnt = 0u;
            int st = 0, ph = 0;
            for (int it = G2_STAGES; it < G2_KSTEPS; it++) {
                mbar_wait(barE + 8 * st, ph);
                const uint32_t dst = sb + st * G2_STAGE;
                const int k0 = ks * 896 + it * 64;
                mbar_expect_tx(barF + 8 * st, 32768);
                tma_load_2d(dst, &mapHH, barF + 8 * st, k0, rb * 128);
                tma_load_3d(dst + 16384, &mapWd, barF + 8 * st, 0, k0, nb * 2);
                if (++st == G2_STAGES) { st = 0; ph ^= 1; }
            }
            mbar_wait(barE + 8 * st, ph);
            mbar_expect_tx(barF + 8 * st, 16384);
            tma_load_2d(sb + st * G2_STAGE, &mapH, barF + 8 * st, rb * 128 + ks * 64, nb * 128);
        }
        __syncwarp();
        cluster_wait();
    } else {
        const int cw = wgi - 1;
        const int g = lane >> 2, t = lane & 3, wl = warp & 3;
        const int tl = tid & 127;
        int st = 0, ph = 0;
        float acc[64];
#pragma unroll 1
        for (int it = 0; it < G2_KSTEPS; it++) {
            mbar_wait(barF + 8 * st, ph);
            if (it == 0) TM(3, 1);
            wgmma_fence();
            const uint32_t aaddr = sb + st * G2_STAGE + cw * 8192;
            const uint32_t baddr = sb + st * G2_STAGE + 16384;
#pragma unroll
            for (int kk = 0; kk < 4; kk++)
                wgmma_m64n128k16_ss(acc, make_desc(aaddr + kk * 32, 16, 1024, 1), make_desc(baddr + kk * 2048, 8192, 1024, 1), (it | kk) != 0);
            wgmma_commit();
            wgmma_wait<0>();
            if (tl == 0) mbar_arrive(barE + 8 * st);
            if (++st == G2_STAGES) { st = 0; ph ^= 1; }
        }
        TM(3, 2);
        cluster_wait();
        if (cw != ks) {
            const uint32_t dst = mapa(sb + G2_OFF_X + tl * 16, (uint32_t)(ks ^ 1));
            const uint32_t rbar = mapa(barX, (uint32_t)(ks ^ 1));
#pragma unroll
            for (int i = 0; i < 16; i++) st_async_v4f(dst + i * 2048, acc[4 * i], acc[4 * i + 1], acc[4 * i + 2], acc[4 * i + 3], rbar);
        } else {
            const float4* xb = reinterpret_cast<const float4*>(smem_raw + G2_OFF_X) + tl;
            const int row0 = rb * 128 + cw * 64 + wl * 16 + g;
            bf16* o0 = out + (size_t)row0 * D_ + nb * 128;
            uint32_t ha[16], hb[16];
            mbar_wait(barF + 8 * st, ph);
            {
                const int chl = 8 * (lane >> 4) + (lane & 7), sb8 = 2 * wl + ((lane >> 3) & 1);
                const uint32_t hbase = sb + st * G2_STAGE + chl * 128 + ((sb8 ^ (lane & 7)) << 4);
#pragma unroll
                for (int j = 0; j < 16; j += 2) ldsm_x4_t(ha[j], hb[j], ha[j + 1], hb[j + 1], hbase + j * 1024);
            }
            mbar_wait_cluster(barX, 0);
            TM(3, 4);
#pragma unroll
            for (int j0 = 0; j0 < 16; j0 += 4) {
                uint32_t P0[4], P1[4];
#pragma unroll
                for (int jj = 0; jj < 4; jj++) {
                    const int j = j0 + jj;
                    const float4 x = xb[j * 128];
                    P0[jj] = hadd2(ha[j], pack_bf16(acc[4 * j] + x.x, acc[4 * j + 1] + x.y));
                    P1[jj] = hadd2(hb[j], pack_bf16(acc[4 * j + 2] + x.z, acc[4 * j + 3] + x.w));
                }
                quad_transpose(P0[0], P0[1], P0[2], P0[3], t);
                quad_transpose(P1[0], P1[1], P1[2], P1[3], t);
                *reinterpret_cast<uint4*>(o0 + 8 * (j0 + t)) = make_uint4(P0[0], P0[1], P0[2], P0[3]);
                *reinterpret_cast<uint4*>(o0 + 8 * D_ + 8 * (j0 + t)) = make_uint4(P1[0], P1[1], P1[2], P1[3]);
            }
        }
        TM(3, 5);
    }
#undef TMT
}

typedef CUresult (*EncodeFn)(CUtensorMap*, CUtensorMapDataType, cuuint32_t, void*, const cuuint64_t*, const cuuint64_t*,
                             const cuuint32_t*, const cuuint32_t*, CUtensorMapInterleave, CUtensorMapSwizzle,
                             CUtensorMapL2promotion, CUtensorMapFloatOOBfill);

static void enc2d(EncodeFn enc, CUtensorMap* m, const void* p, int rows, int cols, int brows, int bcols) {
    cuuint64_t dims[2] = {(cuuint64_t)cols, (cuuint64_t)rows};
    cuuint64_t strides[1] = {(cuuint64_t)cols * 2};
    cuuint32_t box[2] = {(cuuint32_t)bcols, (cuuint32_t)brows};
    cuuint32_t es[2] = {1, 1};
    enc(m, CU_TENSOR_MAP_DATA_TYPE_BFLOAT16, 2, const_cast<void*>(p), dims, strides, box, es, CU_TENSOR_MAP_INTERLEAVE_NONE,
        bcols == 32 ? CU_TENSOR_MAP_SWIZZLE_64B : CU_TENSOR_MAP_SWIZZLE_128B, CU_TENSOR_MAP_L2_PROMOTION_L2_128B, CU_TENSOR_MAP_FLOAT_OOB_FILL_NONE);
}
static void enc2d_plain(EncodeFn enc, CUtensorMap* m, const void* p, int rows, int cols, int brows, int bcols) {
    cuuint64_t dims[2] = {(cuuint64_t)cols, (cuuint64_t)rows};
    cuuint64_t strides[1] = {(cuuint64_t)cols * 2};
    cuuint32_t box[2] = {(cuuint32_t)bcols, (cuuint32_t)brows};
    cuuint32_t es[2] = {1, 1};
    enc(m, CU_TENSOR_MAP_DATA_TYPE_BFLOAT16, 2, const_cast<void*>(p), dims, strides, box, es, CU_TENSOR_MAP_INTERLEAVE_NONE,
        CU_TENSOR_MAP_SWIZZLE_NONE, CU_TENSOR_MAP_L2_PROMOTION_L2_128B, CU_TENSOR_MAP_FLOAT_OOB_FILL_NONE);
}
static void enc3d(EncodeFn enc, CUtensorMap* m, const void* p, int rows, int cols, int atom, int brows, int natoms) {
    cuuint64_t dims[3] = {(cuuint64_t)atom, (cuuint64_t)rows, (cuuint64_t)(cols / atom)};
    cuuint64_t strides[2] = {(cuuint64_t)cols * 2, (cuuint64_t)atom * 2};
    cuuint32_t box[3] = {(cuuint32_t)atom, (cuuint32_t)brows, (cuuint32_t)natoms};
    cuuint32_t es[3] = {1, 1, 1};
    enc(m, CU_TENSOR_MAP_DATA_TYPE_BFLOAT16, 3, const_cast<void*>(p), dims, strides, box, es, CU_TENSOR_MAP_INTERLEAVE_NONE,
        atom == 32 ? CU_TENSOR_MAP_SWIZZLE_64B : CU_TENSOR_MAP_SWIZZLE_128B, CU_TENSOR_MAP_L2_PROMOTION_L2_128B, CU_TENSOR_MAP_FLOAT_OOB_FILL_NONE);
}

extern "C" void kernel_launch(void* const* d_in, const int* in_sizes, int n_in, void* d_out, int out_size) {
    const bf16* q = (const bf16*)d_in[0];
    const bf16* k = (const bf16*)d_in[1];
    const bf16* v = (const bf16*)d_in[2];
    const bf16* shift_k = (const bf16*)d_in[3];
    const bf16* ssm_k = (const bf16*)d_in[4];
    const bf16* ssm_D = (const bf16*)d_in[5];
    const bf16* wg = (const bf16*)d_in[7];
    const bf16* wu = (const bf16*)d_in[8];
    const bf16* wd = (const bf16*)d_in[9];
    bf16* out = (bf16*)d_out;

    static EncodeFn enc = nullptr;
    static void *p_hT = nullptr, *p_hh = nullptr;
    if (!enc) {
        void* fn = nullptr; cudaDriverEntryPointQueryResult qr;
        cudaGetDriverEntryPoint("cuTensorMapEncodeTiled", &fn, cudaEnableDefault, &qr);
        enc = (EncodeFn)fn;
        cudaGetSymbolAddress(&p_hT, g_hT);
        cudaGetSymbolAddress(&p_hh, g_hh);
        cudaFuncSetAttribute(conv_kernel, cudaFuncAttributeMaxDynamicSharedMemorySize, (int)sizeof(K1Smem));
        cudaFuncSetAttribute(gemm1_kernel, cudaFuncAttributeMaxDynamicSharedMemorySize, G1_SMEM);
        cudaFuncSetAttribute(gemm2_kernel, cudaFuncAttributeMaxDynamicSharedMemorySize, G2_SMEM);
    }
    CUtensorMap mA, mG64, mU64, mG32, mU32, mHH, mWd, mH, mWgp, mWup;
    enc2d_plain(enc, &mWgp, wg, D_, F_, 256, 32);
    enc2d_plain(enc, &mWup, wu, D_, F_, 256, 32);
    enc2d(enc, &mA, p_hT, D_, S_, 64, 64);
    enc2d(enc, &mH, p_hT, D_, S_, 128, 64);
    enc3d(enc, &mG64, wg, D_, F_, 32, 64, 4);
    enc3d(enc, &mU64, wu, D_, F_, 32, 64, 4);
    enc3d(enc, &mG32, wg, D_, F_, 32, 64, 3);
    enc3d(enc, &mU32, wu, D_, F_, 32, 64, 3);
    enc2d(enc, &mHH, p_hh, S_, F_, 128, 64);
    enc3d(enc, &mWd, wd, F_, D_, 64, 64, 2);

    cudaStream_t st = cudaStreamPerThread;
    cudaLaunchAttribute at[1];
    at[0].id = cudaLaunchAttributeProgrammaticStreamSerialization;
    at[0].val.programmaticStreamSerializationAllowed = 1;
    cudaLaunchConfig_t cfg = {};
    cfg.stream = st; cfg.attrs = at; cfg.numAttrs = 1;
    conv_kernel<<<128, K1_THREADS, sizeof(K1Smem), st>>>(q, k, v, shift_k, ssm_k, ssm_D, mWgp, mWup, wd);
    cfg.gridDim = dim3(128); cfg.blockDim = dim3(G1_THREADS); cfg.dynamicSmemBytes = G1_SMEM;
    cudaLaunchKernelEx(&cfg, gemm1_kernel, mA, mG64, mU64, mG32, mU32);
    cfg.gridDim = dim3(128); cfg.blockDim = dim3(G2_THREADS); cfg.dynamicSmemBytes = G2_SMEM;
    cudaLaunchKernelEx(&cfg, gemm2_kernel, mHH, mWd, mH, out);
}
```

```cpp
#include <cuda_runtime.h>
#include <cuda_bf16.h>
#include <cuda.h>
#include <stdint.h>

typedef __nv_bfloat16 bf16;
constexpr int S_ = 2048, D_ = 512, F_ = 1792;

__device__ bf16 g_hT[D_ * S_];
__device__ bf16 g_hh[S_ * F_];
__device__ __align__(128) float g_st1[S_ + S_ / 2];
__device__ float g_colsum[2 * F_];
__device__ unsigned int g_cnt;

#define TM(k, i)
#define TR(k, i)
__device__ __forceinline__ uint32_t smem_u32(const void* p) { return (uint32_t)__cvta_generic_to_shared(p); }
__device__ __forceinline__ float bf16r(float x) { return __bfloat162float(__float2bfloat16_rn(x)); }
__device__ __forceinline__ float bf_lo(uint32_t w) { return __uint_as_float(w << 16); }
__device__ __forceinline__ float bf_hi(uint32_t w) { return __uint_as_float(w & 0xffff0000u); }
__device__ __forceinline__ uint32_t pack_bf16(float lo, float hi) {
    __nv_bfloat162 v = __floats2bfloat162_rn(lo, hi);
    return *reinterpret_cast<uint32_t*>(&v);
}
__device__ __forceinline__ uint32_t hmul2(uint32_t a, uint32_t b) {
    __nv_bfloat162 r = __hmul2_rn(*reinterpret_cast<__nv_bfloat162*>(&a), *reinterpret_cast<__nv_bfloat162*>(&b));
    return *reinterpret_cast<uint32_t*>(&r);
}
__device__ __forceinline__ uint32_t hadd2(uint32_t a, uint32_t b) {
    __nv_bfloat162 r = __hadd2_rn(*reinterpret_cast<__nv_bfloat162*>(&a), *reinterpret_cast<__nv_bfloat162*>(&b));
    return *reinterpret_cast<uint32_t*>(&r);
}
__device__ __forceinline__ uint4 ldg128(const void* p) {
    uint4 r; asm volatile("ld.global.nc.v4.u32 {%0,%1,%2,%3}, [%4];" : "=r"(r.x), "=r"(r.y), "=r"(r.z), "=r"(r.w) : "l"(p)); return r;
}
__device__ __forceinline__ uint4 ldcg128(const void* p) {
    uint4 r; asm volatile("ld.global.cg.v4.u32 {%0,%1,%2,%3}, [%4];" : "=r"(r.x), "=r"(r.y), "=r"(r.z), "=r"(r.w) : "l"(p)); return r;
}
__device__ __forceinline__ uint32_t ldg16(const void* p) {
    unsigned short r; asm volatile("ld.global.nc.u16 %0, [%1];" : "=h"(r) : "l"(p)); return (uint32_t)r;
}
__device__ __forceinline__ void mbar_init(uint32_t bar, int cnt) { asm volatile("mbarrier.init.shared::cta.b64 [%0], %1;" :: "r"(bar), "r"(cnt)); }
__device__ __forceinline__ void mbar_expect_tx(uint32_t bar, uint32_t bytes) { asm volatile("mbarrier.arrive.expect_tx.shared::cta.b64 _, [%0], %1;" :: "r"(bar), "r"(bytes) : "memory"); }
__device__ __forceinline__ void mbar_arrive(uint32_t bar) { asm volatile("mbarrier.arrive.shared::cta.b64 _, [%0];" :: "r"(bar) : "memory"); }
__device__ __forceinline__ void mbar_arrive_cluster(uint32_t bar, uint32_t cta) {
    asm volatile("{\n.reg .b32 ra;\nmapa.shared::cluster.u32 ra, %0, %1;\nmbarrier.arrive.shared::cluster.b64 _, [ra];\n}" :: "r"(bar), "r"(cta) : "memory");
}
__device__ __forceinline__ void mbar_wait(uint32_t bar, uint32_t parity) {
    asm volatile("{\n.reg .pred P1;\nLAB_WAIT:\nmbarrier.try_wait.parity.shared::cta.b64 P1, [%0], %1;\n@P1 bra DONE;\nbra LAB_WAIT;\nDONE:\n}" :: "r"(bar), "r"(parity) : "memory");
}
__device__ __forceinline__ void mbar_wait_cluster(uint32_t bar, uint32_t parity) {
    asm volatile("{\n.reg .pred P1;\nLAB_WAIT:\nmbarrier.try_wait.parity.acquire.cluster.shared::cta.b64 P1, [%0], %1;\n@P1 bra DONE;\nbra LAB_WAIT;\nDONE:\n}" :: "r"(bar), "r"(parity) : "memory");
}
__device__ __forceinline__ void tma_load_2d(uint32_t dst, const CUtensorMap* map, uint32_t bar, int c0, int c1) {
    asm volatile("cp.async.bulk.tensor.2d.shared::cluster.global.mbarrier::complete_tx::bytes [%0], [%1, {%3, %4}], [%2];"
        :: "r"(dst), "l"(map), "r"(bar), "r"(c0), "r"(c1) : "memory");
}
__device__ __forceinline__ void tma_load_2d_mc(uint32_t dst, const CUtensorMap* map, uint32_t bar, int c0, int c1, uint16_t mask) {
    asm volatile("cp.async.bulk.tensor.2d.shared::cluster.global.mbarrier::complete_tx::bytes.multicast::cluster [%0], [%1, {%3, %4}], [%2], %5;"
        :: "r"(dst), "l"(map), "r"(bar), "r"(c0), "r"(c1), "h"(mask) : "memory");
}
__device__ __forceinline__ void tma_load_3d(uint32_t dst, const CUtensorMap* map, uint32_t bar, int c0, int c1, int c2) {
    asm volatile("cp.async.bulk.tensor.3d.shared::cluster.global.mbarrier::complete_tx::bytes [%0], [%1, {%3, %4, %5}], [%2];"
        :: "r"(dst), "l"(map), "r"(bar), "r"(c0), "r"(c1), "r"(c2) : "memory");
}
__device__ __forceinline__ void cluster_arrive() { asm volatile("barrier.cluster.arrive.aligned;" ::: "memory"); }
__device__ __forceinline__ void cluster_arrive_relaxed() { asm volatile("barrier.cluster.arrive.relaxed.aligned;" ::: "memory"); }
__device__ __forceinline__ void cluster_wait() { asm volatile("barrier.cluster.wait.aligned;" ::: "memory"); }
__device__ __forceinline__ uint32_t mapa(uint32_t addr, uint32_t cta) {
    uint32_t r; asm volatile("mapa.shared::cluster.u32 %0, %1, %2;" : "=r"(r) : "r"(addr), "r"(cta)); return r;
}
__device__ __forceinline__ void st_async_v2(uint32_t addr, uint32_t a, uint32_t b, uint32_t rbar) {
    asm volatile("st.async.weak.shared::cluster.mbarrier::complete_tx::bytes.v2.b32 [%0], {%1, %2}, [%3];" :: "r"(addr), "r"(a), "r"(b), "r"(rbar) : "memory");
}
__device__ __forceinline__ void st_async_v4f(uint32_t addr, float a, float b, float c, float d, uint32_t rbar) {
    asm volatile("st.async.weak.shared::cluster.mbarrier::complete_tx::bytes.v4.f32 [%0], {%1, %2, %3, %4}, [%5];" :: "r"(addr), "f"(a), "f"(b), "f"(c), "f"(d), "r"(rbar) : "memory");
}
__device__ __forceinline__ void wgmma_fence() { asm volatile("wgmma.fence.sync.aligned;" ::: "memory"); }
__device__ __forceinline__ void wgmma_commit() { asm volatile("wgmma.commit_group.sync.aligned;" ::: "memory"); }
template <int N> __device__ __forceinline__ void wgmma_wait() { asm volatile("wgmma.wait_group.sync.aligned %0;" :: "n"(N) : "memory"); }
__device__ __forceinline__ uint64_t make_desc(uint32_t addr, uint32_t lbo_bytes, uint32_t sbo_bytes, uint32_t layout) {
    return (uint64_t)((addr & 0x3FFFF) >> 4) | ((uint64_t)(lbo_bytes >> 4) << 16) | ((uint64_t)(sbo_bytes >> 4) << 32) | ((uint64_t)layout << 62);
}
template <int R> __device__ __forceinline__ void reg_alloc() { asm volatile("setmaxnreg.inc.sync.aligned.u32 %0;" :: "n"(R)); }
template <int R> __device__ __forceinline__ void reg_dealloc() { asm volatile("setmaxnreg.dec.sync.aligned.u32 %0;" :: "n"(R)); }
__device__ __forceinline__ void pdl_launch() { asm volatile("griddepcontrol.launch_dependents;" ::: "memory"); }
__device__ __forceinline__ void pdl_wait() { asm volatile("griddepcontrol.wait;" ::: "memory"); }
__device__ __forceinline__ void prefetch_map(const CUtensorMap* m) { asm volatile("prefetch.tensormap [%0];" :: "l"(m) : "memory"); }
__device__ __forceinline__ void named_bar(int id, int n) { asm volatile("bar.sync %0, %1;" :: "r"(id), "r"(n) : "memory"); }

__device__ __forceinline__ void wgmma_m64n256k16_ss(float (&d)[128], uint64_t descA, uint64_t descB, int scaleD) {
    asm volatile("{\n.reg .pred p;\nsetp.ne.b32 p, %130, 0;\n"
        "wgmma.mma_async.sync.aligned.m64n256k16.f32.bf16.bf16 {%0, %1, %2, %3, %4, %5, %6, %7, %8, %9, %10, %11, %12, %13, %14, %15, %16, %17, %18, %19, %20, %21, %22, %23, %24, %25, %26, %27, %28, %29, %30, %31, %32, %33, %34, %35, %36, %37, %38, %39, %40, %41, %42, %43, %44, %45, %46, %47, %48, %49, %50, %51, %52, %53, %54, %55, %56, %57, %58, %59, %60, %61, %62, %63, %64, %65, %66, %67, %68, %69, %70, %71, %72, %73, %74, %75, %76, %77, %78, %79, %80, %81, %82, %83, %84, %85, %86, %87, %88, %89, %90, %91, %92, %93, %94, %95, %96, %97, %98, %99, %100, %101, %102, %103, %104, %105, %106, %107, %108, %109, %110, %111, %112, %113, %114, %115, %116, %117, %118, %119, %120, %121, %122, %123, %124, %125, %126, %127}, %128, %129, p, 1, 1, 1, 1;\n}\n"
        : "+f"(d[0]), "+f"(d[1]), "+f"(d[2]), "+f"(d[3]), "+f"(d[4]), "+f"(d[5]), "+f"(d[6]), "+f"(d[7]), "+f"(d[8]), "+f"(d[9]), "+f"(d[10]), "+f"(d[11]), "+f"(d[12]), "+f"(d[13]), "+f"(d[14]), "+f"(d[15]), "+f"(d[16]), "+f"(d[17]), "+f"(d[18]), "+f"(d[19]), "+f"(d[20]), "+f"(d[21]), "+f"(d[22]), "+f"(d[23]), "+f"(d[24]), "+f"(d[25]), "+f"(d[26]), "+f"(d[27]), "+f"(d[28]), "+f"(d[29]), "+f"(d[30]), "+f"(d[31]), "+f"(d[32]), "+f"(d[33]), "+f"(d[34]), "+f"(d[35]), "+f"(d[36]), "+f"(d[37]), "+f"(d[38]), "+f"(d[39]), "+f"(d[40]), "+f"(d[41]), "+f"(d[42]), "+f"(d[43]), "+f"(d[44]), "+f"(d[45]), "+f"(d[46]), "+f"(d[47]), "+f"(d[48]), "+f"(d[49]), "+f"(d[50]), "+f"(d[51]), "+f"(d[52]), "+f"(d[53]), "+f"(d[54]), "+f"(d[55]), "+f"(d[56]), "+f"(d[57]), "+f"(d[58]), "+f"(d[59]), "+f"(d[60]), "+f"(d[61]), "+f"(d[62]), "+f"(d[63]), "+f"(d[64]), "+f"(d[65]), "+f"(d[66]), "+f"(d[67]), "+f"(d[68]), "+f"(d[69]), "+f"(d[70]), "+f"(d[71]), "+f"(d[72]), "+f"(d[73]), "+f"(d[74]), "+f"(d[75]), "+f"(d[76]), "+f"(d[77]), "+f"(d[78]), "+f"(d[79]), "+f"(d[80]), "+f"(d[81]), "+f"(d[82]), "+f"(d[83]), "+f"(d[84]), "+f"(d[85]), "+f"(d[86]), "+f"(d[87]), "+f"(d[88]), "+f"(d[89]), "+f"(d[90]), "+f"(d[91]), "+f"(d[92]), "+f"(d[93]), "+f"(d[94]), "+f"(d[95]), "+f"(d[96]), "+f"(d[97]), "+f"(d[98]), "+f"(d[99]), "+f"(d[100]), "+f"(d[101]), "+f"(d[102]), "+f"(d[103]), "+f"(d[104]), "+f"(d[105]), "+f"(d[106]), "+f"(d[107]), "+f"(d[108]), "+f"(d[109]), "+f"(d[110]), "+f"(d[111]), "+f"(d[112]), "+f"(d[113]), "+f"(d[114]), "+f"(d[115]), "+f"(d[116]), "+f"(d[117]), "+f"(d[118]), "+f"(d[119]), "+f"(d[120]), "+f"(d[121]), "+f"(d[122]), "+f"(d[123]), "+f"(d[124]), "+f"(d[125]), "+f"(d[126]), "+f"(d[127])
        : "l"(descA), "l"(descB), "r"(scaleD));
}

__device__ __forceinline__ void wgmma_m64n192k16_ss(float (&d)[96], uint64_t descA, uint64_t descB, int scaleD) {
    asm volatile("{\n.reg .pred p;\nsetp.ne.b32 p, %98, 0;\n"
        "wgmma.mma_async.sync.aligned.m64n192k16.f32.bf16.bf16 {%0, %1, %2, %3, %4, %5, %6, %7, %8, %9, %10, %11, %12, %13, %14, %15, %16, %17, %18, %19, %20, %21, %22, %23, %24, %25, %26, %27, %28, %29, %30, %31, %32, %33, %34, %35, %36, %37, %38, %39, %40, %41, %42, %43, %44, %45, %46, %47, %48, %49, %50, %51, %52, %53, %54, %55, %56, %57, %58, %59, %60, %61, %62, %63, %64, %65, %66, %67, %68, %69, %70, %71, %72, %73, %74, %75, %76, %77, %78, %79, %80, %81, %82, %83, %84, %85, %86, %87, %88, %89, %90, %91, %92, %93, %94, %95}, %96, %97, p, 1, 1, 1, 1;\n}\n"
        : "+f"(d[0]), "+f"(d[1]), "+f"(d[2]), "+f"(d[3]), "+f"(d[4]), "+f"(d[5]), "+f"(d[6]), "+f"(d[7]), "+f"(d[8]), "+f"(d[9]), "+f"(d[10]), "+f"(d[11]), "+f"(d[12]), "+f"(d[13]), "+f"(d[14]), "+f"(d[15]), "+f"(d[16]), "+f"(d[17]), "+f"(d[18]), "+f"(d[19]), "+f"(d[20]), "+f"(d[21]), "+f"(d[22]), "+f"(d[23]), "+f"(d[24]), "+f"(d[25]), "+f"(d[26]), "+f"(d[27]), "+f"(d[28]), "+f"(d[29]), "+f"(d[30]), "+f"(d[31]), "+f"(d[32]), "+f"(d[33]), "+f"(d[34]), "+f"(d[35]), "+f"(d[36]), "+f"(d[37]), "+f"(d[38]), "+f"(d[39]), "+f"(d[40]), "+f"(d[41]), "+f"(d[42]), "+f"(d[43]), "+f"(d[44]), "+f"(d[45]), "+f"(d[46]), "+f"(d[47]), "+f"(d[48]), "+f"(d[49]), "+f"(d[50]), "+f"(d[51]), "+f"(d[52]), "+f"(d[53]), "+f"(d[54]), "+f"(d[55]), "+f"(d[56]), "+f"(d[57]), "+f"(d[58]), "+f"(d[59]), "+f"(d[60]), "+f"(d[61]), "+f"(d[62]), "+f"(d[63]), "+f"(d[64]), "+f"(d[65]), "+f"(d[66]), "+f"(d[67]), "+f"(d[68]), "+f"(d[69]), "+f"(d[70]), "+f"(d[71]), "+f"(d[72]), "+f"(d[73]), "+f"(d[74]), "+f"(d[75]), "+f"(d[76]), "+f"(d[77]), "+f"(d[78]), "+f"(d[79]), "+f"(d[80]), "+f"(d[81]), "+f"(d[82]), "+f"(d[83]), "+f"(d[84]), "+f"(d[85]), "+f"(d[86]), "+f"(d[87]), "+f"(d[88]), "+f"(d[89]), "+f"(d[90]), "+f"(d[91]), "+f"(d[92]), "+f"(d[93]), "+f"(d[94]), "+f"(d[95])
        : "l"(descA), "l"(descB), "r"(scaleD));
}

__device__ __forceinline__ void wgmma_m64n128k16_ss(float (&d)[64], uint64_t descA, uint64_t descB, int scaleD) {
    asm volatile("{\n.reg .pred p;\nsetp.ne.b32 p, %66, 0;\n"
        "wgmma.mma_async.sync.aligned.m64n128k16.f32.bf16.bf16 {%0, %1, %2, %3, %4, %5, %6, %7, %8, %9, %10, %11, %12, %13, %14, %15, %16, %17, %18, %19, %20, %21, %22, %23, %24, %25, %26, %27, %28, %29, %30, %31, %32, %33, %34, %35, %36, %37, %38, %39, %40, %41, %42, %43, %44, %45, %46, %47, %48, %49, %50, %51, %52, %53, %54, %55, %56, %57, %58, %59, %60, %61, %62, %63}, %64, %65, p, 1, 1, 0, 1;\n}\n"
        : "+f"(d[0]), "+f"(d[1]), "+f"(d[2]), "+f"(d[3]), "+f"(d[4]), "+f"(d[5]), "+f"(d[6]), "+f"(d[7]), "+f"(d[8]), "+f"(d[9]), "+f"(d[10]), "+f"(d[11]), "+f"(d[12]), "+f"(d[13]), "+f"(d[14]), "+f"(d[15]), "+f"(d[16]), "+f"(d[17]), "+f"(d[18]), "+f"(d[19]), "+f"(d[20]), "+f"(d[21]), "+f"(d[22]), "+f"(d[23]), "+f"(d[24]), "+f"(d[25]), "+f"(d[26]), "+f"(d[27]), "+f"(d[28]), "+f"(d[29]), "+f"(d[30]), "+f"(d[31]), "+f"(d[32]), "+f"(d[33]), "+f"(d[34]), "+f"(d[35]), "+f"(d[36]), "+f"(d[37]), "+f"(d[38]), "+f"(d[39]), "+f"(d[40]), "+f"(d[41]), "+f"(d[42]), "+f"(d[43]), "+f"(d[44]), "+f"(d[45]), "+f"(d[46]), "+f"(d[47]), "+f"(d[48]), "+f"(d[49]), "+f"(d[50]), "+f"(d[51]), "+f"(d[52]), "+f"(d[53]), "+f"(d[54]), "+f"(d[55]), "+f"(d[56]), "+f"(d[57]), "+f"(d[58]), "+f"(d[59]), "+f"(d[60]), "+f"(d[61]), "+f"(d[62]), "+f"(d[63])
        : "l"(descA), "l"(descB), "r"(scaleD));
}

__device__ __forceinline__ void quad_transpose(uint32_t& r0, uint32_t& r1, uint32_t& r2, uint32_t& r3, int t) {
    const bool o1 = t & 1, o2 = t & 2;
    uint32_t x, y;
    x = o1 ? r0 : r1; y = __shfl_xor_sync(0xffffffffu, x, 1); if (o1) r0 = y; else r1 = y;
    x = o1 ? r2 : r3; y = __shfl_xor_sync(0xffffffffu, x, 1); if (o1) r2 = y; else r3 = y;
    x = o2 ? r0 : r2; y = __shfl_xor_sync(0xffffffffu, x, 2); if (o2) r0 = y; else r2 = y;
    x = o2 ? r1 : r3; y = __shfl_xor_sync(0xffffffffu, x, 2); if (o2) r1 = y; else r3 = y;
}

__device__ __forceinline__ float warp_sum(float s) {
#pragma unroll
    for (int o = 16; o > 0; o >>= 1) s += __shfl_xor_sync(0xffffffffu, s, o);
    return s;
}
__device__ __forceinline__ uint32_t hsub2(uint32_t a, uint32_t b) {
    __nv_bfloat162 r = __hsub2_rn(*reinterpret_cast<__nv_bfloat162*>(&a), *reinterpret_cast<__nv_bfloat162*>(&b));
    return *reinterpret_cast<uint32_t*>(&r);
}
__device__ __forceinline__ void ln_stats2(const uint32_t (&x)[2][8], float2 (&st)[2]) {
    float piv[2], s[2], ss[2];
#pragma unroll
    for (int r = 0; r < 2; r++) piv[r] = __shfl_sync(0xffffffffu, bf_lo(x[r][0]), 0);
#pragma unroll
    for (int r = 0; r < 2; r++) {
        float s0 = 0.f, s1 = 0.f, q0 = 0.f, q1 = 0.f;
#pragma unroll
        for (int i = 0; i < 8; i++) {
            const float d0 = bf_lo(x[r][i]) - piv[r], d1 = bf_hi(x[r][i]) - piv[r];
            s0 += d0; s1 += d1; q0 = fmaf(d0, d0, q0); q1 = fmaf(d1, d1, q1);
        }
        s[r] = s0 + s1; ss[r] = q0 + q1;
    }
#pragma unroll
    for (int o = 16; o > 0; o >>= 1) {
#pragma unroll
        for (int r = 0; r < 2; r++) { s[r] += __shfl_xor_sync(0xffffffffu, s[r], o); ss[r] += __shfl_xor_sync(0xffffffffu, ss[r], o); }
    }
#pragma unroll
    for (int r = 0; r < 2; r++) {
        const float md = s[r] * (1.0f / D_);
        const float var = bf16r(fmaxf(fmaf(-md, md, ss[r] * (1.0f / D_)), 0.f));
        st[r] = make_float2(bf16r(piv[r] + md), 1.0f / bf16r(sqrtf(bf16r(var + 1e-5f))));
    }
}
__device__ __forceinline__ void ln_apply(const uint32_t (&x)[8], float2 st, uint32_t (&o)[8]) {
    const uint32_t m2 = pack_bf16(st.x, st.x);
#pragma unroll
    for (int i = 0; i < 8; i++) {
        const uint32_t d = hsub2(x[i], m2);
        o[i] = pack_bf16(bf_lo(d) * st.y, bf_hi(d) * st.y);
    }
}

constexpr int K1_THREADS = 352;
constexpr int UT_PAD = 128;
constexpr int UT_LEN = UT_PAD + S_;
constexpr int KR_LEN = 2080;
constexpr int YP_LEN = S_ + (S_ / 32) * 8;

struct __align__(128) K1Smem {
    bf16 uT[4][UT_LEN];
    bf16 xT[4][S_];
    bf16 kr[4][2][KR_LEN];
    float yP[4][YP_LEN];
    alignas(128) float st[S_ + S_ / 2];
    alignas(128) uint4 wS[512][4];
    float red[8][32];
    uint64_t bar, bar2, bar3, bar4;
};

__device__ __forceinline__ void mma16816(float (&c)[4], uint32_t a0, uint32_t a1, uint32_t a2, uint32_t a3, uint32_t b0, uint32_t b1) {
    asm("mma.sync.aligned.m16n8k16.row.col.f32.bf16.bf16.f32 {%0,%1,%2,%3}, {%4,%5,%6,%7}, {%8,%9}, {%0,%1,%2,%3};"
        : "+f"(c[0]), "+f"(c[1]), "+f"(c[2]), "+f"(c[3])
        : "r"(a0), "r"(a1), "r"(a2), "r"(a3), "r"(b0), "r"(b1));
}
__device__ __forceinline__ void ldsm_x4(uint32_t& r0, uint32_t& r1, uint32_t& r2, uint32_t& r3, uint32_t addr) {
    asm volatile("ldmatrix.sync.aligned.m8n8.x4.shared.b16 {%0,%1,%2,%3}, [%4];" : "=r"(r0), "=r"(r1), "=r"(r2), "=r"(r3) : "r"(addr) : "memory");
}

__device__ __forceinline__ void conv_mma(const bf16* uTc, const bf16* krlane, float (&acc)[16][4], int lane, int half) {
    const int lrow = lane & 7, lk = (lane >> 3) & 1, lt = lane >> 4;
    const uint32_t ubase = smem_u32(uTc) + (UT_PAD + 16 * (8 * lt + lrow) + 8 * lk) * 2;
#pragma unroll 1
    for (int pp = 0; pp < 4; pp++) {
        const int p = half * 4 + pp;
        uint32_t U[16][2];
#pragma unroll
        for (int j = 0; j < 16; j += 2) ldsm_x4(U[j][0], U[j][1], U[j + 1][0], U[j + 1][1], ubase + (j * 128 - p * 16) * 2);
        const uint32_t* kp = reinterpret_cast<const uint32_t*>(krlane - 16 * p);
        const volatile uint32_t* kpv = kp;
        uint32_t a0 = kp[0], a1 = kp[-4], a2 = kp[4], a3 = kpv[0];
#pragma unroll
        for (int q = 0; q < 16; q++) {
            uint32_t b0 = 0, b1 = 0, b2 = 0, b3 = 0;
            if (q < 15) { b0 = kp[-64 * (q + 1)]; b1 = kp[-64 * (q + 1) - 4]; b2 = kp[-64 * (q + 1) + 4]; b3 = kpv[-64 * (q + 1)]; }
#pragma unroll
            for (int n = 15; n >= q; n--) mma16816(acc[n], a0, a1, a2, a3, U[n - q][0], U[n - q][1]);
            a0 = b0; a1 = b1; a2 = b2; a3 = b3;
        }
    }
}

__device__ __forceinline__ void cp_async16(uint32_t dst, const void* src) {
    asm volatile("cp.async.cg.shared.global [%0], [%1], 16;" :: "r"(dst), "l"(src) : "memory");
}

__global__ void __cluster_dims__(2, 1, 1) __launch_bounds__(K1_THREADS, 1)
conv_kernel(const bf16* __restrict__ q, const bf16* __restrict__ k, const bf16* __restrict__ v,
            const bf16* __restrict__ shift_k, const bf16* __restrict__ ssm_k, const bf16* __restrict__ ssm_D,
            const __grid_constant__ CUtensorMap mapWg, const __grid_constant__ CUtensorMap mapWu, const bf16* __restrict__ wd) {
    extern __shared__ __align__(1024) uint8_t smem_raw[];
    pdl_launch();
    K1Smem& sm = *reinterpret_cast<K1Smem*>(smem_raw);
    const int tid = threadIdx.x, lane = tid & 31, warp = tid >> 5;
    const int bid = blockIdx.x;
    const int rank = bid & 1;
    const int c0 = 8 * (bid >> 1);
    const int cown = c0 + 4 * rank;
#define TMT 0
    TM(0, 0);
    const uint32_t bar = smem_u32(&sm.bar);
    if (tid == 0) {
        mbar_init(bar, 1);
        mbar_init(bar + 8, 1);
        mbar_init(bar + 16, 1);
        mbar_init(bar + 24, 1);
        asm volatile("fence.mbarrier_init.release.cluster;" ::: "memory");
        mbar_expect_tx(bar, 1024 * 4 * 2);
        mbar_expect_tx(bar + 8, 1024 * 4 * 2);
    }
    cluster_arrive_relaxed();

    if (warp < 8) {
        const int s0 = 1024 * rank + 4 * tid;
        uint4 kk[7], vv[4], qq[4], sw[4];
#pragma unroll
        for (int i = 0; i < 4; i++) kk[3 + i] = ldg128(k + (size_t)(s0 + i) * D_ + c0);
#pragma unroll
        for (int i = 0; i < 4; i++) vv[i] = ldg128(v + (size_t)(s0 + i) * D_ + c0);
        if (lane == 0) {
#pragma unroll
            for (int i = 0; i < 3; i++) {
                const int s = s0 - 3 + i;
                kk[i] = make_uint4(0, 0, 0, 0);
                if (s >= 0) kk[i] = ldg128(k + (size_t)s * D_ + c0);
            }
        }
#pragma unroll
        for (int i = 0; i < 4; i++) sw[i] = ldg128(shift_k + (size_t)c0 * 4 + 8 * i);
        uint4 kq[4]; uint32_t nx[4];
#pragma unroll
        for (int c = 0; c < 4; c++) {
            const bf16* kr = ssm_k + (size_t)(cown + c) * S_;
            kq[c] = ldg128(kr + 8 * tid);
            nx[c] = 0u;
            if (tid < 255) nx[c] = ldg16(kr + 8 * tid + 8);
        }
        const uint32_t dval = ldg16(ssm_D + cown + (warp >> 1));
        if (tid < 64) *reinterpret_cast<uint4*>(&sm.uT[tid >> 4][(tid & 15) * 8]) = make_uint4(0, 0, 0, 0);
#pragma unroll
        for (int i = 0; i < 3; i++) {
            uint4 t;
            t.x = __shfl_up_sync(0xffffffffu, kk[4 + i].x, 1); t.y = __shfl_up_sync(0xffffffffu, kk[4 + i].y, 1);
            t.z = __shfl_up_sync(0xffffffffu, kk[4 + i].z, 1); t.w = __shfl_up_sync(0xffffffffu, kk[4 + i].w, 1);
            if (lane != 0) kk[i] = t;
        }
        uint32_t kvw[4][4];
        const uint32_t* kkw = reinterpret_cast<const uint32_t*>(kk);
        const uint32_t* vvw = reinterpret_cast<const uint32_t*>(vv);
        const uint32_t* qqw = reinterpret_cast<const uint32_t*>(qq);
#pragma unroll
        for (int i2 = 0; i2 < 4; i2++) {
            const uint32_t t0 = __byte_perm(sw[i2].x, sw[i2].z, 0x5410), t1 = __byte_perm(sw[i2].x, sw[i2].z, 0x7632);
            const uint32_t t2 = __byte_perm(sw[i2].y, sw[i2].w, 0x5410), t3 = __byte_perm(sw[i2].y, sw[i2].w, 0x7632);
#pragma unroll
            for (int r = 0; r < 4; r++) {
                uint32_t a = hmul2(kkw[(r + 0) * 4 + i2], t3);
                a = hadd2(a, hmul2(kkw[(r + 1) * 4 + i2], t2));
                a = hadd2(a, hmul2(kkw[(r + 2) * 4 + i2], t1));
                a = hadd2(a, hmul2(kkw[(r + 3) * 4 + i2], t0));
                kvw[r][i2] = hmul2(a, vvw[r * 4 + i2]);
            }
        }
        TM(0, 1);
        cluster_wait();
        const uint32_t rbar = mapa(bar, (uint32_t)(rank ^ 1));
#pragma unroll
        for (int i2 = 0; i2 < 4; i2++) {
#pragma unroll
            for (int e = 0; e < 2; e++) {
                const uint32_t sel = e ? 0x7632 : 0x5410;
                const uint32_t w0 = __byte_perm(kvw[0][i2], kvw[1][i2], sel), w1 = __byte_perm(kvw[2][i2], kvw[3][i2], sel);
                const int cc = 2 * i2 + e;
                if ((cc >> 2) == rank) *reinterpret_cast<uint2*>(&sm.uT[cc & 3][UT_PAD + s0]) = make_uint2(w0, w1);
                else st_async_v2(mapa(smem_u32(&sm.uT[cc & 3][UT_PAD + s0]), (uint32_t)(rank ^ 1)), w0, w1, rbar);
            }
        }
#pragma unroll
        for (int c = 0; c < 4; c++) {
            uint4 a, b;
            a.x = __byte_perm(kq[c].w, 0, 0x1032); a.y = __byte_perm(kq[c].z, 0, 0x1032);
            a.z = __byte_perm(kq[c].y, 0, 0x1032); a.w = __byte_perm(kq[c].x, 0, 0x1032);
            b.x = __byte_perm(nx[c], kq[c].w, 0x7610); b.y = __byte_perm(kq[c].w, kq[c].z, 0x7610);
            b.z = __byte_perm(kq[c].z, kq[c].y, 0x7610); b.w = __byte_perm(kq[c].y, kq[c].x, 0x7610);
            *reinterpret_cast<uint4*>(&sm.kr[c][0][2040 - 8 * tid]) = a;
            *reinterpret_cast<uint4*>(&sm.kr[c][1][2040 - 8 * tid]) = b;
            if (tid == 0) {
                *reinterpret_cast<uint4*>(&sm.kr[c][1][2048]) = make_uint4(kq[c].x & 0xffffu, 0, 0, 0);
            } else if (tid < 8) {
                if (tid < 4) *reinterpret_cast<uint4*>(&sm.kr[c][1][2048 + 8 * tid]) = make_uint4(0, 0, 0, 0);
                else *reinterpret_cast<uint4*>(&sm.kr[c][0][2048 + 8 * (tid - 4)]) = make_uint4(0, 0, 0, 0);
            }
        }
#pragma unroll
        for (int i = 0; i < 4; i++) qq[i] = ldg128(q + (size_t)(s0 + i) * D_ + c0);
        TM(0, 3);
        named_bar(6, 352);
        mbar_wait_cluster(bar, 0);
        TM(0, 4);

        const int ch = warp >> 1, half = warp & 1;
        const int g = lane >> 2, t = lane & 3;
        float acc[16][4];
#pragma unroll
        for (int i = 0; i < 16; i++) { acc[i][0] = acc[i][1] = acc[i][2] = acc[i][3] = 0.f; }
        const bf16* krlane = (g & 1) ? &sm.kr[ch][0][2047 - g + 2 * t] : &sm.kr[ch][1][2048 - g + 2 * t];
        conv_mma(sm.uT[ch], krlane, acc, lane, half);
        TM(0, 5);
#pragma unroll
        for (int i2 = 0; i2 < 4; i2++) {
#pragma unroll
            for (int e = 0; e < 2; e++) {
                const uint32_t sel = e ? 0x7632 : 0x5410;
                const uint32_t w0 = __byte_perm(qqw[i2], qqw[4 + i2], sel), w1 = __byte_perm(qqw[8 + i2], qqw[12 + i2], sel);
                const int cc = 2 * i2 + e;
                if ((cc >> 2) == rank) *reinterpret_cast<uint2*>(&sm.xT[cc & 3][s0]) = make_uint2(w0, w1);
                else st_async_v2(mapa(smem_u32(&sm.xT[cc & 3][s0]), (uint32_t)(rank ^ 1)), w0, w1, rbar + 8);
            }
        }
        float* yp = &sm.yP[ch][40 * t + g];
        if (half) {
#pragma unroll
            for (int n = 0; n < 16; n++) {
                yp[160 * n] = acc[n][0];
                yp[160 * n + 16] = acc[n][1];
                yp[160 * n + 8] = acc[n][2];
                yp[160 * n + 24] = acc[n][3];
            }
        }
        named_bar(1 + ch, 64);
        if (!half) {
#pragma unroll
            for (int n = 0; n < 16; n++) {
                yp[160 * n] += acc[n][0];
                yp[160 * n + 16] += acc[n][1];
                yp[160 * n + 8] += acc[n][2];
                yp[160 * n + 24] += acc[n][3];
            }
        }
        named_bar(7, 288);
        mbar_wait_cluster(bar + 8, 0);
        TM(0, 6);
        {
            const int tt = tid & 63;
            bf16* dst = g_hT + (size_t)(cown + ch) * S_;
            const uint32_t d2 = dval * 0x10001u;
#pragma unroll
            for (int j = 0; j < 4; j++) {
                const int s = (j * 64 + tt) * 8;
                const float* src = &sm.yP[ch][s + (s >> 5) * 8];
                const float4 a = *reinterpret_cast<const float4*>(src), b = *reinterpret_cast<const float4*>(src + 4);
                const uint4 kv4 = *reinterpret_cast<const uint4*>(&sm.uT[ch][UT_PAD + s]);
                const uint4 x4 = *reinterpret_cast<const uint4*>(&sm.xT[ch][s]);
                const uint32_t y2[4] = {hadd2(pack_bf16(a.x, a.y), hmul2(kv4.x, d2)), hadd2(pack_bf16(a.z, a.w), hmul2(kv4.y, d2)),
                                        hadd2(pack_bf16(b.x, b.y), hmul2(kv4.z, d2)), hadd2(pack_bf16(b.z, b.w), hmul2(kv4.w, d2))};
                const uint32_t xw[4] = {x4.x, x4.y, x4.z, x4.w};
                const uint4 m4 = *reinterpret_cast<const uint4*>(&sm.st[S_ + s / 2]);
                const float4 ra = *reinterpret_cast<const float4*>(&sm.st[s]), rb4 = *reinterpret_cast<const float4*>(&sm.st[s + 4]);
                const uint32_t mw[4] = {m4.x, m4.y, m4.z, m4.w};
                const float rw[8] = {ra.x, ra.y, ra.z, ra.w, rb4.x, rb4.y, rb4.z, rb4.w};
                uint32_t o[4];
#pragma unroll
                for (int i = 0; i < 4; i++) {
                    const uint32_t d = hsub2(xw[i], mw[i]);
                    const uint32_t qn = pack_bf16(bf_lo(d) * rw[2 * i], bf_hi(d) * rw[2 * i + 1]);
                    o[i] = hadd2(xw[i], hmul2(qn, y2[i]));
                }
                *reinterpret_cast<uint4*>(dst + s) = make_uint4(o[0], o[1], o[2], o[3]);
            }
        }
        TM(0, 7);
    } else {
        cluster_wait();
        named_bar(6, 352);
        const uint32_t hbar = bar + 16;
        if (warp < 10) {
            {
                const int rr = 8 * (warp - 8);
                uint32_t xq[4][2][8];
#pragma unroll
                for (int r = 0; r < 8; r++) {
                    const uint4 qa = ldg128(q + (size_t)(16 * bid + rr + r) * D_ + 8 * lane);
                    const uint4 qb = ldg128(q + (size_t)(16 * bid + rr + r) * D_ + 8 * (lane + 32));
                    uint32_t* x = xq[r >> 1][r & 1];
                    x[0] = qa.x; x[1] = qa.y; x[2] = qa.z; x[3] = qa.w; x[4] = qb.x; x[5] = qb.y; x[6] = qb.z; x[7] = qb.w;
                }
#pragma unroll
                for (int r2 = 0; r2 < 4; r2++) {
                    float2 sa[2];
                    ln_stats2(xq[r2], sa);
                    if (lane == 0) {
                        *reinterpret_cast<float2*>(&g_st1[16 * bid + rr + 2 * r2]) = make_float2(sa[0].y, sa[1].y);
                        reinterpret_cast<uint32_t*>(&g_st1[S_])[(16 * bid + rr) / 2 + r2] = pack_bf16(sa[0].x, sa[1].x);
                    }
                }
            }
            if (lane == 0) { __threadfence(); atomicAdd(&g_cnt, 1u); }
            if (warp == 9) return;
            {
                unsigned int c; int spins = 0;
                do { asm volatile("ld.acquire.gpu.global.u32 %0, [%1];" : "=r"(c) : "l"(&g_cnt) : "memory"); } while (c < 2 * gridDim.x && ++spins < (1 << 22));
            }
            if (lane == 0) {
                asm volatile("fence.proxy.async;" ::: "memory");
                mbar_expect_tx(hbar + 8, 12288);
                asm volatile("cp.async.bulk.shared::cluster.global.mbarrier::complete_tx::bytes [%0], [%1], %2, [%3];"
                    :: "r"(smem_u32(&sm.st[0])), "l"(&g_st1[0]), "r"(12288), "r"(hbar + 8) : "memory");
            }
            mbar_wait(hbar + 8, 0);
            named_bar(7, 288);
        } else {
            if (lane == 0) asm volatile("cp.async.bulk.prefetch.L2.global [%0], %1;" :: "l"(wd + (size_t)bid * 7168), "r"(14336) : "memory");
            if (bid < 112) {
                if (lane == 0) {
                    mbar_expect_tx(hbar, 32768);
                    const CUtensorMap* mw = (bid < 56) ? &mapWg : &mapWu;
                    const int col = 32 * ((bid < 56) ? bid : bid - 56);
                    tma_load_2d(smem_u32(&sm.wS[0][0]), mw, hbar, col, 0);
                    tma_load_2d(smem_u32(&sm.wS[256][0]), mw, hbar, col, 256);
                }
                mbar_wait(hbar, 0);
                const int cq = lane & 3, rgp = lane >> 2;
                float cs[8];
#pragma unroll
                for (int i = 0; i < 8; i++) cs[i] = 0.f;
#pragma unroll 4
                for (int r = 0; r < 64; r++) {
                    const uint4 w = sm.wS[r * 8 + rgp][cq];
                    cs[0] += bf_lo(w.x); cs[1] += bf_hi(w.x); cs[2] += bf_lo(w.y); cs[3] += bf_hi(w.y);
                    cs[4] += bf_lo(w.z); cs[5] += bf_hi(w.z); cs[6] += bf_lo(w.w); cs[7] += bf_hi(w.w);
                }
#pragma unroll
                for (int i = 0; i < 8; i++) {
                    cs[i] += __shfl_xor_sync(0xffffffffu, cs[i], 4);
                    cs[i] += __shfl_xor_sync(0xffffffffu, cs[i], 8);
                    cs[i] += __shfl_xor_sync(0xffffffffu, cs[i], 16);
                }
                if (lane < 4) {
                    *reinterpret_cast<float4*>(&g_colsum[32 * bid + lane * 8]) = make_float4(cs[0], cs[1], cs[2], cs[3]);
                    *reinterpret_cast<float4*>(&g_colsum[32 * bid + lane * 8 + 4]) = make_float4(cs[4], cs[5], cs[6], cs[7]);
                }
            }
        }
    }
#undef TMT
}

constexpr int G1_THREADS = 384;
constexpr int G1_STAGES = 3;
constexpr int G1_A_BYTES = 8 * 16384;
constexpr int G1_B_STAGE = 32768;
constexpr int G1_OFF_B = G1_A_BYTES;
constexpr int G1_OFF_STATS = G1_OFF_B + G1_STAGES * G1_B_STAGE;
constexpr int G1_OFF_CS = G1_OFF_STATS + 1024;
constexpr int G1_OFF_BAR = G1_OFF_CS + 1792;
constexpr int G1_SMEM = G1_OFF_BAR + 128;

__device__ __forceinline__ float tanh_fast(float x) { float t; asm("tanh.approx.f32 %0, %1;" : "=f"(t) : "f"(x)); return t; }

template <int NT>
__device__ __forceinline__ void g1_math(const float (&acc)[NT * 8], const float* cs_g, const float* cs_u, float2 st0, float2 st1, uint32_t (&P)[NT * 2], int t) {
    const float r0 = st0.y, r1 = st1.y, m0 = -st0.x * st0.y, m1 = -st1.x * st1.y;
#pragma unroll
    for (int j = 0; j < NT; j++) {
        const float2 cg = *reinterpret_cast<const float2*>(cs_g + 8 * j + 2 * t);
        const float2 cu = *reinterpret_cast<const float2*>(cs_u + 8 * j + 2 * t);
        float r[4];
#pragma unroll
        for (int e = 0; e < 4; e++) {
            const float rr = (e < 2) ? r0 : r1, mm = (e < 2) ? m0 : m1;
            const float gv = fmaf(acc[4 * j + e], rr, mm * ((e & 1) ? cg.y : cg.x));
            const float uv = fmaf(acc[4 * (NT + j) + e], rr, mm * ((e & 1) ? cu.y : cu.x));
            r[e] = fmaf(tanh_fast(0.5f * gv), 0.5f, 0.5f) * uv;
        }
        P[2 * j] = pack_bf16(r[0], r[1]);
        P[2 * j + 1] = pack_bf16(r[2], r[3]);
    }
}
template <int NT>
__device__ __forceinline__ void g1_store(uint32_t (&P)[NT * 2], bf16* out0, int t) {
#pragma unroll
    for (int j0 = 0; j0 < NT; j0 += 4) {
        quad_transpose(P[2 * j0], P[2 * j0 + 2], P[2 * j0 + 4], P[2 * j0 + 6], t);
        quad_transpose(P[2 * j0 + 1], P[2 * j0 + 3], P[2 * j0 + 5], P[2 * j0 + 7], t);
        *reinterpret_cast<uint4*>(out0 + 8 * (j0 + t)) = make_uint4(P[2 * j0], P[2 * j0 + 2], P[2 * j0 + 4], P[2 * j0 + 6]);
        *reinterpret_cast<uint4*>(out0 + 8 * F_ + 8 * (j0 + t)) = make_uint4(P[2 * j0 + 1], P[2 * j0 + 3], P[2 * j0 + 5], P[2 * j0 + 7]);
    }
}

__global__ void __cluster_dims__(2, 1, 1) __launch_bounds__(G1_THREADS, 1)
gemm1_kernel(const __grid_constant__ CUtensorMap mapA, const __grid_constant__ CUtensorMap mapG4, const __grid_constant__ CUtensorMap mapU4,
             const __grid_constant__ CUtensorMap mapG3, const __grid_constant__ CUtensorMap mapU3) {
    extern __shared__ __align__(1024) uint8_t smem_raw[];
    const uint32_t sb = smem_u32(smem_raw);
    const int tid = threadIdx.x, lane = tid & 31, warp = tid >> 5, wgi = tid >> 7;
    const int rank = blockIdx.x & 1;
    const int cb = blockIdx.x & 7, rb = blockIdx.x >> 3;
#define TMT 128
    TM(2, 0);
    pdl_launch();
    if (tid == 32) { prefetch_map(&mapA); prefetch_map(&mapG3); prefetch_map(&mapU3); }
    const uint32_t barA = sb + G1_OFF_BAR;
    const uint32_t barF = barA + 64;
    const uint32_t barE = barF + 8 * G1_STAGES;
    const uint32_t barS = barE + 8 * G1_STAGES;
    if (tid == 0) {
        for (int i = 0; i < 8; i++) mbar_init(barA + 8 * i, 1);
        for (int i = 0; i < G1_STAGES; i++) { mbar_init(barF + 8 * i, 1); mbar_init(barE + 8 * i, 2); }
        mbar_init(barS, 1);
        for (int i = 0; i < 8; i++) mbar_expect_tx(barA + 8 * i, 16384);
        asm volatile("fence.mbarrier_init.release.cluster;" ::: "memory");
    }
    __syncthreads();
    cluster_arrive_relaxed();

    if (wgi == 0) {
        reg_dealloc<40>();
        if (warp == 0) {
            if (lane == 0) {
                int st = 0, ph = 1;
                for (int it = 0; it < 16; it++) {
                    const int kc = it & 7;
                    mbar_wait(barE + 8 * st, ph);
                    const uint32_t dst = sb + G1_OFF_B + st * G1_B_STAGE;
                    if (it < 8) {
                        mbar_expect_tx(barF + 8 * st, 32768);
                        tma_load_3d(dst, &mapG4, barF + 8 * st, 0, kc * 64, cb * 7);
                        tma_load_3d(dst + 16384, &mapU4, barF + 8 * st, 0, kc * 64, cb * 7);
                    } else {
                        mbar_expect_tx(barF + 8 * st, 24576);
                        tma_load_3d(dst, &mapG3, barF + 8 * st, 0, kc * 64, cb * 7 + 4);
                        tma_load_3d(dst + 12288, &mapU3, barF + 8 * st, 0, kc * 64, cb * 7 + 4);
                    }
                    if (++st == G1_STAGES) { st = 0; ph ^= 1; }
                }
            }
            __syncwarp();
            cluster_wait();
        } else if (warp == 1) {
            cluster_wait();
            pdl_wait();
            if (lane < 8) {
                const int c = 2 * (lane >> 1) + rank, mh = lane & 1;
                tma_load_2d_mc(sb + c * 16384 + mh * 8192, &mapA, barA + 8 * c, rb * 128 + mh * 64, c * 64, (uint16_t)3);
            }
            __syncwarp();
            float* cs = reinterpret_cast<float*>(smem_raw + G1_OFF_CS);
            for (int i = lane; i < 448; i += 32) cs[i] = __ldcg((i < 224) ? &g_colsum[cb * 224 + i] : &g_colsum[F_ + cb * 224 + (i - 224)]);
            __syncwarp();
            if (lane == 0) mbar_arrive(barS);
        } else {
            cluster_wait();
        }
    } else {
        reg_alloc<232>();
        cluster_wait();
        const int cw = wgi - 1;
        const int g = lane >> 2, t = lane & 3, wl = warp & 3, tl = tid & 127;
        bf16* outp = g_hh + (size_t)(rb * 128 + cw * 64 + wl * 16 + g) * F_ + cb * 224;
        const float* cs = reinterpret_cast<const float*>(smem_raw + G1_OFF_CS);
        int st = 0, ph = 0;
        float2 st0, st1;
        uint32_t P1[32];
        {
            float acc[128];
            const int kq = lane >> 3, mp = lane & 7;
            const uint8_t* sbase = smem_raw + cw * 8192 + kq * 128 + (mp & 3) * 4;
            const int mc = 2 * wl + (mp >> 2);
            float p0 = 0.f, p1 = 0.f, s0 = 0.f, s1 = 0.f, q0 = 0.f, q1 = 0.f;
#pragma unroll 1
            for (int kc = 0; kc < 8; kc++) {
                mbar_wait(barA + 8 * kc, 0);
                mbar_wait(barF + 8 * st, ph);
                if (tl == 0 && cw == 0) TR(1, kc);
                wgmma_fence();
                const uint32_t aaddr = sb + kc * 16384 + cw * 8192;
                const uint32_t baddr = sb + G1_OFF_B + st * G1_B_STAGE;
#pragma unroll
                for (int kk = 0; kk < 4; kk++)
                    wgmma_m64n256k16_ss(acc, make_desc(aaddr + kk * 2048, 8192, 1024, 1), make_desc(baddr + kk * 1024, 4096, 512, 2), (kc | kk) != 0);
                wgmma_commit();
                if (kc == 0) {
                    const uint32_t w = *reinterpret_cast<const uint32_t*>(smem_raw + cw * 8192 + (mc << 4) + (mp & 3) * 4);
                    p0 = bf_lo(w); p1 = bf_hi(w);
                }
#pragma unroll
                for (int i = 0; i < 16; i++) {
                    const int kr = 4 * i;
                    const uint32_t w = *reinterpret_cast<const uint32_t*>(sbase + kc * 16384 + kr * 128 + ((mc ^ ((kr + kq) & 7)) << 4));
                    const float d0 = bf_lo(w) - p0, d1 = bf_hi(w) - p1;
                    s0 += d0; s1 += d1; q0 = fmaf(d0, d0, q0); q1 = fmaf(d1, d1, q1);
                }
                wgmma_wait<0>();
                if (tl == 0) mbar_arrive(barE + 8 * st);
                if (++st == G1_STAGES) { st = 0; ph ^= 1; }
            }
            TM(2, 1);
            {
#pragma unroll
                for (int o = 8; o <= 16; o <<= 1) {
                    s0 += __shfl_xor_sync(0xffffffffu, s0, o); s1 += __shfl_xor_sync(0xffffffffu, s1, o);
                    q0 += __shfl_xor_sync(0xffffffffu, q0, o); q1 += __shfl_xor_sync(0xffffffffu, q1, o);
                }
                const float md0 = s0 * (1.0f / D_), md1 = s1 * (1.0f / D_);
                const float v0 = bf16r(fmaxf(fmaf(-md0, md0, q0 * (1.0f / D_)), 0.f)), v1 = bf16r(fmaxf(fmaf(-md1, md1, q1 * (1.0f / D_)), 0.f));
                const float ma = bf16r(p0 + md0), mb = bf16r(p1 + md1);
                const float ra = 1.0f / bf16r(sqrtf(bf16r(v0 + 1e-5f))), rbb = 1.0f / bf16r(sqrtf(bf16r(v1 + 1e-5f)));
                const float mA = __shfl_sync(0xffffffffu, ma, g >> 1), mB = __shfl_sync(0xffffffffu, mb, g >> 1);
                const float rA = __shfl_sync(0xffffffffu, ra, g >> 1), rB = __shfl_sync(0xffffffffu, rbb, g >> 1);
                const float mC = __shfl_sync(0xffffffffu, ma, 4 + (g >> 1)), mD = __shfl_sync(0xffffffffu, mb, 4 + (g >> 1));
                const float rC = __shfl_sync(0xffffffffu, ra, 4 + (g >> 1)), rD = __shfl_sync(0xffffffffu, rbb, 4 + (g >> 1));
                st0 = (g & 1) ? make_float2(mB, rB) : make_float2(mA, rA);
                st1 = (g & 1) ? make_float2(mD, rD) : make_float2(mC, rC);
            }
            mbar_wait(barS, 0);
            TM(2, 5);
            g1_math<16>(acc, cs, cs + 224, st0, st1, P1, t);
            TM(2, 2);
        }
        {
            float acc[96];
#pragma unroll 1
            for (int kc = 0; kc < 8; kc++) {
                mbar_wait(barF + 8 * st, ph);
                if (tl == 0 && cw == 0) TR(1, 8 + kc);
                wgmma_fence();
                const uint32_t aaddr = sb + kc * 16384 + cw * 8192;
                const uint32_t baddr = sb + G1_OFF_B + st * G1_B_STAGE;
#pragma unroll
                for (int kk = 0; kk < 4; kk++)
                    wgmma_m64n192k16_ss(acc, make_desc(aaddr + kk * 2048, 8192, 1024, 1), make_desc(baddr + kk * 1024, 4096, 512, 2), (kc | kk) != 0);
                wgmma_commit();
                if (kc == 0) g1_store<16>(P1, outp, t);
                wgmma_wait<0>();
                if (tl == 0) mbar_arrive(barE + 8 * st);
                if (++st == G1_STAGES) { st = 0; ph ^= 1; }
            }
            TM(2, 3);
            uint32_t P2[24];
            g1_math<12>(acc, cs + 128, cs + 224 + 128, st0, st1, P2, t);
            g1_store<12>(P2, outp + 128, t);
            TM(2, 4);
        }
    }
}

constexpr int G2_THREADS = 384;
constexpr int G2_STAGES = 6;
constexpr int G2_STAGE = 32768;
constexpr int G2_OFF_X = G2_STAGES * G2_STAGE;
constexpr int G2_OFF_BAR = G2_OFF_X + 32768;
constexpr int G2_SMEM = G2_OFF_BAR + 128;
constexpr int G2_KSTEPS = 14;

__device__ __forceinline__ void ldsm_x4_t(uint32_t& r0, uint32_t& r1, uint32_t& r2, uint32_t& r3, uint32_t addr) {
    asm volatile("ldmatrix.sync.aligned.m8n8.x4.trans.shared.b16 {%0,%1,%2,%3}, [%4];" : "=r"(r0), "=r"(r1), "=r"(r2), "=r"(r3) : "r"(addr) : "memory");
}

__global__ void __cluster_dims__(2, 1, 1) __launch_bounds__(G2_THREADS, 1)
gemm2_kernel(const __grid_constant__ CUtensorMap mapHH, const __grid_constant__ CUtensorMap mapWd, const __grid_constant__ CUtensorMap mapH,
             bf16* __restrict__ out) {
    extern __shared__ __align__(1024) uint8_t smem_raw[];
    const uint32_t sb = smem_u32(smem_raw);
    const int tid = threadIdx.x, lane = tid & 31, warp = tid >> 5, wgi = tid >> 7;
    const int ks = blockIdx.x & 1, nb = (blockIdx.x >> 1) & 3, rb = blockIdx.x >> 3;
    TM(3, 0);
    if (tid == 32) { prefetch_map(&mapHH); prefetch_map(&mapH); }
    const uint32_t barF = sb + G2_OFF_BAR;
    const uint32_t barE = barF + 8 * G2_STAGES;
    const uint32_t barX = barE + 8 * G2_STAGES;
    if (tid == 0) {
        for (int i = 0; i < G2_STAGES; i++) { mbar_init(barF + 8 * i, 1); mbar_init(barE + 8 * i, 2); }
        mbar_init(barX, 1);
        asm volatile("fence.mbarrier_init.release.cluster;" ::: "memory");
        mbar_expect_tx(barX, 32768);
        for (int it = 0; it < G2_STAGES; it++) {
            mbar_expect_tx(barF + 8 * it, 32768);
            tma_load_3d(sb + it * G2_STAGE + 16384, &mapWd, barF + 8 * it, 0, ks * 896 + it * 64, nb * 2);
        }
    }
    __syncthreads();
    cluster_arrive_relaxed();

    if (wgi == 0) {
        if (tid == 0) {
            pdl_wait();
            for (int it = 0; it < G2_STAGES; it++)
                tma_load_2d(sb + it * G2_STAGE, &mapHH, barF + 8 * it, ks * 896 + it * 64, rb * 128);
            if (blockIdx.x == 0) g_cnt = 0u;
            int st = 0, ph = 0;
            for (int it = G2_STAGES; it < G2_KSTEPS; it++) {
                mbar_wait(barE + 8 * st, ph);
                const uint32_t dst = sb + st * G2_STAGE;
                const int k0 = ks * 896 + it * 64;
                mbar_expect_tx(barF + 8 * st, 32768);
                tma_load_2d(dst, &mapHH, barF + 8 * st, k0, rb * 128);
                tma_load_3d(dst + 16384, &mapWd, barF + 8 * st, 0, k0, nb * 2);
                if (++st == G2_STAGES) { st = 0; ph ^= 1; }
            }
            mbar_wait(barE + 8 * st, ph);
            mbar_expect_tx(barF + 8 * st, 16384);
            tma_load_2d(sb + st * G2_STAGE, &mapH, barF + 8 * st, rb * 128 + ks * 64, nb * 128);
        }
        __syncwarp();
        cluster_wait();
    } else {
        const int cw = wgi - 1;
        const int g = lane >> 2, t = lane & 3, wl = warp & 3;
        const int tl = tid & 127;
        int st = 0, ph = 0;
        float acc[64];
#pragma unroll 1
        for (int it = 0; it < G2_KSTEPS; it++) {
            mbar_wait(barF + 8 * st, ph);
            if (it == 0) TM(3, 1);
            wgmma_fence();
            const uint32_t aaddr = sb + st * G2_STAGE + cw * 8192;
            const uint32_t baddr = sb + st * G2_STAGE + 16384;
#pragma unroll
            for (int kk = 0; kk < 4; kk++)
                wgmma_m64n128k16_ss(acc, make_desc(aaddr + kk * 32, 16, 1024, 1), make_desc(baddr + kk * 2048, 8192, 1024, 1), (it | kk) != 0);
            wgmma_commit();
            wgmma_wait<0>();
            if (tl == 0) mbar_arrive(barE + 8 * st);
            if (++st == G2_STAGES) { st = 0; ph ^= 1; }
        }
        TM(3, 2);
        cluster_wait();
        if (cw != ks) {
            const uint32_t dst = mapa(sb + G2_OFF_X + tl * 16, (uint32_t)(ks ^ 1));
            const uint32_t rbar = mapa(barX, (uint32_t)(ks ^ 1));
#pragma unroll
            for (int i = 0; i < 16; i++) st_async_v4f(dst + i * 2048, acc[4 * i], acc[4 * i + 1], acc[4 * i + 2], acc[4 * i + 3], rbar);
        } else {
            const float4* xb = reinterpret_cast<const float4*>(smem_raw + G2_OFF_X) + tl;
            const int row0 = rb * 128 + cw * 64 + wl * 16 + g;
            bf16* o0 = out + (size_t)row0 * D_ + nb * 128;
            uint32_t ha[16], hb[16];
            mbar_wait(barF + 8 * st, ph);
            {
                const int chl = 8 * (lane >> 4) + (lane & 7), sb8 = 2 * wl + ((lane >> 3) & 1);
                const uint32_t hbase = sb + st * G2_STAGE + chl * 128 + ((sb8 ^ (lane & 7)) << 4);
#pragma unroll
                for (int j = 0; j < 16; j += 2) ldsm_x4_t(ha[j], hb[j], ha[j + 1], hb[j + 1], hbase + j * 1024);
            }
            mbar_wait_cluster(barX, 0);
            TM(3, 4);
#pragma unroll
            for (int j0 = 0; j0 < 16; j0 += 4) {
                uint32_t P0[4], P1[4];
#pragma unroll
                for (int jj = 0; jj < 4; jj++) {
                    const int j = j0 + jj;
                    const float4 x = xb[j * 128];
                    P0[jj] = hadd2(ha[j], pack_bf16(acc[4 * j] + x.x, acc[4 * j + 1] + x.y));
                    P1[jj] = hadd2(hb[j], pack_bf16(acc[4 * j + 2] + x.z, acc[4 * j + 3] + x.w));
                }
                quad_transpose(P0[0], P0[1], P0[2], P0[3], t);
                quad_transpose(P1[0], P1[1], P1[2], P1[3], t);
                *reinterpret_cast<uint4*>(o0 + 8 * (j0 + t)) = make_uint4(P0[0], P0[1], P0[2], P0[3]);
                *reinterpret_cast<uint4*>(o0 + 8 * D_ + 8 * (j0 + t)) = make_uint4(P1[0], P1[1], P1[2], P1[3]);
            }
        }
        TM(3, 5);
    }
#undef TMT
}

typedef CUresult (*EncodeFn)(CUtensorMap*, CUtensorMapDataType, cuuint32_t, void*, const cuuint64_t*, const cuuint64_t*,
                             const cuuint32_t*, const cuuint32_t*, CUtensorMapInterleave, CUtensorMapSwizzle,
                             CUtensorMapL2promotion, CUtensorMapFloatOOBfill);

static void enc2d(EncodeFn enc, CUtensorMap* m, const void* p, int rows, int cols, int brows, int bcols) {
    cuuint64_t dims[2] = {(cuuint64_t)cols, (cuuint64_t)rows};
    cuuint64_t strides[1] = {(cuuint64_t)cols * 2};
    cuuint32_t box[2] = {(cuuint32_t)bcols, (cuuint32_t)brows};
    cuuint32_t es[2] = {1, 1};
    enc(m, CU_TENSOR_MAP_DATA_TYPE_BFLOAT16, 2, const_cast<void*>(p), dims, strides, box, es, CU_TENSOR_MAP_INTERLEAVE_NONE,
        bcols == 32 ? CU_TENSOR_MAP_SWIZZLE_64B : CU_TENSOR_MAP_SWIZZLE_128B, CU_TENSOR_MAP_L2_PROMOTION_L2_128B, CU_TENSOR_MAP_FLOAT_OOB_FILL_NONE);
}
static void enc2d_plain(EncodeFn enc, CUtensorMap* m, const void* p, int rows, int cols, int brows, int bcols) {
    cuuint64_t dims[2] = {(cuuint64_t)cols, (cuuint64_t)rows};
    cuuint64_t strides[1] = {(cuuint64_t)cols * 2};
    cuuint32_t box[2] = {(cuuint32_t)bcols, (cuuint32_t)brows};
    cuuint32_t es[2] = {1, 1};
    enc(m, CU_TENSOR_MAP_DATA_TYPE_BFLOAT16, 2, const_cast<void*>(p), dims, strides, box, es, CU_TENSOR_MAP_INTERLEAVE_NONE,
        CU_TENSOR_MAP_SWIZZLE_NONE, CU_TENSOR_MAP_L2_PROMOTION_L2_128B, CU_TENSOR_MAP_FLOAT_OOB_FILL_NONE);
}
static void enc3d(EncodeFn enc, CUtensorMap* m, const void* p, int rows, int cols, int atom, int brows, int natoms) {
    cuuint64_t dims[3] = {(cuuint64_t)atom, (cuuint64_t)rows, (cuuint64_t)(cols / atom)};
    cuuint64_t strides[2] = {(cuuint64_t)cols * 2, (cuuint64_t)atom * 2};
    cuuint32_t box[3] = {(cuuint32_t)atom, (cuuint32_t)brows, (cuuint32_t)natoms};
    cuuint32_t es[3] = {1, 1, 1};
    enc(m, CU_TENSOR_MAP_DATA_TYPE_BFLOAT16, 3, const_cast<void*>(p), dims, strides, box, es, CU_TENSOR_MAP_INTERLEAVE_NONE,
        atom == 32 ? CU_TENSOR_MAP_SWIZZLE_64B : CU_TENSOR_MAP_SWIZZLE_128B, CU_TENSOR_MAP_L2_PROMOTION_L2_128B, CU_TENSOR_MAP_FLOAT_OOB_FILL_NONE);
}

extern "C" void kernel_launch(void* const* d_in, const int* in_sizes, int n_in, void* d_out, int out_size) {
    const bf16* q = (const bf16*)d_in[0];
    const bf16* k = (const bf16*)d_in[1];
    const bf16* v = (const bf16*)d_in[2];
    const bf16* shift_k = (const bf16*)d_in[3];
    const bf16* ssm_k = (const bf16*)d_in[4];
    const bf16* ssm_D = (const bf16*)d_in[5];
    const bf16* wg = (const bf16*)d_in[7];
    const bf16* wu = (const bf16*)d_in[8];
    const bf16* wd = (const bf16*)d_in[9];
    bf16* out = (bf16*)d_out;

    static EncodeFn enc = nullptr;
    static void *p_hT = nullptr, *p_hh = nullptr;
    if (!enc) {
        void* fn = nullptr; cudaDriverEntryPointQueryResult qr;
        cudaGetDriverEntryPoint("cuTensorMapEncodeTiled", &fn, cudaEnableDefault, &qr);
        enc = (EncodeFn)fn;
        cudaGetSymbolAddress(&p_hT, g_hT);
        cudaGetSymbolAddress(&p_hh, g_hh);
        cudaFuncSetAttribute(conv_kernel, cudaFuncAttributeMaxDynamicSharedMemorySize, (int)sizeof(K1Smem));
        cudaFuncSetAttribute(gemm1_kernel, cudaFuncAttributeMaxDynamicSharedMemorySize, G1_SMEM);
        cudaFuncSetAttribute(gemm2_kernel, cudaFuncAttributeMaxDynamicSharedMemorySize, G2_SMEM);
    }
    CUtensorMap mA, mG64, mU64, mG32, mU32, mHH, mWd, mH, mWgp, mWup;
    enc2d_plain(enc, &mWgp, wg, D_, F_, 256, 32);
    enc2d_plain(enc, &mWup, wu, D_, F_, 256, 32);
    enc2d(enc, &mA, p_hT, D_, S_, 64, 64);
    enc2d(enc, &mH, p_hT, D_, S_, 128, 64);
    enc3d(enc, &mG64, wg, D_, F_, 32, 64, 4);
    enc3d(enc, &mU64, wu, D_, F_, 32, 64, 4);
    enc3d(enc, &mG32, wg, D_, F_, 32, 64, 3);
    enc3d(enc, &mU32, wu, D_, F_, 32, 64, 3);
    enc2d(enc, &mHH, p_hh, S_, F_, 128, 64);
    enc3d(enc, &mWd, wd, F_, D_, 64, 64, 2);

    cudaStream_t st = cudaStreamPerThread;
    cudaLaunchAttribute at[1];
    at[0].id = cudaLaunchAttributeProgrammaticStreamSerialization;
    at[0].val.programmaticStreamSerializationAllowed = 1;
    cudaLaunchConfig_t cfg = {};
    cfg.stream = st; cfg.attrs = at; cfg.numAttrs = 1;
    conv_kernel<<<128, K1_THREADS, sizeof(K1Smem), st>>>(q, k, v, shift_k, ssm_k, ssm_D, mWgp, mWup, wd);
    cfg.gridDim = dim3(128); cfg.blockDim = dim3(G1_THREADS); cfg.dynamicSmemBytes = G1_SMEM;
    cudaLaunchKernelEx(&cfg, gemm1_kernel, mA, mG64, mU64, mG32, mU32);
    cfg.gridDim = dim3(128); cfg.blockDim = dim3(G2_THREADS); cfg.dynamicSmemBytes = G2_SMEM;
    cudaLaunchKernelEx(&cfg, gemm2_kernel, mHH, mWd, mH, out);
}
```

```cpp
#include <cuda_runtime.h>
#include <cuda_bf16.h>
#include <cuda.h>
#include <stdint.h>

typedef __nv_bfloat16 bf16;
constexpr int S_ = 2048, D_ = 512, F_ = 1792;

constexpr int HT_PITCH = S_ + 64;
__device__ __align__(128) bf16 g_hT[D_ * HT_PITCH];
__device__ bf16 g_hh[S_ * F_];
__device__ __align__(128) float g_st1[S_ + S_ / 2];
__device__ float g_colsum[2 * F_];
__device__ unsigned int g_cnt;

#define TM(k, i)
#define TR(k, i)
__device__ __forceinline__ uint32_t smem_u32(const void* p) { return (uint32_t)__cvta_generic_to_shared(p); }
__device__ __forceinline__ float bf16r(float x) { return __bfloat162float(__float2bfloat16_rn(x)); }
__device__ __forceinline__ float bf_lo(uint32_t w) { return __uint_as_float(w << 16); }
__device__ __forceinline__ float bf_hi(uint32_t w) { return __uint_as_float(w & 0xffff0000u); }
__device__ __forceinline__ uint32_t pack_bf16(float lo, float hi) {
    __nv_bfloat162 v = __floats2bfloat162_rn(lo, hi);
    return *reinterpret_cast<uint32_t*>(&v);
}
__device__ __forceinline__ uint32_t hmul2(uint32_t a, uint32_t b) {
    __nv_bfloat162 r = __hmul2_rn(*reinterpret_cast<__nv_bfloat162*>(&a), *reinterpret_cast<__nv_bfloat162*>(&b));
    return *reinterpret_cast<uint32_t*>(&r);
}
__device__ __forceinline__ uint32_t hadd2(uint32_t a, uint32_t b) {
    __nv_bfloat162 r = __hadd2_rn(*reinterpret_cast<__nv_bfloat162*>(&a), *reinterpret_cast<__nv_bfloat162*>(&b));
    return *reinterpret_cast<uint32_t*>(&r);
}
__device__ __forceinline__ uint4 ldg128(const void* p) {
    uint4 r; asm volatile("ld.global.nc.v4.u32 {%0,%1,%2,%3}, [%4];" : "=r"(r.x), "=r"(r.y), "=r"(r.z), "=r"(r.w) : "l"(p)); return r;
}
__device__ __forceinline__ uint4 ldcg128(const void* p) {
    uint4 r; asm volatile("ld.global.cg.v4.u32 {%0,%1,%2,%3}, [%4];" : "=r"(r.x), "=r"(r.y), "=r"(r.z), "=r"(r.w) : "l"(p)); return r;
}
__device__ __forceinline__ uint32_t ldg16(const void* p) {
    unsigned short r; asm volatile("ld.global.nc.u16 %0, [%1];" : "=h"(r) : "l"(p)); return (uint32_t)r;
}
__device__ __forceinline__ void mbar_init(uint32_t bar, int cnt) { asm volatile("mbarrier.init.shared::cta.b64 [%0], %1;" :: "r"(bar), "r"(cnt)); }
__device__ __forceinline__ void mbar_expect_tx(uint32_t bar, uint32_t bytes) { asm volatile("mbarrier.arrive.expect_tx.shared::cta.b64 _, [%0], %1;" :: "r"(bar), "r"(bytes) : "memory"); }
__device__ __forceinline__ void mbar_arrive(uint32_t bar) { asm volatile("mbarrier.arrive.shared::cta.b64 _, [%0];" :: "r"(bar) : "memory"); }
__device__ __forceinline__ void mbar_arrive_cluster(uint32_t bar, uint32_t cta) {
    asm volatile("{\n.reg .b32 ra;\nmapa.shared::cluster.u32 ra, %0, %1;\nmbarrier.arrive.shared::cluster.b64 _, [ra];\n}" :: "r"(bar), "r"(cta) : "memory");
}
__device__ __forceinline__ void mbar_wait(uint32_t bar, uint32_t parity) {
    asm volatile("{\n.reg .pred P1;\nLAB_WAIT:\nmbarrier.try_wait.parity.shared::cta.b64 P1, [%0], %1;\n@P1 bra DONE;\nbra LAB_WAIT;\nDONE:\n}" :: "r"(bar), "r"(parity) : "memory");
}
__device__ __forceinline__ void mbar_wait_cluster(uint32_t bar, uint32_t parity) {
    asm volatile("{\n.reg .pred P1;\nLAB_WAIT:\nmbarrier.try_wait.parity.acquire.cluster.shared::cta.b64 P1, [%0], %1;\n@P1 bra DONE;\nbra LAB_WAIT;\nDONE:\n}" :: "r"(bar), "r"(parity) : "memory");
}
__device__ __forceinline__ void tma_load_2d(uint32_t dst, const CUtensorMap* map, uint32_t bar, int c0, int c1) {
    asm volatile("cp.async.bulk.tensor.2d.shared::cluster.global.mbarrier::complete_tx::bytes [%0], [%1, {%3, %4}], [%2];"
        :: "r"(dst), "l"(map), "r"(bar), "r"(c0), "r"(c1) : "memory");
}
__device__ __forceinline__ void tma_load_2d_mc(uint32_t dst, const CUtensorMap* map, uint32_t bar, int c0, int c1, uint16_t mask) {
    asm volatile("cp.async.bulk.tensor.2d.shared::cluster.global.mbarrier::complete_tx::bytes.multicast::cluster [%0], [%1, {%3, %4}], [%2], %5;"
        :: "r"(dst), "l"(map), "r"(bar), "r"(c0), "r"(c1), "h"(mask) : "memory");
}
__device__ __forceinline__ void tma_load_3d_mc(uint32_t dst, const CUtensorMap* map, uint32_t bar, int c0, int c1, int c2, uint16_t mask) {
    asm volatile("cp.async.bulk.tensor.3d.shared::cluster.global.mbarrier::complete_tx::bytes.multicast::cluster [%0], [%1, {%3, %4, %5}], [%2], %6;"
        :: "r"(dst), "l"(map), "r"(bar), "r"(c0), "r"(c1), "r"(c2), "h"(mask) : "memory");
}
__device__ __forceinline__ void tma_load_3d(uint32_t dst, const CUtensorMap* map, uint32_t bar, int c0, int c1, int c2) {
    asm volatile("cp.async.bulk.tensor.3d.shared::cluster.global.mbarrier::complete_tx::bytes [%0], [%1, {%3, %4, %5}], [%2];"
        :: "r"(dst), "l"(map), "r"(bar), "r"(c0), "r"(c1), "r"(c2) : "memory");
}
__device__ __forceinline__ void cluster_arrive() { asm volatile("barrier.cluster.arrive.aligned;" ::: "memory"); }
__device__ __forceinline__ void cluster_arrive_relaxed() { asm volatile("barrier.cluster.arrive.relaxed.aligned;" ::: "memory"); }
__device__ __forceinline__ void cluster_wait() { asm volatile("barrier.cluster.wait.aligned;" ::: "memory"); }
__device__ __forceinline__ uint32_t mapa(uint32_t addr, uint32_t cta) {
    uint32_t r; asm volatile("mapa.shared::cluster.u32 %0, %1, %2;" : "=r"(r) : "r"(addr), "r"(cta)); return r;
}
__device__ __forceinline__ void st_async_v2(uint32_t addr, uint32_t a, uint32_t b, uint32_t rbar) {
    asm volatile("st.async.weak.shared::cluster.mbarrier::complete_tx::bytes.v2.b32 [%0], {%1, %2}, [%3];" :: "r"(addr), "r"(a), "r"(b), "r"(rbar) : "memory");
}
__device__ __forceinline__ void st_async_v4f(uint32_t addr, float a, float b, float c, float d, uint32_t rbar) {
    asm volatile("st.async.weak.shared::cluster.mbarrier::complete_tx::bytes.v4.f32 [%0], {%1, %2, %3, %4}, [%5];" :: "r"(addr), "f"(a), "f"(b), "f"(c), "f"(d), "r"(rbar) : "memory");
}
__device__ __forceinline__ void wgmma_fence() { asm volatile("wgmma.fence.sync.aligned;" ::: "memory"); }
__device__ __forceinline__ void wgmma_commit() { asm volatile("wgmma.commit_group.sync.aligned;" ::: "memory"); }
template <int N> __device__ __forceinline__ void wgmma_wait() { asm volatile("wgmma.wait_group.sync.aligned %0;" :: "n"(N) : "memory"); }
__device__ __forceinline__ uint64_t make_desc(uint32_t addr, uint32_t lbo_bytes, uint32_t sbo_bytes, uint32_t layout) {
    return (uint64_t)((addr & 0x3FFFF) >> 4) | ((uint64_t)(lbo_bytes >> 4) << 16) | ((uint64_t)(sbo_bytes >> 4) << 32) | ((uint64_t)layout << 62);
}
template <int R> __device__ __forceinline__ void reg_alloc() { asm volatile("setmaxnreg.inc.sync.aligned.u32 %0;" :: "n"(R)); }
template <int R> __device__ __forceinline__ void reg_dealloc() { asm volatile("setmaxnreg.dec.sync.aligned.u32 %0;" :: "n"(R)); }
__device__ __forceinline__ void pdl_launch() { asm volatile("griddepcontrol.launch_dependents;" ::: "memory"); }
__device__ __forceinline__ void pdl_wait() { asm volatile("griddepcontrol.wait;" ::: "memory"); }
__device__ __forceinline__ void prefetch_map(const CUtensorMap* m) { asm volatile("prefetch.tensormap [%0];" :: "l"(m) : "memory"); }
__device__ __forceinline__ void named_bar(int id, int n) { asm volatile("bar.sync %0, %1;" :: "r"(id), "r"(n) : "memory"); }

__device__ __forceinline__ void wgmma_m64n256k16_ss(float (&d)[128], uint64_t descA, uint64_t descB, int scaleD) {
    asm volatile("{\n.reg .pred p;\nsetp.ne.b32 p, %130, 0;\n"
        "wgmma.mma_async.sync.aligned.m64n256k16.f32.bf16.bf16 {%0, %1, %2, %3, %4, %5, %6, %7, %8, %9, %10, %11, %12, %13, %14, %15, %16, %17, %18, %19, %20, %21, %22, %23, %24, %25, %26, %27, %28, %29, %30, %31, %32, %33, %34, %35, %36, %37, %38, %39, %40, %41, %42, %43, %44, %45, %46, %47, %48, %49, %50, %51, %52, %53, %54, %55, %56, %57, %58, %59, %60, %61, %62, %63, %64, %65, %66, %67, %68, %69, %70, %71, %72, %73, %74, %75, %76, %77, %78, %79, %80, %81, %82, %83, %84, %85, %86, %87, %88, %89, %90, %91, %92, %93, %94, %95, %96, %97, %98, %99, %100, %101, %102, %103, %104, %105, %106, %107, %108, %109, %110, %111, %112, %113, %114, %115, %116, %117, %118, %119, %120, %121, %122, %123, %124, %125, %126, %127}, %128, %129, p, 1, 1, 1, 1;\n}\n"
        : "+f"(d[0]), "+f"(d[1]), "+f"(d[2]), "+f"(d[3]), "+f"(d[4]), "+f"(d[5]), "+f"(d[6]), "+f"(d[7]), "+f"(d[8]), "+f"(d[9]), "+f"(d[10]), "+f"(d[11]), "+f"(d[12]), "+f"(d[13]), "+f"(d[14]), "+f"(d[15]), "+f"(d[16]), "+f"(d[17]), "+f"(d[18]), "+f"(d[19]), "+f"(d[20]), "+f"(d[21]), "+f"(d[22]), "+f"(d[23]), "+f"(d[24]), "+f"(d[25]), "+f"(d[26]), "+f"(d[27]), "+f"(d[28]), "+f"(d[29]), "+f"(d[30]), "+f"(d[31]), "+f"(d[32]), "+f"(d[33]), "+f"(d[34]), "+f"(d[35]), "+f"(d[36]), "+f"(d[37]), "+f"(d[38]), "+f"(d[39]), "+f"(d[40]), "+f"(d[41]), "+f"(d[42]), "+f"(d[43]), "+f"(d[44]), "+f"(d[45]), "+f"(d[46]), "+f"(d[47]), "+f"(d[48]), "+f"(d[49]), "+f"(d[50]), "+f"(d[51]), "+f"(d[52]), "+f"(d[53]), "+f"(d[54]), "+f"(d[55]), "+f"(d[56]), "+f"(d[57]), "+f"(d[58]), "+f"(d[59]), "+f"(d[60]), "+f"(d[61]), "+f"(d[62]), "+f"(d[63]), "+f"(d[64]), "+f"(d[65]), "+f"(d[66]), "+f"(d[67]), "+f"(d[68]), "+f"(d[69]), "+f"(d[70]), "+f"(d[71]), "+f"(d[72]), "+f"(d[73]), "+f"(d[74]), "+f"(d[75]), "+f"(d[76]), "+f"(d[77]), "+f"(d[78]), "+f"(d[79]), "+f"(d[80]), "+f"(d[81]), "+f"(d[82]), "+f"(d[83]), "+f"(d[84]), "+f"(d[85]), "+f"(d[86]), "+f"(d[87]), "+f"(d[88]), "+f"(d[89]), "+f"(d[90]), "+f"(d[91]), "+f"(d[92]), "+f"(d[93]), "+f"(d[94]), "+f"(d[95]), "+f"(d[96]), "+f"(d[97]), "+f"(d[98]), "+f"(d[99]), "+f"(d[100]), "+f"(d[101]), "+f"(d[102]), "+f"(d[103]), "+f"(d[104]), "+f"(d[105]), "+f"(d[106]), "+f"(d[107]), "+f"(d[108]), "+f"(d[109]), "+f"(d[110]), "+f"(d[111]), "+f"(d[112]), "+f"(d[113]), "+f"(d[114]), "+f"(d[115]), "+f"(d[116]), "+f"(d[117]), "+f"(d[118]), "+f"(d[119]), "+f"(d[120]), "+f"(d[121]), "+f"(d[122]), "+f"(d[123]), "+f"(d[124]), "+f"(d[125]), "+f"(d[126]), "+f"(d[127])
        : "l"(descA), "l"(descB), "r"(scaleD));
}

__device__ __forceinline__ void wgmma_m64n192k16_ss(float (&d)[96], uint64_t descA, uint64_t descB, int scaleD) {
    asm volatile("{\n.reg .pred p;\nsetp.ne.b32 p, %98, 0;\n"
        "wgmma.mma_async.sync.aligned.m64n192k16.f32.bf16.bf16 {%0, %1, %2, %3, %4, %5, %6, %7, %8, %9, %10, %11, %12, %13, %14, %15, %16, %17, %18, %19, %20, %21, %22, %23, %24, %25, %26, %27, %28, %29, %30, %31, %32, %33, %34, %35, %36, %37, %38, %39, %40, %41, %42, %43, %44, %45, %46, %47, %48, %49, %50, %51, %52, %53, %54, %55, %56, %57, %58, %59, %60, %61, %62, %63, %64, %65, %66, %67, %68, %69, %70, %71, %72, %73, %74, %75, %76, %77, %78, %79, %80, %81, %82, %83, %84, %85, %86, %87, %88, %89, %90, %91, %92, %93, %94, %95}, %96, %97, p, 1, 1, 1, 1;\n}\n"
        : "+f"(d[0]), "+f"(d[1]), "+f"(d[2]), "+f"(d[3]), "+f"(d[4]), "+f"(d[5]), "+f"(d[6]), "+f"(d[7]), "+f"(d[8]), "+f"(d[9]), "+f"(d[10]), "+f"(d[11]), "+f"(d[12]), "+f"(d[13]), "+f"(d[14]), "+f"(d[15]), "+f"(d[16]), "+f"(d[17]), "+f"(d[18]), "+f"(d[19]), "+f"(d[20]), "+f"(d[21]), "+f"(d[22]), "+f"(d[23]), "+f"(d[24]), "+f"(d[25]), "+f"(d[26]), "+f"(d[27]), "+f"(d[28]), "+f"(d[29]), "+f"(d[30]), "+f"(d[31]), "+f"(d[32]), "+f"(d[33]), "+f"(d[34]), "+f"(d[35]), "+f"(d[36]), "+f"(d[37]), "+f"(d[38]), "+f"(d[39]), "+f"(d[40]), "+f"(d[41]), "+f"(d[42]), "+f"(d[43]), "+f"(d[44]), "+f"(d[45]), "+f"(d[46]), "+f"(d[47]), "+f"(d[48]), "+f"(d[49]), "+f"(d[50]), "+f"(d[51]), "+f"(d[52]), "+f"(d[53]), "+f"(d[54]), "+f"(d[55]), "+f"(d[56]), "+f"(d[57]), "+f"(d[58]), "+f"(d[59]), "+f"(d[60]), "+f"(d[61]), "+f"(d[62]), "+f"(d[63]), "+f"(d[64]), "+f"(d[65]), "+f"(d[66]), "+f"(d[67]), "+f"(d[68]), "+f"(d[69]), "+f"(d[70]), "+f"(d[71]), "+f"(d[72]), "+f"(d[73]), "+f"(d[74]), "+f"(d[75]), "+f"(d[76]), "+f"(d[77]), "+f"(d[78]), "+f"(d[79]), "+f"(d[80]), "+f"(d[81]), "+f"(d[82]), "+f"(d[83]), "+f"(d[84]), "+f"(d[85]), "+f"(d[86]), "+f"(d[87]), "+f"(d[88]), "+f"(d[89]), "+f"(d[90]), "+f"(d[91]), "+f"(d[92]), "+f"(d[93]), "+f"(d[94]), "+f"(d[95])
        : "l"(descA), "l"(descB), "r"(scaleD));
}

__device__ __forceinline__ void wgmma_m64n128k16_ss(float (&d)[64], uint64_t descA, uint64_t descB, int scaleD) {
    asm volatile("{\n.reg .pred p;\nsetp.ne.b32 p, %66, 0;\n"
        "wgmma.mma_async.sync.aligned.m64n128k16.f32.bf16.bf16 {%0, %1, %2, %3, %4, %5, %6, %7, %8, %9, %10, %11, %12, %13, %14, %15, %16, %17, %18, %19, %20, %21, %22, %23, %24, %25, %26, %27, %28, %29, %30, %31, %32, %33, %34, %35, %36, %37, %38, %39, %40, %41, %42, %43, %44, %45, %46, %47, %48, %49, %50, %51, %52, %53, %54, %55, %56, %57, %58, %59, %60, %61, %62, %63}, %64, %65, p, 1, 1, 0, 1;\n}\n"
        : "+f"(d[0]), "+f"(d[1]), "+f"(d[2]), "+f"(d[3]), "+f"(d[4]), "+f"(d[5]), "+f"(d[6]), "+f"(d[7]), "+f"(d[8]), "+f"(d[9]), "+f"(d[10]), "+f"(d[11]), "+f"(d[12]), "+f"(d[13]), "+f"(d[14]), "+f"(d[15]), "+f"(d[16]), "+f"(d[17]), "+f"(d[18]), "+f"(d[19]), "+f"(d[20]), "+f"(d[21]), "+f"(d[22]), "+f"(d[23]), "+f"(d[24]), "+f"(d[25]), "+f"(d[26]), "+f"(d[27]), "+f"(d[28]), "+f"(d[29]), "+f"(d[30]), "+f"(d[31]), "+f"(d[32]), "+f"(d[33]), "+f"(d[34]), "+f"(d[35]), "+f"(d[36]), "+f"(d[37]), "+f"(d[38]), "+f"(d[39]), "+f"(d[40]), "+f"(d[41]), "+f"(d[42]), "+f"(d[43]), "+f"(d[44]), "+f"(d[45]), "+f"(d[46]), "+f"(d[47]), "+f"(d[48]), "+f"(d[49]), "+f"(d[50]), "+f"(d[51]), "+f"(d[52]), "+f"(d[53]), "+f"(d[54]), "+f"(d[55]), "+f"(d[56]), "+f"(d[57]), "+f"(d[58]), "+f"(d[59]), "+f"(d[60]), "+f"(d[61]), "+f"(d[62]), "+f"(d[63])
        : "l"(descA), "l"(descB), "r"(scaleD));
}

__device__ __forceinline__ void quad_transpose(uint32_t& r0, uint32_t& r1, uint32_t& r2, uint32_t& r3, int t) {
    const bool o1 = t & 1, o2 = t & 2;
    uint32_t x, y;
    x = o1 ? r0 : r1; y = __shfl_xor_sync(0xffffffffu, x, 1); if (o1) r0 = y; else r1 = y;
    x = o1 ? r2 : r3; y = __shfl_xor_sync(0xffffffffu, x, 1); if (o1) r2 = y; else r3 = y;
    x = o2 ? r0 : r2; y = __shfl_xor_sync(0xffffffffu, x, 2); if (o2) r0 = y; else r2 = y;
    x = o2 ? r1 : r3; y = __shfl_xor_sync(0xffffffffu, x, 2); if (o2) r1 = y; else r3 = y;
}

__device__ __forceinline__ float warp_sum(float s) {
#pragma unroll
    for (int o = 16; o > 0; o >>= 1) s += __shfl_xor_sync(0xffffffffu, s, o);
    return s;
}
__device__ __forceinline__ uint32_t hsub2(uint32_t a, uint32_t b) {
    __nv_bfloat162 r = __hsub2_rn(*reinterpret_cast<__nv_bfloat162*>(&a), *reinterpret_cast<__nv_bfloat162*>(&b));
    return *reinterpret_cast<uint32_t*>(&r);
}
__device__ __forceinline__ void ln_stats2(const uint32_t (&x)[2][8], float2 (&st)[2]) {
    float piv[2], s[2], ss[2];
#pragma unroll
    for (int r = 0; r < 2; r++) piv[r] = __shfl_sync(0xffffffffu, bf_lo(x[r][0]), 0);
#pragma unroll
    for (int r = 0; r < 2; r++) {
        float s0 = 0.f, s1 = 0.f, q0 = 0.f, q1 = 0.f;
#pragma unroll
        for (int i = 0; i < 8; i++) {
            const float d0 = bf_lo(x[r][i]) - piv[r], d1 = bf_hi(x[r][i]) - piv[r];
            s0 += d0; s1 += d1; q0 = fmaf(d0, d0, q0); q1 = fmaf(d1, d1, q1);
        }
        s[r] = s0 + s1; ss[r] = q0 + q1;
    }
#pragma unroll
    for (int o = 16; o > 0; o >>= 1) {
#pragma unroll
        for (int r = 0; r < 2; r++) { s[r] += __shfl_xor_sync(0xffffffffu, s[r], o); ss[r] += __shfl_xor_sync(0xffffffffu, ss[r], o); }
    }
#pragma unroll
    for (int r = 0; r < 2; r++) {
        const float md = s[r] * (1.0f / D_);
        const float var = bf16r(fmaxf(fmaf(-md, md, ss[r] * (1.0f / D_)), 0.f));
        st[r] = make_float2(bf16r(piv[r] + md), 1.0f / bf16r(sqrtf(bf16r(var + 1e-5f))));
    }
}
__device__ __forceinline__ void ln_apply(const uint32_t (&x)[8], float2 st, uint32_t (&o)[8]) {
    const uint32_t m2 = pack_bf16(st.x, st.x);
#pragma unroll
    for (int i = 0; i < 8; i++) {
        const uint32_t d = hsub2(x[i], m2);
        o[i] = pack_bf16(bf_lo(d) * st.y, bf_hi(d) * st.y);
    }
}

constexpr int K1_THREADS = 352;
constexpr int UT_PAD = 128;
constexpr int UT_LEN = UT_PAD + S_;
constexpr int KR_LEN = 2080;
constexpr int YP_LEN = S_ + (S_ / 32) * 8;

struct __align__(128) K1Smem {
    bf16 uT[4][UT_LEN];
    bf16 xT[4][S_];
    bf16 kr[4][2][KR_LEN];
    float yP[4][YP_LEN];
    alignas(128) float st[S_ + S_ / 2];
    alignas(128) uint4 wS[512][4];
    float red[8][32];
    uint64_t bar, bar2, bar3, bar4;
};

__device__ __forceinline__ void mma16816(float (&c)[4], uint32_t a0, uint32_t a1, uint32_t a2, uint32_t a3, uint32_t b0, uint32_t b1) {
    asm("mma.sync.aligned.m16n8k16.row.col.f32.bf16.bf16.f32 {%0,%1,%2,%3}, {%4,%5,%6,%7}, {%8,%9}, {%0,%1,%2,%3};"
        : "+f"(c[0]), "+f"(c[1]), "+f"(c[2]), "+f"(c[3])
        : "r"(a0), "r"(a1), "r"(a2), "r"(a3), "r"(b0), "r"(b1));
}
__device__ __forceinline__ void ldsm_x4(uint32_t& r0, uint32_t& r1, uint32_t& r2, uint32_t& r3, uint32_t addr) {
    asm volatile("ldmatrix.sync.aligned.m8n8.x4.shared.b16 {%0,%1,%2,%3}, [%4];" : "=r"(r0), "=r"(r1), "=r"(r2), "=r"(r3) : "r"(addr) : "memory");
}

__device__ __forceinline__ void conv_mma(const bf16* uTc, const bf16* krlane, float (&acc)[16][4], int lane, int half) {
    const int lrow = lane & 7, lk = (lane >> 3) & 1, lt = lane >> 4;
    const uint32_t ubase = smem_u32(uTc) + (UT_PAD + 16 * (8 * lt + lrow) + 8 * lk) * 2;
#pragma unroll 1
    for (int pp = 0; pp < 4; pp++) {
        const int p = half * 4 + pp;
        uint32_t U[16][2];
#pragma unroll
        for (int j = 0; j < 16; j += 2) ldsm_x4(U[j][0], U[j][1], U[j + 1][0], U[j + 1][1], ubase + (j * 128 - p * 16) * 2);
        const uint32_t* kp = reinterpret_cast<const uint32_t*>(krlane - 16 * p);
        const volatile uint32_t* kpv = kp;
        uint32_t a0 = kp[0], a1 = kp[-4], a2 = kp[4], a3 = kpv[0];
#pragma unroll
        for (int q = 0; q < 16; q++) {
            uint32_t b0 = 0, b1 = 0, b2 = 0, b3 = 0;
            if (q < 15) { b0 = kp[-64 * (q + 1)]; b1 = kp[-64 * (q + 1) - 4]; b2 = kp[-64 * (q + 1) + 4]; b3 = kpv[-64 * (q + 1)]; }
#pragma unroll
            for (int n = 15; n >= q; n--) mma16816(acc[n], a0, a1, a2, a3, U[n - q][0], U[n - q][1]);
            a0 = b0; a1 = b1; a2 = b2; a3 = b3;
        }
    }
}

__device__ __forceinline__ void cp_async16(uint32_t dst, const void* src) {
    asm volatile("cp.async.cg.shared.global [%0], [%1], 16;" :: "r"(dst), "l"(src) : "memory");
}

__global__ void __cluster_dims__(2, 1, 1) __launch_bounds__(K1_THREADS, 1)
conv_kernel(const bf16* __restrict__ q, const bf16* __restrict__ k, const bf16* __restrict__ v,
            const bf16* __restrict__ shift_k, const bf16* __restrict__ ssm_k, const bf16* __restrict__ ssm_D,
            const __grid_constant__ CUtensorMap mapWg, const __grid_constant__ CUtensorMap mapWu, const bf16* __restrict__ wd) {
    extern __shared__ __align__(1024) uint8_t smem_raw[];
    pdl_launch();
    K1Smem& sm = *reinterpret_cast<K1Smem*>(smem_raw);
    const int tid = threadIdx.x, lane = tid & 31, warp = tid >> 5;
    const int bid = blockIdx.x;
    const int rank = bid & 1;
    const int c0 = 8 * (bid >> 1);
    const int cown = c0 + 4 * rank;
#define TMT 0
    TM(0, 0);
    const uint32_t bar = smem_u32(&sm.bar);
    if (tid == 0) {
        mbar_init(bar, 1);
        mbar_init(bar + 8, 1);
        mbar_init(bar + 16, 1);
        mbar_init(bar + 24, 1);
        asm volatile("fence.mbarrier_init.release.cluster;" ::: "memory");
        mbar_expect_tx(bar, 1024 * 4 * 2);
        mbar_expect_tx(bar + 8, 1024 * 4 * 2);
    }
    cluster_arrive_relaxed();

    if (warp < 8) {
        const int s0 = 1024 * rank + 4 * tid;
        uint4 kk[7], vv[4], qq[4], sw[4];
#pragma unroll
        for (int i = 0; i < 4; i++) kk[3 + i] = ldg128(k + (size_t)(s0 + i) * D_ + c0);
#pragma unroll
        for (int i = 0; i < 4; i++) vv[i] = ldg128(v + (size_t)(s0 + i) * D_ + c0);
        if (lane == 0) {
#pragma unroll
            for (int i = 0; i < 3; i++) {
                const int s = s0 - 3 + i;
                kk[i] = make_uint4(0, 0, 0, 0);
                if (s >= 0) kk[i] = ldg128(k + (size_t)s * D_ + c0);
            }
        }
#pragma unroll
        for (int i = 0; i < 4; i++) sw[i] = ldg128(shift_k + (size_t)c0 * 4 + 8 * i);
        uint4 kq[4]; uint32_t nx[4];
#pragma unroll
        for (int c = 0; c < 4; c++) {
            const bf16* kr = ssm_k + (size_t)(cown + c) * S_;
            kq[c] = ldg128(kr + 8 * tid);
            nx[c] = 0u;
            if (tid < 255) nx[c] = ldg16(kr + 8 * tid + 8);
        }
        const uint32_t dval = ldg16(ssm_D + cown + (warp >> 1));
        if (tid < 64) *reinterpret_cast<uint4*>(&sm.uT[tid >> 4][(tid & 15) * 8]) = make_uint4(0, 0, 0, 0);
#pragma unroll
        for (int i = 0; i < 3; i++) {
            uint4 t;
            t.x = __shfl_up_sync(0xffffffffu, kk[4 + i].x, 1); t.y = __shfl_up_sync(0xffffffffu, kk[4 + i].y, 1);
            t.z = __shfl_up_sync(0xffffffffu, kk[4 + i].z, 1); t.w = __shfl_up_sync(0xffffffffu, kk[4 + i].w, 1);
            if (lane != 0) kk[i] = t;
        }
        uint32_t kvw[4][4];
        const uint32_t* kkw = reinterpret_cast<const uint32_t*>(kk);
        const uint32_t* vvw = reinterpret_cast<const uint32_t*>(vv);
        const uint32_t* qqw = reinterpret_cast<const uint32_t*>(qq);
#pragma unroll
        for (int i2 = 0; i2 < 4; i2++) {
            const uint32_t t0 = __byte_perm(sw[i2].x, sw[i2].z, 0x5410), t1 = __byte_perm(sw[i2].x, sw[i2].z, 0x7632);
            const uint32_t t2 = __byte_perm(sw[i2].y, sw[i2].w, 0x5410), t3 = __byte_perm(sw[i2].y, sw[i2].w, 0x7632);
#pragma unroll
            for (int r = 0; r < 4; r++) {
                uint32_t a = hmul2(kkw[(r + 0) * 4 + i2], t3);
                a = hadd2(a, hmul2(kkw[(r + 1) * 4 + i2], t2));
                a = hadd2(a, hmul2(kkw[(r + 2) * 4 + i2], t1));
                a = hadd2(a, hmul2(kkw[(r + 3) * 4 + i2], t0));
                kvw[r][i2] = hmul2(a, vvw[r * 4 + i2]);
            }
        }
        TM(0, 1);
        cluster_wait();
        const uint32_t rbar = mapa(bar, (uint32_t)(rank ^ 1));
#pragma unroll
        for (int i2 = 0; i2 < 4; i2++) {
#pragma unroll
            for (int e = 0; e < 2; e++) {
                const uint32_t sel = e ? 0x7632 : 0x5410;
                const uint32_t w0 = __byte_perm(kvw[0][i2], kvw[1][i2], sel), w1 = __byte_perm(kvw[2][i2], kvw[3][i2], sel);
                const int cc = 2 * i2 + e;
                if ((cc >> 2) == rank) *reinterpret_cast<uint2*>(&sm.uT[cc & 3][UT_PAD + s0]) = make_uint2(w0, w1);
                else st_async_v2(mapa(smem_u32(&sm.uT[cc & 3][UT_PAD + s0]), (uint32_t)(rank ^ 1)), w0, w1, rbar);
            }
        }
#pragma unroll
        for (int c = 0; c < 4; c++) {
            uint4 a, b;
            a.x = __byte_perm(kq[c].w, 0, 0x1032); a.y = __byte_perm(kq[c].z, 0, 0x1032);
            a.z = __byte_perm(kq[c].y, 0, 0x1032); a.w = __byte_perm(kq[c].x, 0, 0x1032);
            b.x = __byte_perm(nx[c], kq[c].w, 0x7610); b.y = __byte_perm(kq[c].w, kq[c].z, 0x7610);
            b.z = __byte_perm(kq[c].z, kq[c].y, 0x7610); b.w = __byte_perm(kq[c].y, kq[c].x, 0x7610);
            *reinterpret_cast<uint4*>(&sm.kr[c][0][2040 - 8 * tid]) = a;
            *reinterpret_cast<uint4*>(&sm.kr[c][1][2040 - 8 * tid]) = b;
            if (tid == 0) {
                *reinterpret_cast<uint4*>(&sm.kr[c][1][2048]) = make_uint4(kq[c].x & 0xffffu, 0, 0, 0);
            } else if (tid < 8) {
                if (tid < 4) *reinterpret_cast<uint4*>(&sm.kr[c][1][2048 + 8 * tid]) = make_uint4(0, 0, 0, 0);
                else *reinterpret_cast<uint4*>(&sm.kr[c][0][2048 + 8 * (tid - 4)]) = make_uint4(0, 0, 0, 0);
            }
        }
#pragma unroll
        for (int i = 0; i < 4; i++) qq[i] = ldg128(q + (size_t)(s0 + i) * D_ + c0);
        TM(0, 3);
        named_bar(6, 352);
        mbar_wait_cluster(bar, 0);
        TM(0, 4);

        const int ch = warp >> 1, half = warp & 1;
        const int g = lane >> 2, t = lane & 3;
        float acc[16][4];
#pragma unroll
        for (int i = 0; i < 16; i++) { acc[i][0] = acc[i][1] = acc[i][2] = acc[i][3] = 0.f; }
        const bf16* krlane = (g & 1) ? &sm.kr[ch][0][2047 - g + 2 * t] : &sm.kr[ch][1][2048 - g + 2 * t];
        conv_mma(sm.uT[ch], krlane, acc, lane, half);
        TM(0, 5);
#pragma unroll
        for (int i2 = 0; i2 < 4; i2++) {
#pragma unroll
            for (int e = 0; e < 2; e++) {
                const uint32_t sel = e ? 0x7632 : 0x5410;
                const uint32_t w0 = __byte_perm(qqw[i2], qqw[4 + i2], sel), w1 = __byte_perm(qqw[8 + i2], qqw[12 + i2], sel);
                const int cc = 2 * i2 + e;
                if ((cc >> 2) == rank) *reinterpret_cast<uint2*>(&sm.xT[cc & 3][s0]) = make_uint2(w0, w1);
                else st_async_v2(mapa(smem_u32(&sm.xT[cc & 3][s0]), (uint32_t)(rank ^ 1)), w0, w1, rbar + 8);
            }
        }
        float* yp = &sm.yP[ch][40 * t + g];
        if (half) {
#pragma unroll
            for (int n = 0; n < 16; n++) {
                yp[160 * n] = acc[n][0];
                yp[160 * n + 16] = acc[n][1];
                yp[160 * n + 8] = acc[n][2];
                yp[160 * n + 24] = acc[n][3];
            }
        }
        named_bar(1 + ch, 64);
        if (!half) {
#pragma unroll
            for (int n = 0; n < 16; n++) {
                yp[160 * n] += acc[n][0];
                yp[160 * n + 16] += acc[n][1];
                yp[160 * n + 8] += acc[n][2];
                yp[160 * n + 24] += acc[n][3];
            }
        }
        named_bar(7, 288);
        mbar_wait_cluster(bar + 8, 0);
        TM(0, 6);
        {
            const int tt = tid & 63;
            bf16* dst = g_hT + (size_t)(cown + ch) * HT_PITCH;
            const uint32_t d2 = dval * 0x10001u;
#pragma unroll
            for (int j = 0; j < 4; j++) {
                const int s = (j * 64 + tt) * 8;
                const float* src = &sm.yP[ch][s + (s >> 5) * 8];
                const float4 a = *reinterpret_cast<const float4*>(src), b = *reinterpret_cast<const float4*>(src + 4);
                const uint4 kv4 = *reinterpret_cast<const uint4*>(&sm.uT[ch][UT_PAD + s]);
                const uint4 x4 = *reinterpret_cast<const uint4*>(&sm.xT[ch][s]);
                const uint32_t y2[4] = {hadd2(pack_bf16(a.x, a.y), hmul2(kv4.x, d2)), hadd2(pack_bf16(a.z, a.w), hmul2(kv4.y, d2)),
                                        hadd2(pack_bf16(b.x, b.y), hmul2(kv4.z, d2)), hadd2(pack_bf16(b.z, b.w), hmul2(kv4.w, d2))};
                const uint32_t xw[4] = {x4.x, x4.y, x4.z, x4.w};
                const uint4 m4 = *reinterpret_cast<const uint4*>(&sm.st[S_ + s / 2]);
                const float4 ra = *reinterpret_cast<const float4*>(&sm.st[s]), rb4 = *reinterpret_cast<const float4*>(&sm.st[s + 4]);
                const uint32_t mw[4] = {m4.x, m4.y, m4.z, m4.w};
                const float rw[8] = {ra.x, ra.y, ra.z, ra.w, rb4.x, rb4.y, rb4.z, rb4.w};
                uint32_t o[4];
#pragma unroll
                for (int i = 0; i < 4; i++) {
                    const uint32_t d = hsub2(xw[i], mw[i]);
                    const uint32_t qn = pack_bf16(bf_lo(d) * rw[2 * i], bf_hi(d) * rw[2 * i + 1]);
                    o[i] = hadd2(xw[i], hmul2(qn, y2[i]));
                }
                *reinterpret_cast<uint4*>(dst + s) = make_uint4(o[0], o[1], o[2], o[3]);
            }
        }
        TM(0, 7);
    } else {
        cluster_wait();
        named_bar(6, 352);
        const uint32_t hbar = bar + 16;
        if (warp < 10) {
            {
                const int rr = 8 * (warp - 8);
                uint32_t xq[4][2][8];
#pragma unroll
                for (int r = 0; r < 8; r++) {
                    const uint4 qa = ldg128(q + (size_t)(16 * bid + rr + r) * D_ + 8 * lane);
                    const uint4 qb = ldg128(q + (size_t)(16 * bid + rr + r) * D_ + 8 * (lane + 32));
                    uint32_t* x = xq[r >> 1][r & 1];
                    x[0] = qa.x; x[1] = qa.y; x[2] = qa.z; x[3] = qa.w; x[4] = qb.x; x[5] = qb.y; x[6] = qb.z; x[7] = qb.w;
                }
#pragma unroll
                for (int r2 = 0; r2 < 4; r2++) {
                    float2 sa[2];
                    ln_stats2(xq[r2], sa);
                    if (lane == 0) {
                        *reinterpret_cast<float2*>(&g_st1[16 * bid + rr + 2 * r2]) = make_float2(sa[0].y, sa[1].y);
                        reinterpret_cast<uint32_t*>(&g_st1[S_])[(16 * bid + rr) / 2 + r2] = pack_bf16(sa[0].x, sa[1].x);
                    }
                }
            }
            if (lane == 0) { __threadfence(); atomicAdd(&g_cnt, 1u); }
            if (warp == 9) return;
            {
                unsigned int c; int spins = 0;
                do { asm volatile("ld.acquire.gpu.global.u32 %0, [%1];" : "=r"(c) : "l"(&g_cnt) : "memory"); } while (c < 2 * gridDim.x && ++spins < (1 << 22));
            }
            if (lane == 0) {
                asm volatile("fence.proxy.async;" ::: "memory");
                mbar_expect_tx(hbar + 8, 12288);
                asm volatile("cp.async.bulk.shared::cluster.global.mbarrier::complete_tx::bytes [%0], [%1], %2, [%3];"
                    :: "r"(smem_u32(&sm.st[0])), "l"(&g_st1[0]), "r"(12288), "r"(hbar + 8) : "memory");
            }
            mbar_wait(hbar + 8, 0);
            named_bar(7, 288);
        } else {
            if (lane == 0) asm volatile("cp.async.bulk.prefetch.L2.global [%0], %1;" :: "l"(wd + (size_t)bid * 7168), "r"(14336) : "memory");
            if (bid < 112) {
                if (lane == 0) {
                    mbar_expect_tx(hbar, 32768);
                    const CUtensorMap* mw = (bid < 56) ? &mapWg : &mapWu;
                    const int col = 32 * ((bid < 56) ? bid : bid - 56);
                    tma_load_2d(smem_u32(&sm.wS[0][0]), mw, hbar, col, 0);
                    tma_load_2d(smem_u32(&sm.wS[256][0]), mw, hbar, col, 256);
                }
                mbar_wait(hbar, 0);
                const int cq = lane & 3, rgp = lane >> 2;
                float cs[8];
#pragma unroll
                for (int i = 0; i < 8; i++) cs[i] = 0.f;
#pragma unroll 4
                for (int r = 0; r < 64; r++) {
                    const uint4 w = sm.wS[r * 8 + rgp][cq];
                    cs[0] += bf_lo(w.x); cs[1] += bf_hi(w.x); cs[2] += bf_lo(w.y); cs[3] += bf_hi(w.y);
                    cs[4] += bf_lo(w.z); cs[5] += bf_hi(w.z); cs[6] += bf_lo(w.w); cs[7] += bf_hi(w.w);
                }
#pragma unroll
                for (int i = 0; i < 8; i++) {
                    cs[i] += __shfl_xor_sync(0xffffffffu, cs[i], 4);
                    cs[i] += __shfl_xor_sync(0xffffffffu, cs[i], 8);
                    cs[i] += __shfl_xor_sync(0xffffffffu, cs[i], 16);
                }
                if (lane < 4) {
                    *reinterpret_cast<float4*>(&g_colsum[32 * bid + lane * 8]) = make_float4(cs[0], cs[1], cs[2], cs[3]);
                    *reinterpret_cast<float4*>(&g_colsum[32 * bid + lane * 8 + 4]) = make_float4(cs[4], cs[5], cs[6], cs[7]);
                }
            }
        }
    }
#undef TMT
}

constexpr int G1_THREADS = 384;
constexpr int G1_STAGES = 3;
constexpr int G1_A_BYTES = 8 * 16384;
constexpr int G1_B_STAGE = 32768;
constexpr int G1_OFF_B = G1_A_BYTES;
constexpr int G1_OFF_STATS = G1_OFF_B + G1_STAGES * G1_B_STAGE;
constexpr int G1_OFF_CS = G1_OFF_STATS + 1024;
constexpr int G1_OFF_BAR = G1_OFF_CS + 1792;
constexpr int G1_SMEM = G1_OFF_BAR + 128;

__device__ __forceinline__ float tanh_fast(float x) { float t; asm("tanh.approx.f32 %0, %1;" : "=f"(t) : "f"(x)); return t; }

template <int NT>
__device__ __forceinline__ void g1_math(const float (&acc)[NT * 8], const float* cs_g, const float* cs_u, float2 st0, float2 st1, uint32_t (&P)[NT * 2], int t) {
    const float r0 = st0.y, r1 = st1.y, m0 = -st0.x * st0.y, m1 = -st1.x * st1.y;
#pragma unroll
    for (int j = 0; j < NT; j++) {
        const float2 cg = *reinterpret_cast<const float2*>(cs_g + 8 * j + 2 * t);
        const float2 cu = *reinterpret_cast<const float2*>(cs_u + 8 * j + 2 * t);
        float r[4];
#pragma unroll
        for (int e = 0; e < 4; e++) {
            const float rr = (e < 2) ? r0 : r1, mm = (e < 2) ? m0 : m1;
            const float gv = fmaf(acc[4 * j + e], rr, mm * ((e & 1) ? cg.y : cg.x));
            const float uv = fmaf(acc[4 * (NT + j) + e], rr, mm * ((e & 1) ? cu.y : cu.x));
            r[e] = fmaf(tanh_fast(0.5f * gv), 0.5f, 0.5f) * uv;
        }
        P[2 * j] = pack_bf16(r[0], r[1]);
        P[2 * j + 1] = pack_bf16(r[2], r[3]);
    }
}
template <int NT>
__device__ __forceinline__ void g1_store(uint32_t (&P)[NT * 2], bf16* out0, int t) {
#pragma unroll
    for (int j0 = 0; j0 < NT; j0 += 4) {
        quad_transpose(P[2 * j0], P[2 * j0 + 2], P[2 * j0 + 4], P[2 * j0 + 6], t);
        quad_transpose(P[2 * j0 + 1], P[2 * j0 + 3], P[2 * j0 + 5], P[2 * j0 + 7], t);
        *reinterpret_cast<uint4*>(out0 + 8 * (j0 + t)) = make_uint4(P[2 * j0], P[2 * j0 + 2], P[2 * j0 + 4], P[2 * j0 + 6]);
        *reinterpret_cast<uint4*>(out0 + 8 * F_ + 8 * (j0 + t)) = make_uint4(P[2 * j0 + 1], P[2 * j0 + 3], P[2 * j0 + 5], P[2 * j0 + 7]);
    }
}

__global__ void __cluster_dims__(2, 1, 1) __launch_bounds__(G1_THREADS, 1)
gemm1_kernel(const __grid_constant__ CUtensorMap mapA, const __grid_constant__ CUtensorMap mapG4, const __grid_constant__ CUtensorMap mapU4,
             const __grid_constant__ CUtensorMap mapG3, const __grid_constant__ CUtensorMap mapU3) {
    extern __shared__ __align__(1024) uint8_t smem_raw[];
    const uint32_t sb = smem_u32(smem_raw);
    const int tid = threadIdx.x, lane = tid & 31, warp = tid >> 5, wgi = tid >> 7;
    const int rank = blockIdx.x & 1;
    const int cb = blockIdx.x & 7, rb = blockIdx.x >> 3;
#define TMT 128
    TM(2, 0);
    pdl_launch();
    if (tid == 32) { prefetch_map(&mapA); prefetch_map(&mapG3); prefetch_map(&mapU3); }
    const uint32_t barA = sb + G1_OFF_BAR;
    const uint32_t barF = barA + 64;
    const uint32_t barE = barF + 8 * G1_STAGES;
    const uint32_t barS = barE + 8 * G1_STAGES;
    if (tid == 0) {
        for (int i = 0; i < 8; i++) mbar_init(barA + 8 * i, 1);
        for (int i = 0; i < G1_STAGES; i++) { mbar_init(barF + 8 * i, 1); mbar_init(barE + 8 * i, 2); }
        mbar_init(barS, 1);
        for (int i = 0; i < 8; i++) mbar_expect_tx(barA + 8 * i, 16384);
        asm volatile("fence.mbarrier_init.release.cluster;" ::: "memory");
    }
    __syncthreads();
    cluster_arrive_relaxed();

    if (wgi == 0) {
        reg_dealloc<40>();
        if (warp == 0) {
            if (lane == 0) {
                int st = 0, ph = 1;
                for (int it = 0; it < 16; it++) {
                    const int kc = it & 7;
                    mbar_wait(barE + 8 * st, ph);
                    const uint32_t dst = sb + G1_OFF_B + st * G1_B_STAGE;
                    if (it < 8) {
                        mbar_expect_tx(barF + 8 * st, 32768);
                        tma_load_3d(dst, &mapG4, barF + 8 * st, 0, kc * 64, cb * 7);
                        tma_load_3d(dst + 16384, &mapU4, barF + 8 * st, 0, kc * 64, cb * 7);
                    } else {
                        mbar_expect_tx(barF + 8 * st, 24576);
                        tma_load_3d(dst, &mapG3, barF + 8 * st, 0, kc * 64, cb * 7 + 4);
                        tma_load_3d(dst + 12288, &mapU3, barF + 8 * st, 0, kc * 64, cb * 7 + 4);
                    }
                    if (++st == G1_STAGES) { st = 0; ph ^= 1; }
                }
            }
            __syncwarp();
            cluster_wait();
        } else if (warp == 1) {
            cluster_wait();
            pdl_wait();
            if (lane < 4) {
                const int c = 2 * lane + rank;
                tma_load_3d_mc(sb + c * 16384, &mapA, barA + 8 * c, 0, c * 64, rb * 2, (uint16_t)3);
            }
            __syncwarp();
            float* cs = reinterpret_cast<float*>(smem_raw + G1_OFF_CS);
            for (int i = lane; i < 448; i += 32) cs[i] = __ldcg((i < 224) ? &g_colsum[cb * 224 + i] : &g_colsum[F_ + cb * 224 + (i - 224)]);
            __syncwarp();
            if (lane == 0) mbar_arrive(barS);
        } else {
            cluster_wait();
        }
    } else {
        reg_alloc<232>();
        cluster_wait();
        const int cw = wgi - 1;
        const int g = lane >> 2, t = lane & 3, wl = warp & 3, tl = tid & 127;
        bf16* outp = g_hh + (size_t)(rb * 128 + cw * 64 + wl * 16 + g) * F_ + cb * 224;
        const float* cs = reinterpret_cast<const float*>(smem_raw + G1_OFF_CS);
        int st = 0, ph = 0;
        float2 st0, st1;
        uint32_t P1[32];
        {
            float acc[128];
            const int kq = lane >> 3, mp = lane & 7;
            const uint8_t* sbase = smem_raw + cw * 8192 + kq * 128 + (mp & 3) * 4;
            const int mc = 2 * wl + (mp >> 2);
            float p0 = 0.f, p1 = 0.f, s0 = 0.f, s1 = 0.f, q0 = 0.f, q1 = 0.f;
#pragma unroll 1
            for (int kc = 0; kc < 8; kc++) {
                mbar_wait(barA + 8 * kc, 0);
                mbar_wait(barF + 8 * st, ph);
                if (tl == 0 && cw == 0) TR(1, kc);
                wgmma_fence();
                const uint32_t aaddr = sb + kc * 16384 + cw * 8192;
                const uint32_t baddr = sb + G1_OFF_B + st * G1_B_STAGE;
#pragma unroll
                for (int kk = 0; kk < 4; kk++)
                    wgmma_m64n256k16_ss(acc, make_desc(aaddr + kk * 2048, 8192, 1024, 1), make_desc(baddr + kk * 1024, 4096, 512, 2), (kc | kk) != 0);
                wgmma_commit();
                if (kc == 0) {
                    const uint32_t w = *reinterpret_cast<const uint32_t*>(smem_raw + cw * 8192 + (mc << 4) + (mp & 3) * 4);
                    p0 = bf_lo(w); p1 = bf_hi(w);
                }
#pragma unroll
                for (int i = 0; i < 16; i++) {
                    const int kr = 4 * i;
                    const uint32_t w = *reinterpret_cast<const uint32_t*>(sbase + kc * 16384 + kr * 128 + ((mc ^ ((kr + kq) & 7)) << 4));
                    const float d0 = bf_lo(w) - p0, d1 = bf_hi(w) - p1;
                    s0 += d0; s1 += d1; q0 = fmaf(d0, d0, q0); q1 = fmaf(d1, d1, q1);
                }
                wgmma_wait<0>();
                if (tl == 0) mbar_arrive(barE + 8 * st);
                if (++st == G1_STAGES) { st = 0; ph ^= 1; }
            }
            TM(2, 1);
            {
#pragma unroll
                for (int o = 8; o <= 16; o <<= 1) {
                    s0 += __shfl_xor_sync(0xffffffffu, s0, o); s1 += __shfl_xor_sync(0xffffffffu, s1, o);
                    q0 += __shfl_xor_sync(0xffffffffu, q0, o); q1 += __shfl_xor_sync(0xffffffffu, q1, o);
                }
                const float md0 = s0 * (1.0f / D_), md1 = s1 * (1.0f / D_);
                const float v0 = bf16r(fmaxf(fmaf(-md0, md0, q0 * (1.0f / D_)), 0.f)), v1 = bf16r(fmaxf(fmaf(-md1, md1, q1 * (1.0f / D_)), 0.f));
                const float ma = bf16r(p0 + md0), mb = bf16r(p1 + md1);
                const float ra = 1.0f / bf16r(sqrtf(bf16r(v0 + 1e-5f))), rbb = 1.0f / bf16r(sqrtf(bf16r(v1 + 1e-5f)));
                const float mA = __shfl_sync(0xffffffffu, ma, g >> 1), mB = __shfl_sync(0xffffffffu, mb, g >> 1);
                const float rA = __shfl_sync(0xffffffffu, ra, g >> 1), rB = __shfl_sync(0xffffffffu, rbb, g >> 1);
                const float mC = __shfl_sync(0xffffffffu, ma, 4 + (g >> 1)), mD = __shfl_sync(0xffffffffu, mb, 4 + (g >> 1));
                const float rC = __shfl_sync(0xffffffffu, ra, 4 + (g >> 1)), rD = __shfl_sync(0xffffffffu, rbb, 4 + (g >> 1));
                st0 = (g & 1) ? make_float2(mB, rB) : make_float2(mA, rA);
                st1 = (g & 1) ? make_float2(mD, rD) : make_float2(mC, rC);
            }
            mbar_wait(barS, 0);
            TM(2, 5);
            g1_math<16>(acc, cs, cs + 224, st0, st1, P1, t);
            TM(2, 2);
        }
        {
            float acc[96];
#pragma unroll 1
            for (int kc = 0; kc < 8; kc++) {
                mbar_wait(barF + 8 * st, ph);
                if (tl == 0 && cw == 0) TR(1, 8 + kc);
                wgmma_fence();
                const uint32_t aaddr = sb + kc * 16384 + cw * 8192;
                const uint32_t baddr = sb + G1_OFF_B + st * G1_B_STAGE;
#pragma unroll
                for (int kk = 0; kk < 4; kk++)
                    wgmma_m64n192k16_ss(acc, make_desc(aaddr + kk * 2048, 8192, 1024, 1), make_desc(baddr + kk * 1024, 4096, 512, 2), (kc | kk) != 0);
                wgmma_commit();
                if (kc == 0) g1_store<16>(P1, outp, t);
                wgmma_wait<0>();
                if (tl == 0) mbar_arrive(barE + 8 * st);
                if (++st == G1_STAGES) { st = 0; ph ^= 1; }
            }
            TM(2, 3);
            uint32_t P2[24];
            g1_math<12>(acc, cs + 128, cs + 224 + 128, st0, st1, P2, t);
            g1_store<12>(P2, outp + 128, t);
            TM(2, 4);
        }
    }
}

constexpr int G2_THREADS = 384;
constexpr int G2_STAGES = 6;
constexpr int G2_STAGE = 32768;
constexpr int G2_OFF_X = G2_STAGES * G2_STAGE;
constexpr int G2_OFF_BAR = G2_OFF_X + 32768;
constexpr int G2_SMEM = G2_OFF_BAR + 128;
constexpr int G2_KSTEPS = 14;

__device__ __forceinline__ void ldsm_x4_t(uint32_t& r0, uint32_t& r1, uint32_t& r2, uint32_t& r3, uint32_t addr) {
    asm volatile("ldmatrix.sync.aligned.m8n8.x4.trans.shared.b16 {%0,%1,%2,%3}, [%4];" : "=r"(r0), "=r"(r1), "=r"(r2), "=r"(r3) : "r"(addr) : "memory");
}

__global__ void __cluster_dims__(2, 1, 1) __launch_bounds__(G2_THREADS, 1)
gemm2_kernel(const __grid_constant__ CUtensorMap mapHH, const __grid_constant__ CUtensorMap mapWd, const __grid_constant__ CUtensorMap mapH,
             bf16* __restrict__ out) {
    extern __shared__ __align__(1024) uint8_t smem_raw[];
    const uint32_t sb = smem_u32(smem_raw);
    const int tid = threadIdx.x, lane = tid & 31, warp = tid >> 5, wgi = tid >> 7;
    const int ks = blockIdx.x & 1, nb = (blockIdx.x >> 1) & 3, rb = blockIdx.x >> 3;
    TM(3, 0);
    if (tid == 32) { prefetch_map(&mapHH); prefetch_map(&mapH); }
    const uint32_t barF = sb + G2_OFF_BAR;
    const uint32_t barE = barF + 8 * G2_STAGES;
    const uint32_t barX = barE + 8 * G2_STAGES;
    if (tid == 0) {
        for (int i = 0; i < G2_STAGES; i++) { mbar_init(barF + 8 * i, 1); mbar_init(barE + 8 * i, 2); }
        mbar_init(barX, 1);
        asm volatile("fence.mbarrier_init.release.cluster;" ::: "memory");
        mbar_expect_tx(barX, 32768);
        for (int it = 0; it < G2_STAGES; it++) {
            mbar_expect_tx(barF + 8 * it, 32768);
            tma_load_3d(sb + it * G2_STAGE + 16384, &mapWd, barF + 8 * it, 0, ks * 896 + it * 64, nb * 2);
        }
    }
    __syncthreads();
    cluster_arrive_relaxed();

    if (wgi == 0) {
        if (tid == 0) {
            pdl_wait();
            for (int it = 0; it < G2_STAGES; it++)
                tma_load_2d(sb + it * G2_STAGE, &mapHH, barF + 8 * it, ks * 896 + it * 64, rb * 128);
            if (blockIdx.x == 0) g_cnt = 0u;
            int st = 0, ph = 0;
            for (int it = G2_STAGES; it < G2_KSTEPS; it++) {
                mbar_wait(barE + 8 * st, ph);
                const uint32_t dst = sb + st * G2_STAGE;
                const int k0 = ks * 896 + it * 64;
                mbar_expect_tx(barF + 8 * st, 32768);
                tma_load_2d(dst, &mapHH, barF + 8 * st, k0, rb * 128);
                tma_load_3d(dst + 16384, &mapWd, barF + 8 * st, 0, k0, nb * 2);
                if (++st == G2_STAGES) { st = 0; ph ^= 1; }
            }
            mbar_wait(barE + 8 * st, ph);
            mbar_expect_tx(barF + 8 * st, 16384);
            tma_load_2d(sb + st * G2_STAGE, &mapH, barF + 8 * st, rb * 128 + ks * 64, nb * 128);
        }
        __syncwarp();
        cluster_wait();
    } else {
        const int cw = wgi - 1;
        const int g = lane >> 2, t = lane & 3, wl = warp & 3;
        const int tl = tid & 127;
        int st = 0, ph = 0;
        float acc[64];
#pragma unroll 1
        for (int it = 0; it < G2_KSTEPS; it++) {
            mbar_wait(barF + 8 * st, ph);
            if (it == 0) TM(3, 1);
            wgmma_fence();
            const uint32_t aaddr = sb + st * G2_STAGE + cw * 8192;
            const uint32_t baddr = sb + st * G2_STAGE + 16384;
#pragma unroll
            for (int kk = 0; kk < 4; kk++)
                wgmma_m64n128k16_ss(acc, make_desc(aaddr + kk * 32, 16, 1024, 1), make_desc(baddr + kk * 2048, 8192, 1024, 1), (it | kk) != 0);
            wgmma_commit();
            wgmma_wait<0>();
            if (tl == 0) mbar_arrive(barE + 8 * st);
            if (++st == G2_STAGES) { st = 0; ph ^= 1; }
        }
        TM(3, 2);
        cluster_wait();
        if (cw != ks) {
            const uint32_t dst = mapa(sb + G2_OFF_X + tl * 16, (uint32_t)(ks ^ 1));
            const uint32_t rbar = mapa(barX, (uint32_t)(ks ^ 1));
#pragma unroll
            for (int i = 0; i < 16; i++) st_async_v4f(dst + i * 2048, acc[4 * i], acc[4 * i + 1], acc[4 * i + 2], acc[4 * i + 3], rbar);
        } else {
            const float4* xb = reinterpret_cast<const float4*>(smem_raw + G2_OFF_X) + tl;
            const int row0 = rb * 128 + cw * 64 + wl * 16 + g;
            bf16* o0 = out + (size_t)row0 * D_ + nb * 128;
            uint32_t ha[16], hb[16];
            mbar_wait(barF + 8 * st, ph);
            {
                const int chl = 8 * (lane >> 4) + (lane & 7), sb8 = 2 * wl + ((lane >> 3) & 1);
                const uint32_t hbase = sb + st * G2_STAGE + chl * 128 + ((sb8 ^ (lane & 7)) << 4);
#pragma unroll
                for (int j = 0; j < 16; j += 2) ldsm_x4_t(ha[j], hb[j], ha[j + 1], hb[j + 1], hbase + j * 1024);
            }
            mbar_wait_cluster(barX, 0);
            TM(3, 4);
#pragma unroll
            for (int j0 = 0; j0 < 16; j0 += 4) {
                uint32_t P0[4], P1[4];
#pragma unroll
                for (int jj = 0; jj < 4; jj++) {
                    const int j = j0 + jj;
                    const float4 x = xb[j * 128];
                    P0[jj] = hadd2(ha[j], pack_bf16(acc[4 * j] + x.x, acc[4 * j + 1] + x.y));
                    P1[jj] = hadd2(hb[j], pack_bf16(acc[4 * j + 2] + x.z, acc[4 * j + 3] + x.w));
                }
                quad_transpose(P0[0], P0[1], P0[2], P0[3], t);
                quad_transpose(P1[0], P1[1], P1[2], P1[3], t);
                *reinterpret_cast<uint4*>(o0 + 8 * (j0 + t)) = make_uint4(P0[0], P0[1], P0[2], P0[3]);
                *reinterpret_cast<uint4*>(o0 + 8 * D_ + 8 * (j0 + t)) = make_uint4(P1[0], P1[1], P1[2], P1[3]);
            }
        }
        TM(3, 5);
    }
#undef TMT
}

typedef CUresult (*EncodeFn)(CUtensorMap*, CUtensorMapDataType, cuuint32_t, void*, const cuuint64_t*, const cuuint64_t*,
                             const cuuint32_t*, const cuuint32_t*, CUtensorMapInterleave, CUtensorMapSwizzle,
                             CUtensorMapL2promotion, CUtensorMapFloatOOBfill);

static void enc2d(EncodeFn enc, CUtensorMap* m, const void* p, int rows, int cols, int brows, int bcols, int pitch = 0) {
    cuuint64_t dims[2] = {(cuuint64_t)cols, (cuuint64_t)rows};
    cuuint64_t strides[1] = {(cuuint64_t)(pitch ? pitch : cols) * 2};
    cuuint32_t box[2] = {(cuuint32_t)bcols, (cuuint32_t)brows};
    cuuint32_t es[2] = {1, 1};
    enc(m, CU_TENSOR_MAP_DATA_TYPE_BFLOAT16, 2, const_cast<void*>(p), dims, strides, box, es, CU_TENSOR_MAP_INTERLEAVE_NONE,
        bcols == 32 ? CU_TENSOR_MAP_SWIZZLE_64B : CU_TENSOR_MAP_SWIZZLE_128B, CU_TENSOR_MAP_L2_PROMOTION_L2_128B, CU_TENSOR_MAP_FLOAT_OOB_FILL_NONE);
}
static void enc2d_plain(EncodeFn enc, CUtensorMap* m, const void* p, int rows, int cols, int brows, int bcols) {
    cuuint64_t dims[2] = {(cuuint64_t)cols, (cuuint64_t)rows};
    cuuint64_t strides[1] = {(cuuint64_t)cols * 2};
    cuuint32_t box[2] = {(cuuint32_t)bcols, (cuuint32_t)brows};
    cuuint32_t es[2] = {1, 1};
    enc(m, CU_TENSOR_MAP_DATA_TYPE_BFLOAT16, 2, const_cast<void*>(p), dims, strides, box, es, CU_TENSOR_MAP_INTERLEAVE_NONE,
        CU_TENSOR_MAP_SWIZZLE_NONE, CU_TENSOR_MAP_L2_PROMOTION_L2_128B, CU_TENSOR_MAP_FLOAT_OOB_FILL_NONE);
}
static void enc3d(EncodeFn enc, CUtensorMap* m, const void* p, int rows, int cols, int atom, int brows, int natoms, int pitch = 0) {
    cuuint64_t dims[3] = {(cuuint64_t)atom, (cuuint64_t)rows, (cuuint64_t)(cols / atom)};
    cuuint64_t strides[2] = {(cuuint64_t)(pitch ? pitch : cols) * 2, (cuuint64_t)atom * 2};
    cuuint32_t box[3] = {(cuuint32_t)atom, (cuuint32_t)brows, (cuuint32_t)natoms};
    cuuint32_t es[3] = {1, 1, 1};
    enc(m, CU_TENSOR_MAP_DATA_TYPE_BFLOAT16, 3, const_cast<void*>(p), dims, strides, box, es, CU_TENSOR_MAP_INTERLEAVE_NONE,
        atom == 32 ? CU_TENSOR_MAP_SWIZZLE_64B : CU_TENSOR_MAP_SWIZZLE_128B, CU_TENSOR_MAP_L2_PROMOTION_L2_128B, CU_TENSOR_MAP_FLOAT_OOB_FILL_NONE);
}

extern "C" void kernel_launch(void* const* d_in, const int* in_sizes, int n_in, void* d_out, int out_size) {
    const bf16* q = (const bf16*)d_in[0];
    const bf16* k = (const bf16*)d_in[1];
    const bf16* v = (const bf16*)d_in[2];
    const bf16* shift_k = (const bf16*)d_in[3];
    const bf16* ssm_k = (const bf16*)d_in[4];
    const bf16* ssm_D = (const bf16*)d_in[5];
    const bf16* wg = (const bf16*)d_in[7];
    const bf16* wu = (const bf16*)d_in[8];
    const bf16* wd = (const bf16*)d_in[9];
    bf16* out = (bf16*)d_out;

    static EncodeFn enc = nullptr;
    static void *p_hT = nullptr, *p_hh = nullptr;
    if (!enc) {
        void* fn = nullptr; cudaDriverEntryPointQueryResult qr;
        cudaGetDriverEntryPoint("cuTensorMapEncodeTiled", &fn, cudaEnableDefault, &qr);
        enc = (EncodeFn)fn;
        cudaGetSymbolAddress(&p_hT, g_hT);
        cudaGetSymbolAddress(&p_hh, g_hh);
        cudaFuncSetAttribute(conv_kernel, cudaFuncAttributeMaxDynamicSharedMemorySize, (int)sizeof(K1Smem));
        cudaFuncSetAttribute(gemm1_kernel, cudaFuncAttributeMaxDynamicSharedMemorySize, G1_SMEM);
        cudaFuncSetAttribute(gemm2_kernel, cudaFuncAttributeMaxDynamicSharedMemorySize, G2_SMEM);
    }
    CUtensorMap mA, mG64, mU64, mG32, mU32, mHH, mWd, mH, mWgp, mWup;
    enc2d_plain(enc, &mWgp, wg, D_, F_, 256, 32);
    enc2d_plain(enc, &mWup, wu, D_, F_, 256, 32);
    enc3d(enc, &mA, p_hT, D_, S_, 64, 64, 2, HT_PITCH);
    enc2d(enc, &mH, p_hT, D_, S_, 128, 64, HT_PITCH);
    enc3d(enc, &mG64, wg, D_, F_, 32, 64, 4);
    enc3d(enc, &mU64, wu, D_, F_, 32, 64, 4);
    enc3d(enc, &mG32, wg, D_, F_, 32, 64, 3);
    enc3d(enc, &mU32, wu, D_, F_, 32, 64, 3);
    enc2d(enc, &mHH, p_hh, S_, F_, 128, 64);
    enc3d(enc, &mWd, wd, F_, D_, 64, 64, 2);

    cudaStream_t st = cudaStreamPerThread;
    cudaLaunchAttribute at[1];
    at[0].id = cudaLaunchAttributeProgrammaticStreamSerialization;
    at[0].val.programmaticStreamSerializationAllowed = 1;
    cudaLaunchConfig_t cfg = {};
    cfg.stream = st; cfg.attrs = at; cfg.numAttrs = 1;
    conv_kernel<<<128, K1_THREADS, sizeof(K1Smem), st>>>(q, k, v, shift_k, ssm_k, ssm_D, mWgp, mWup, wd);
    cfg.gridDim = dim3(128); cfg.blockDim = dim3(G1_THREADS); cfg.dynamicSmemBytes = G1_SMEM;
    cudaLaunchKernelEx(&cfg, gemm1_kernel, mA, mG64, mU64, mG32, mU32);
    cfg.gridDim = dim3(128); cfg.blockDim = dim3(G2_THREADS); cfg.dynamicSmemBytes = G2_SMEM;
    cudaLaunchKernelEx(&cfg, gemm2_kernel, mHH, mWd, mH, out);
}
```

```cpp
#include <cuda_runtime.h>
#include <cuda_bf16.h>
#include <cuda.h>
#include <stdint.h>

typedef __nv_bfloat16 bf16;
constexpr int S_ = 2048, D_ = 512, F_ = 1792;

constexpr int HT_PITCH = S_ + 64;
__device__ __align__(128) bf16 g_hT[D_ * HT_PITCH];
__device__ bf16 g_hh[S_ * F_];
__device__ __align__(128) float g_st1[S_ + S_ / 2];
__device__ float g_colsum[2 * F_];
__device__ unsigned int g_cnt;

#define TM(k, i)
#define TR(k, i)
__device__ __forceinline__ uint32_t smem_u32(const void* p) { return (uint32_t)__cvta_generic_to_shared(p); }
__device__ __forceinline__ float bf16r(float x) { return __bfloat162float(__float2bfloat16_rn(x)); }
__device__ __forceinline__ float bf_lo(uint32_t w) { return __uint_as_float(w << 16); }
__device__ __forceinline__ float bf_hi(uint32_t w) { return __uint_as_float(w & 0xffff0000u); }
__device__ __forceinline__ uint32_t pack_bf16(float lo, float hi) {
    __nv_bfloat162 v = __floats2bfloat162_rn(lo, hi);
    return *reinterpret_cast<uint32_t*>(&v);
}
__device__ __forceinline__ uint32_t hmul2(uint32_t a, uint32_t b) {
    __nv_bfloat162 r = __hmul2_rn(*reinterpret_cast<__nv_bfloat162*>(&a), *reinterpret_cast<__nv_bfloat162*>(&b));
    return *reinterpret_cast<uint32_t*>(&r);
}
__device__ __forceinline__ uint32_t hadd2(uint32_t a, uint32_t b) {
    __nv_bfloat162 r = __hadd2_rn(*reinterpret_cast<__nv_bfloat162*>(&a), *reinterpret_cast<__nv_bfloat162*>(&b));
    return *reinterpret_cast<uint32_t*>(&r);
}
__device__ __forceinline__ uint4 ldg128(const void* p) {
    uint4 r; asm volatile("ld.global.nc.v4.u32 {%0,%1,%2,%3}, [%4];" : "=r"(r.x), "=r"(r.y), "=r"(r.z), "=r"(r.w) : "l"(p)); return r;
}
__device__ __forceinline__ uint4 ldcg128(const void* p) {
    uint4 r; asm volatile("ld.global.cg.v4.u32 {%0,%1,%2,%3}, [%4];" : "=r"(r.x), "=r"(r.y), "=r"(r.z), "=r"(r.w) : "l"(p)); return r;
}
__device__ __forceinline__ uint32_t ldg16(const void* p) {
    unsigned short r; asm volatile("ld.global.nc.u16 %0, [%1];" : "=h"(r) : "l"(p)); return (uint32_t)r;
}
__device__ __forceinline__ void mbar_init(uint32_t bar, int cnt) { asm volatile("mbarrier.init.shared::cta.b64 [%0], %1;" :: "r"(bar), "r"(cnt)); }
__device__ __forceinline__ void mbar_expect_tx(uint32_t bar, uint32_t bytes) { asm volatile("mbarrier.arrive.expect_tx.shared::cta.b64 _, [%0], %1;" :: "r"(bar), "r"(bytes) : "memory"); }
__device__ __forceinline__ void mbar_arrive(uint32_t bar) { asm volatile("mbarrier.arrive.shared::cta.b64 _, [%0];" :: "r"(bar) : "memory"); }
__device__ __forceinline__ void mbar_arrive_cluster(uint32_t bar, uint32_t cta) {
    asm volatile("{\n.reg .b32 ra;\nmapa.shared::cluster.u32 ra, %0, %1;\nmbarrier.arrive.shared::cluster.b64 _, [ra];\n}" :: "r"(bar), "r"(cta) : "memory");
}
__device__ __forceinline__ void mbar_wait(uint32_t bar, uint32_t parity) {
    asm volatile("{\n.reg .pred P1;\nLAB_WAIT:\nmbarrier.try_wait.parity.shared::cta.b64 P1, [%0], %1;\n@P1 bra DONE;\nbra LAB_WAIT;\nDONE:\n}" :: "r"(bar), "r"(parity) : "memory");
}
__device__ __forceinline__ void mbar_wait_cluster(uint32_t bar, uint32_t parity) {
    asm volatile("{\n.reg .pred P1;\nLAB_WAIT:\nmbarrier.try_wait.parity.acquire.cluster.shared::cta.b64 P1, [%0], %1;\n@P1 bra DONE;\nbra LAB_WAIT;\nDONE:\n}" :: "r"(bar), "r"(parity) : "memory");
}
__device__ __forceinline__ void tma_load_2d(uint32_t dst, const CUtensorMap* map, uint32_t bar, int c0, int c1) {
    asm volatile("cp.async.bulk.tensor.2d.shared::cluster.global.mbarrier::complete_tx::bytes [%0], [%1, {%3, %4}], [%2];"
        :: "r"(dst), "l"(map), "r"(bar), "r"(c0), "r"(c1) : "memory");
}
__device__ __forceinline__ void tma_load_2d_mc(uint32_t dst, const CUtensorMap* map, uint32_t bar, int c0, int c1, uint16_t mask) {
    asm volatile("cp.async.bulk.tensor.2d.shared::cluster.global.mbarrier::complete_tx::bytes.multicast::cluster [%0], [%1, {%3, %4}], [%2], %5;"
        :: "r"(dst), "l"(map), "r"(bar), "r"(c0), "r"(c1), "h"(mask) : "memory");
}
__device__ __forceinline__ void tma_load_3d_mc(uint32_t dst, const CUtensorMap* map, uint32_t bar, int c0, int c1, int c2, uint16_t mask) {
    asm volatile("cp.async.bulk.tensor.3d.shared::cluster.global.mbarrier::complete_tx::bytes.multicast::cluster [%0], [%1, {%3, %4, %5}], [%2], %6;"
        :: "r"(dst), "l"(map), "r"(bar), "r"(c0), "r"(c1), "r"(c2), "h"(mask) : "memory");
}
__device__ __forceinline__ void tma_load_3d(uint32_t dst, const CUtensorMap* map, uint32_t bar, int c0, int c1, int c2) {
    asm volatile("cp.async.bulk.tensor.3d.shared::cluster.global.mbarrier::complete_tx::bytes [%0], [%1, {%3, %4, %5}], [%2];"
        :: "r"(dst), "l"(map), "r"(bar), "r"(c0), "r"(c1), "r"(c2) : "memory");
}
__device__ __forceinline__ void cluster_arrive() { asm volatile("barrier.cluster.arrive.aligned;" ::: "memory"); }
__device__ __forceinline__ void cluster_arrive_relaxed() { asm volatile("barrier.cluster.arrive.relaxed.aligned;" ::: "memory"); }
__device__ __forceinline__ void cluster_wait() { asm volatile("barrier.cluster.wait.aligned;" ::: "memory"); }
__device__ __forceinline__ uint32_t mapa(uint32_t addr, uint32_t cta) {
    uint32_t r; asm volatile("mapa.shared::cluster.u32 %0, %1, %2;" : "=r"(r) : "r"(addr), "r"(cta)); return r;
}
__device__ __forceinline__ void st_async_v2(uint32_t addr, uint32_t a, uint32_t b, uint32_t rbar) {
    asm volatile("st.async.weak.shared::cluster.mbarrier::complete_tx::bytes.v2.b32 [%0], {%1, %2}, [%3];" :: "r"(addr), "r"(a), "r"(b), "r"(rbar) : "memory");
}
__device__ __forceinline__ void st_async_v4f(uint32_t addr, float a, float b, float c, float d, uint32_t rbar) {
    asm volatile("st.async.weak.shared::cluster.mbarrier::complete_tx::bytes.v4.f32 [%0], {%1, %2, %3, %4}, [%5];" :: "r"(addr), "f"(a), "f"(b), "f"(c), "f"(d), "r"(rbar) : "memory");
}
__device__ __forceinline__ void wgmma_fence() { asm volatile("wgmma.fence.sync.aligned;" ::: "memory"); }
__device__ __forceinline__ void wgmma_commit() { asm volatile("wgmma.commit_group.sync.aligned;" ::: "memory"); }
template <int N> __device__ __forceinline__ void wgmma_wait() { asm volatile("wgmma.wait_group.sync.aligned %0;" :: "n"(N) : "memory"); }
__device__ __forceinline__ uint64_t make_desc(uint32_t addr, uint32_t lbo_bytes, uint32_t sbo_bytes, uint32_t layout) {
    return (uint64_t)((addr & 0x3FFFF) >> 4) | ((uint64_t)(lbo_bytes >> 4) << 16) | ((uint64_t)(sbo_bytes >> 4) << 32) | ((uint64_t)layout << 62);
}
template <int R> __device__ __forceinline__ void reg_alloc() { asm volatile("setmaxnreg.inc.sync.aligned.u32 %0;" :: "n"(R)); }
template <int R> __device__ __forceinline__ void reg_dealloc() { asm volatile("setmaxnreg.dec.sync.aligned.u32 %0;" :: "n"(R)); }
__device__ __forceinline__ void pdl_launch() { asm volatile("griddepcontrol.launch_dependents;" ::: "memory"); }
__device__ __forceinline__ void pdl_wait() { asm volatile("griddepcontrol.wait;" ::: "memory"); }
__device__ __forceinline__ void prefetch_map(const CUtensorMap* m) { asm volatile("prefetch.tensormap [%0];" :: "l"(m) : "memory"); }
__device__ __forceinline__ void named_bar(int id, int n) { asm volatile("bar.sync %0, %1;" :: "r"(id), "r"(n) : "memory"); }

__device__ __forceinline__ void wgmma_m64n256k16_ss(float (&d)[128], uint64_t descA, uint64_t descB, int scaleD) {
    asm volatile("{\n.reg .pred p;\nsetp.ne.b32 p, %130, 0;\n"
        "wgmma.mma_async.sync.aligned.m64n256k16.f32.bf16.bf16 {%0, %1, %2, %3, %4, %5, %6, %7, %8, %9, %10, %11, %12, %13, %14, %15, %16, %17, %18, %19, %20, %21, %22, %23, %24, %25, %26, %27, %28, %29, %30, %31, %32, %33, %34, %35, %36, %37, %38, %39, %40, %41, %42, %43, %44, %45, %46, %47, %48, %49, %50, %51, %52, %53, %54, %55, %56, %57, %58, %59, %60, %61, %62, %63, %64, %65, %66, %67, %68, %69, %70, %71, %72, %73, %74, %75, %76, %77, %78, %79, %80, %81, %82, %83, %84, %85, %86, %87, %88, %89, %90, %91, %92, %93, %94, %95, %96, %97, %98, %99, %100, %101, %102, %103, %104, %105, %106, %107, %108, %109, %110, %111, %112, %113, %114, %115, %116, %117, %118, %119, %120, %121, %122, %123, %124, %125, %126, %127}, %128, %129, p, 1, 1, 1, 1;\n}\n"
        : "+f"(d[0]), "+f"(d[1]), "+f"(d[2]), "+f"(d[3]), "+f"(d[4]), "+f"(d[5]), "+f"(d[6]), "+f"(d[7]), "+f"(d[8]), "+f"(d[9]), "+f"(d[10]), "+f"(d[11]), "+f"(d[12]), "+f"(d[13]), "+f"(d[14]), "+f"(d[15]), "+f"(d[16]), "+f"(d[17]), "+f"(d[18]), "+f"(d[19]), "+f"(d[20]), "+f"(d[21]), "+f"(d[22]), "+f"(d[23]), "+f"(d[24]), "+f"(d[25]), "+f"(d[26]), "+f"(d[27]), "+f"(d[28]), "+f"(d[29]), "+f"(d[30]), "+f"(d[31]), "+f"(d[32]), "+f"(d[33]), "+f"(d[34]), "+f"(d[35]), "+f"(d[36]), "+f"(d[37]), "+f"(d[38]), "+f"(d[39]), "+f"(d[40]), "+f"(d[41]), "+f"(d[42]), "+f"(d[43]), "+f"(d[44]), "+f"(d[45]), "+f"(d[46]), "+f"(d[47]), "+f"(d[48]), "+f"(d[49]), "+f"(d[50]), "+f"(d[51]), "+f"(d[52]), "+f"(d[53]), "+f"(d[54]), "+f"(d[55]), "+f"(d[56]), "+f"(d[57]), "+f"(d[58]), "+f"(d[59]), "+f"(d[60]), "+f"(d[61]), "+f"(d[62]), "+f"(d[63]), "+f"(d[64]), "+f"(d[65]), "+f"(d[66]), "+f"(d[67]), "+f"(d[68]), "+f"(d[69]), "+f"(d[70]), "+f"(d[71]), "+f"(d[72]), "+f"(d[73]), "+f"(d[74]), "+f"(d[75]), "+f"(d[76]), "+f"(d[77]), "+f"(d[78]), "+f"(d[79]), "+f"(d[80]), "+f"(d[81]), "+f"(d[82]), "+f"(d[83]), "+f"(d[84]), "+f"(d[85]), "+f"(d[86]), "+f"(d[87]), "+f"(d[88]), "+f"(d[89]), "+f"(d[90]), "+f"(d[91]), "+f"(d[92]), "+f"(d[93]), "+f"(d[94]), "+f"(d[95]), "+f"(d[96]), "+f"(d[97]), "+f"(d[98]), "+f"(d[99]), "+f"(d[100]), "+f"(d[101]), "+f"(d[102]), "+f"(d[103]), "+f"(d[104]), "+f"(d[105]), "+f"(d[106]), "+f"(d[107]), "+f"(d[108]), "+f"(d[109]), "+f"(d[110]), "+f"(d[111]), "+f"(d[112]), "+f"(d[113]), "+f"(d[114]), "+f"(d[115]), "+f"(d[116]), "+f"(d[117]), "+f"(d[118]), "+f"(d[119]), "+f"(d[120]), "+f"(d[121]), "+f"(d[122]), "+f"(d[123]), "+f"(d[124]), "+f"(d[125]), "+f"(d[126]), "+f"(d[127])
        : "l"(descA), "l"(descB), "r"(scaleD));
}

__device__ __forceinline__ void wgmma_m64n192k16_ss(float (&d)[96], uint64_t descA, uint64_t descB, int scaleD) {
    asm volatile("{\n.reg .pred p;\nsetp.ne.b32 p, %98, 0;\n"
        "wgmma.mma_async.sync.aligned.m64n192k16.f32.bf16.bf16 {%0, %1, %2, %3, %4, %5, %6, %7, %8, %9, %10, %11, %12, %13, %14, %15, %16, %17, %18, %19, %20, %21, %22, %23, %24, %25, %26, %27, %28, %29, %30, %31, %32, %33, %34, %35, %36, %37, %38, %39, %40, %41, %42, %43, %44, %45, %46, %47, %48, %49, %50, %51, %52, %53, %54, %55, %56, %57, %58, %59, %60, %61, %62, %63, %64, %65, %66, %67, %68, %69, %70, %71, %72, %73, %74, %75, %76, %77, %78, %79, %80, %81, %82, %83, %84, %85, %86, %87, %88, %89, %90, %91, %92, %93, %94, %95}, %96, %97, p, 1, 1, 1, 1;\n}\n"
        : "+f"(d[0]), "+f"(d[1]), "+f"(d[2]), "+f"(d[3]), "+f"(d[4]), "+f"(d[5]), "+f"(d[6]), "+f"(d[7]), "+f"(d[8]), "+f"(d[9]), "+f"(d[10]), "+f"(d[11]), "+f"(d[12]), "+f"(d[13]), "+f"(d[14]), "+f"(d[15]), "+f"(d[16]), "+f"(d[17]), "+f"(d[18]), "+f"(d[19]), "+f"(d[20]), "+f"(d[21]), "+f"(d[22]), "+f"(d[23]), "+f"(d[24]), "+f"(d[25]), "+f"(d[26]), "+f"(d[27]), "+f"(d[28]), "+f"(d[29]), "+f"(d[30]), "+f"(d[31]), "+f"(d[32]), "+f"(d[33]), "+f"(d[34]), "+f"(d[35]), "+f"(d[36]), "+f"(d[37]), "+f"(d[38]), "+f"(d[39]), "+f"(d[40]), "+f"(d[41]), "+f"(d[42]), "+f"(d[43]), "+f"(d[44]), "+f"(d[45]), "+f"(d[46]), "+f"(d[47]), "+f"(d[48]), "+f"(d[49]), "+f"(d[50]), "+f"(d[51]), "+f"(d[52]), "+f"(d[53]), "+f"(d[54]), "+f"(d[55]), "+f"(d[56]), "+f"(d[57]), "+f"(d[58]), "+f"(d[59]), "+f"(d[60]), "+f"(d[61]), "+f"(d[62]), "+f"(d[63]), "+f"(d[64]), "+f"(d[65]), "+f"(d[66]), "+f"(d[67]), "+f"(d[68]), "+f"(d[69]), "+f"(d[70]), "+f"(d[71]), "+f"(d[72]), "+f"(d[73]), "+f"(d[74]), "+f"(d[75]), "+f"(d[76]), "+f"(d[77]), "+f"(d[78]), "+f"(d[79]), "+f"(d[80]), "+f"(d[81]), "+f"(d[82]), "+f"(d[83]), "+f"(d[84]), "+f"(d[85]), "+f"(d[86]), "+f"(d[87]), "+f"(d[88]), "+f"(d[89]), "+f"(d[90]), "+f"(d[91]), "+f"(d[92]), "+f"(d[93]), "+f"(d[94]), "+f"(d[95])
        : "l"(descA), "l"(descB), "r"(scaleD));
}

__device__ __forceinline__ void wgmma_m64n128k16_ss(float (&d)[64], uint64_t descA, uint64_t descB, int scaleD) {
    asm volatile("{\n.reg .pred p;\nsetp.ne.b32 p, %66, 0;\n"
        "wgmma.mma_async.sync.aligned.m64n128k16.f32.bf16.bf16 {%0, %1, %2, %3, %4, %5, %6, %7, %8, %9, %10, %11, %12, %13, %14, %15, %16, %17, %18, %19, %20, %21, %22, %23, %24, %25, %26, %27, %28, %29, %30, %31, %32, %33, %34, %35, %36, %37, %38, %39, %40, %41, %42, %43, %44, %45, %46, %47, %48, %49, %50, %51, %52, %53, %54, %55, %56, %57, %58, %59, %60, %61, %62, %63}, %64, %65, p, 1, 1, 0, 1;\n}\n"
        : "+f"(d[0]), "+f"(d[1]), "+f"(d[2]), "+f"(d[3]), "+f"(d[4]), "+f"(d[5]), "+f"(d[6]), "+f"(d[7]), "+f"(d[8]), "+f"(d[9]), "+f"(d[10]), "+f"(d[11]), "+f"(d[12]), "+f"(d[13]), "+f"(d[14]), "+f"(d[15]), "+f"(d[16]), "+f"(d[17]), "+f"(d[18]), "+f"(d[19]), "+f"(d[20]), "+f"(d[21]), "+f"(d[22]), "+f"(d[23]), "+f"(d[24]), "+f"(d[25]), "+f"(d[26]), "+f"(d[27]), "+f"(d[28]), "+f"(d[29]), "+f"(d[30]), "+f"(d[31]), "+f"(d[32]), "+f"(d[33]), "+f"(d[34]), "+f"(d[35]), "+f"(d[36]), "+f"(d[37]), "+f"(d[38]), "+f"(d[39]), "+f"(d[40]), "+f"(d[41]), "+f"(d[42]), "+f"(d[43]), "+f"(d[44]), "+f"(d[45]), "+f"(d[46]), "+f"(d[47]), "+f"(d[48]), "+f"(d[49]), "+f"(d[50]), "+f"(d[51]), "+f"(d[52]), "+f"(d[53]), "+f"(d[54]), "+f"(d[55]), "+f"(d[56]), "+f"(d[57]), "+f"(d[58]), "+f"(d[59]), "+f"(d[60]), "+f"(d[61]), "+f"(d[62]), "+f"(d[63])
        : "l"(descA), "l"(descB), "r"(scaleD));
}

__device__ __forceinline__ void quad_transpose(uint32_t& r0, uint32_t& r1, uint32_t& r2, uint32_t& r3, int t) {
    const bool o1 = t & 1, o2 = t & 2;
    uint32_t x, y;
    x = o1 ? r0 : r1; y = __shfl_xor_sync(0xffffffffu, x, 1); if (o1) r0 = y; else r1 = y;
    x = o1 ? r2 : r3; y = __shfl_xor_sync(0xffffffffu, x, 1); if (o1) r2 = y; else r3 = y;
    x = o2 ? r0 : r2; y = __shfl_xor_sync(0xffffffffu, x, 2); if (o2) r0 = y; else r2 = y;
    x = o2 ? r1 : r3; y = __shfl_xor_sync(0xffffffffu, x, 2); if (o2) r1 = y; else r3 = y;
}

__device__ __forceinline__ float warp_sum(float s) {
#pragma unroll
    for (int o = 16; o > 0; o >>= 1) s += __shfl_xor_sync(0xffffffffu, s, o);
    return s;
}
__device__ __forceinline__ uint32_t hsub2(uint32_t a, uint32_t b) {
    __nv_bfloat162 r = __hsub2_rn(*reinterpret_cast<__nv_bfloat162*>(&a), *reinterpret_cast<__nv_bfloat162*>(&b));
    return *reinterpret_cast<uint32_t*>(&r);
}
__device__ __forceinline__ void ln_stats2(const uint32_t (&x)[2][8], float2 (&st)[2]) {
    float piv[2], s[2], ss[2];
#pragma unroll
    for (int r = 0; r < 2; r++) piv[r] = __shfl_sync(0xffffffffu, bf_lo(x[r][0]), 0);
#pragma unroll
    for (int r = 0; r < 2; r++) {
        float s0 = 0.f, s1 = 0.f, q0 = 0.f, q1 = 0.f;
#pragma unroll
        for (int i = 0; i < 8; i++) {
            const float d0 = bf_lo(x[r][i]) - piv[r], d1 = bf_hi(x[r][i]) - piv[r];
            s0 += d0; s1 += d1; q0 = fmaf(d0, d0, q0); q1 = fmaf(d1, d1, q1);
        }
        s[r] = s0 + s1; ss[r] = q0 + q1;
    }
#pragma unroll
    for (int o = 16; o > 0; o >>= 1) {
#pragma unroll
        for (int r = 0; r < 2; r++) { s[r] += __shfl_xor_sync(0xffffffffu, s[r], o); ss[r] += __shfl_xor_sync(0xffffffffu, ss[r], o); }
    }
#pragma unroll
    for (int r = 0; r < 2; r++) {
        const float md = s[r] * (1.0f / D_);
        const float var = bf16r(fmaxf(fmaf(-md, md, ss[r] * (1.0f / D_)), 0.f));
        st[r] = make_float2(bf16r(piv[r] + md), 1.0f / bf16r(sqrtf(bf16r(var + 1e-5f))));
    }
}
__device__ __forceinline__ void ln_apply(const uint32_t (&x)[8], float2 st, uint32_t (&o)[8]) {
    const uint32_t m2 = pack_bf16(st.x, st.x);
#pragma unroll
    for (int i = 0; i < 8; i++) {
        const uint32_t d = hsub2(x[i], m2);
        o[i] = pack_bf16(bf_lo(d) * st.y, bf_hi(d) * st.y);
    }
}

constexpr int K1_THREADS = 352;
constexpr int UT_PAD = 128;
constexpr int UT_LEN = UT_PAD + S_;
constexpr int KR_LEN = 2080;
constexpr int YP_LEN = S_ + (S_ / 32) * 8;

struct __align__(128) K1Smem {
    bf16 uT[4][UT_LEN];
    bf16 xT[4][S_];
    bf16 kr[4][2][KR_LEN];
    float yP[4][YP_LEN];
    alignas(128) float st[S_ + S_ / 2];
    alignas(128) uint4 wS[512][4];
    float red[8][32];
    uint64_t bar, bar2, bar3, bar4;
};

__device__ __forceinline__ void mma16816(float (&c)[4], uint32_t a0, uint32_t a1, uint32_t a2, uint32_t a3, uint32_t b0, uint32_t b1) {
    asm("mma.sync.aligned.m16n8k16.row.col.f32.bf16.bf16.f32 {%0,%1,%2,%3}, {%4,%5,%6,%7}, {%8,%9}, {%0,%1,%2,%3};"
        : "+f"(c[0]), "+f"(c[1]), "+f"(c[2]), "+f"(c[3])
        : "r"(a0), "r"(a1), "r"(a2), "r"(a3), "r"(b0), "r"(b1));
}
__device__ __forceinline__ void ldsm_x4(uint32_t& r0, uint32_t& r1, uint32_t& r2, uint32_t& r3, uint32_t addr) {
    asm volatile("ldmatrix.sync.aligned.m8n8.x4.shared.b16 {%0,%1,%2,%3}, [%4];" : "=r"(r0), "=r"(r1), "=r"(r2), "=r"(r3) : "r"(addr) : "memory");
}

__device__ __forceinline__ void conv_mma(const bf16* uTc, const bf16* krlane, float (&acc)[16][4], int lane, int half) {
    const int lrow = lane & 7, lk = (lane >> 3) & 1, lt = lane >> 4;
    const uint32_t ubase = smem_u32(uTc) + (UT_PAD + 16 * (8 * lt + lrow) + 8 * lk) * 2;
#pragma unroll 1
    for (int pp = 0; pp < 4; pp++) {
        const int p = half * 4 + pp;
        uint32_t U[16][2];
#pragma unroll
        for (int j = 0; j < 16; j += 2) ldsm_x4(U[j][0], U[j][1], U[j + 1][0], U[j + 1][1], ubase + (j * 128 - p * 16) * 2);
        const uint32_t* kp = reinterpret_cast<const uint32_t*>(krlane - 16 * p);
        const volatile uint32_t* kpv = kp;
        uint32_t a0 = kp[0], a1 = kp[-4], a2 = kp[4], a3 = kpv[0];
#pragma unroll
        for (int q = 0; q < 16; q++) {
            uint32_t b0 = 0, b1 = 0, b2 = 0, b3 = 0;
            if (q < 15) { b0 = kp[-64 * (q + 1)]; b1 = kp[-64 * (q + 1) - 4]; b2 = kp[-64 * (q + 1) + 4]; b3 = kpv[-64 * (q + 1)]; }
#pragma unroll
            for (int n = 15; n >= q; n--) mma16816(acc[n], a0, a1, a2, a3, U[n - q][0], U[n - q][1]);
            a0 = b0; a1 = b1; a2 = b2; a3 = b3;
        }
    }
}

__device__ __forceinline__ void cp_async16(uint32_t dst, const void* src) {
    asm volatile("cp.async.cg.shared.global [%0], [%1], 16;" :: "r"(dst), "l"(src) : "memory");
}

__global__ void __cluster_dims__(2, 1, 1) __launch_bounds__(K1_THREADS, 1)
conv_kernel(const bf16* __restrict__ q, const bf16* __restrict__ k, const bf16* __restrict__ v,
            const bf16* __restrict__ shift_k, const bf16* __restrict__ ssm_k, const bf16* __restrict__ ssm_D,
            const __grid_constant__ CUtensorMap mapWg, const __grid_constant__ CUtensorMap mapWu, const bf16* __restrict__ wd) {
    extern __shared__ __align__(1024) uint8_t smem_raw[];
    pdl_launch();
    K1Smem& sm = *reinterpret_cast<K1Smem*>(smem_raw);
    const int tid = threadIdx.x, lane = tid & 31, warp = tid >> 5;
    const int bid = blockIdx.x;
    const int rank = bid & 1;
    const int c0 = 8 * (bid >> 1);
    const int cown = c0 + 4 * rank;
#define TMT 0
    TM(0, 0);
    const uint32_t bar = smem_u32(&sm.bar);
    if (tid == 0) {
        mbar_init(bar, 1);
        mbar_init(bar + 8, 1);
        mbar_init(bar + 16, 1);
        mbar_init(bar + 24, 1);
        asm volatile("fence.mbarrier_init.release.cluster;" ::: "memory");
        mbar_expect_tx(bar, 1024 * 4 * 2);
        mbar_expect_tx(bar + 8, 1024 * 4 * 2);
    }
    cluster_arrive_relaxed();

    if (warp < 8) {
        const int s0 = 1024 * rank + 4 * tid;
        uint4 kk[7], vv[4], qq[4], sw[4];
#pragma unroll
        for (int i = 0; i < 4; i++) kk[3 + i] = ldg128(k + (size_t)(s0 + i) * D_ + c0);
#pragma unroll
        for (int i = 0; i < 4; i++) vv[i] = ldg128(v + (size_t)(s0 + i) * D_ + c0);
        if (lane == 0) {
#pragma unroll
            for (int i = 0; i < 3; i++) {
                const int s = s0 - 3 + i;
                kk[i] = make_uint4(0, 0, 0, 0);
                if (s >= 0) kk[i] = ldg128(k + (size_t)s * D_ + c0);
            }
        }
#pragma unroll
        for (int i = 0; i < 4; i++) sw[i] = ldg128(shift_k + (size_t)c0 * 4 + 8 * i);
        uint4 kq[4]; uint32_t nx[4];
#pragma unroll
        for (int c = 0; c < 4; c++) {
            const bf16* kr = ssm_k + (size_t)(cown + c) * S_;
            kq[c] = ldg128(kr + 8 * tid);
            nx[c] = 0u;
            if (tid < 255) nx[c] = ldg16(kr + 8 * tid + 8);
        }
        const uint32_t dval = ldg16(ssm_D + cown + (warp >> 1));
        if (tid < 64) *reinterpret_cast<uint4*>(&sm.uT[tid >> 4][(tid & 15) * 8]) = make_uint4(0, 0, 0, 0);
#pragma unroll
        for (int i = 0; i < 3; i++) {
            uint4 t;
            t.x = __shfl_up_sync(0xffffffffu, kk[4 + i].x, 1); t.y = __shfl_up_sync(0xffffffffu, kk[4 + i].y, 1);
            t.z = __shfl_up_sync(0xffffffffu, kk[4 + i].z, 1); t.w = __shfl_up_sync(0xffffffffu, kk[4 + i].w, 1);
            if (lane != 0) kk[i] = t;
        }
        uint32_t kvw[4][4];
        const uint32_t* kkw = reinterpret_cast<const uint32_t*>(kk);
        const uint32_t* vvw = reinterpret_cast<const uint32_t*>(vv);
        const uint32_t* qqw = reinterpret_cast<const uint32_t*>(qq);
#pragma unroll
        for (int i2 = 0; i2 < 4; i2++) {
            const uint32_t t0 = __byte_perm(sw[i2].x, sw[i2].z, 0x5410), t1 = __byte_perm(sw[i2].x, sw[i2].z, 0x7632);
            const uint32_t t2 = __byte_perm(sw[i2].y, sw[i2].w, 0x5410), t3 = __byte_perm(sw[i2].y, sw[i2].w, 0x7632);
#pragma unroll
            for (int r = 0; r < 4; r++) {
                uint32_t a = hmul2(kkw[(r + 0) * 4 + i2], t3);
                a = hadd2(a, hmul2(kkw[(r + 1) * 4 + i2], t2));
                a = hadd2(a, hmul2(kkw[(r + 2) * 4 + i2], t1));
                a = hadd2(a, hmul2(kkw[(r + 3) * 4 + i2], t0));
                kvw[r][i2] = hmul2(a, vvw[r * 4 + i2]);
            }
        }
        TM(0, 1);
        cluster_wait();
        const uint32_t rbar = mapa(bar, (uint32_t)(rank ^ 1));
#pragma unroll
        for (int i2 = 0; i2 < 4; i2++) {
#pragma unroll
            for (int e = 0; e < 2; e++) {
                const uint32_t sel = e ? 0x7632 : 0x5410;
                const uint32_t w0 = __byte_perm(kvw[0][i2], kvw[1][i2], sel), w1 = __byte_perm(kvw[2][i2], kvw[3][i2], sel);
                const int cc = 2 * i2 + e;
                if ((cc >> 2) == rank) *reinterpret_cast<uint2*>(&sm.uT[cc & 3][UT_PAD + s0]) = make_uint2(w0, w1);
                else st_async_v2(mapa(smem_u32(&sm.uT[cc & 3][UT_PAD + s0]), (uint32_t)(rank ^ 1)), w0, w1, rbar);
            }
        }
#pragma unroll
        for (int c = 0; c < 4; c++) {
            uint4 a, b;
            a.x = __byte_perm(kq[c].w, 0, 0x1032); a.y = __byte_perm(kq[c].z, 0, 0x1032);
            a.z = __byte_perm(kq[c].y, 0, 0x1032); a.w = __byte_perm(kq[c].x, 0, 0x1032);
            b.x = __byte_perm(nx[c], kq[c].w, 0x7610); b.y = __byte_perm(kq[c].w, kq[c].z, 0x7610);
            b.z = __byte_perm(kq[c].z, kq[c].y, 0x7610); b.w = __byte_perm(kq[c].y, kq[c].x, 0x7610);
            *reinterpret_cast<uint4*>(&sm.kr[c][0][2040 - 8 * tid]) = a;
            *reinterpret_cast<uint4*>(&sm.kr[c][1][2040 - 8 * tid]) = b;
            if (tid == 0) {
                *reinterpret_cast<uint4*>(&sm.kr[c][1][2048]) = make_uint4(kq[c].x & 0xffffu, 0, 0, 0);
            } else if (tid < 8) {
                if (tid < 4) *reinterpret_cast<uint4*>(&sm.kr[c][1][2048 + 8 * tid]) = make_uint4(0, 0, 0, 0);
                else *reinterpret_cast<uint4*>(&sm.kr[c][0][2048 + 8 * (tid - 4)]) = make_uint4(0, 0, 0, 0);
            }
        }
#pragma unroll
        for (int i = 0; i < 4; i++) qq[i] = ldg128(q + (size_t)(s0 + i) * D_ + c0);
        TM(0, 3);
        named_bar(6, 352);
        mbar_wait_cluster(bar, 0);
        TM(0, 4);

        const int ch = warp >> 1, half = warp & 1;
        const int g = lane >> 2, t = lane & 3;
        float acc[16][4];
#pragma unroll
        for (int i = 0; i < 16; i++) { acc[i][0] = acc[i][1] = acc[i][2] = acc[i][3] = 0.f; }
        const bf16* krlane = (g & 1) ? &sm.kr[ch][0][2047 - g + 2 * t] : &sm.kr[ch][1][2048 - g + 2 * t];
        conv_mma(sm.uT[ch], krlane, acc, lane, half);
        TM(0, 5);
#pragma unroll
        for (int i2 = 0; i2 < 4; i2++) {
#pragma unroll
            for (int e = 0; e < 2; e++) {
                const uint32_t sel = e ? 0x7632 : 0x5410;
                const uint32_t w0 = __byte_perm(qqw[i2], qqw[4 + i2], sel), w1 = __byte_perm(qqw[8 + i2], qqw[12 + i2], sel);
                const int cc = 2 * i2 + e;
                if ((cc >> 2) == rank) *reinterpret_cast<uint2*>(&sm.xT[cc & 3][s0]) = make_uint2(w0, w1);
                else st_async_v2(mapa(smem_u32(&sm.xT[cc & 3][s0]), (uint32_t)(rank ^ 1)), w0, w1, rbar + 8);
            }
        }
        float* yp = &sm.yP[ch][40 * t + g];
        if (half) {
#pragma unroll
            for (int n = 0; n < 16; n++) {
                yp[160 * n] = acc[n][0];
                yp[160 * n + 16] = acc[n][1];
                yp[160 * n + 8] = acc[n][2];
                yp[160 * n + 24] = acc[n][3];
            }
        }
        named_bar(1 + ch, 64);
        if (!half) {
#pragma unroll
            for (int n = 0; n < 16; n++) {
                yp[160 * n] += acc[n][0];
                yp[160 * n + 16] += acc[n][1];
                yp[160 * n + 8] += acc[n][2];
                yp[160 * n + 24] += acc[n][3];
            }
        }
        named_bar(7, 288);
        mbar_wait_cluster(bar + 8, 0);
        TM(0, 6);
        {
            const int tt = tid & 63;
            bf16* dst = g_hT + (size_t)(cown + ch) * HT_PITCH;
            const uint32_t d2 = dval * 0x10001u;
#pragma unroll
            for (int j = 0; j < 4; j++) {
                const int s = (j * 64 + tt) * 8;
                const float* src = &sm.yP[ch][s + (s >> 5) * 8];
                const float4 a = *reinterpret_cast<const float4*>(src), b = *reinterpret_cast<const float4*>(src + 4);
                const uint4 kv4 = *reinterpret_cast<const uint4*>(&sm.uT[ch][UT_PAD + s]);
                const uint4 x4 = *reinterpret_cast<const uint4*>(&sm.xT[ch][s]);
                const uint32_t y2[4] = {hadd2(pack_bf16(a.x, a.y), hmul2(kv4.x, d2)), hadd2(pack_bf16(a.z, a.w), hmul2(kv4.y, d2)),
                                        hadd2(pack_bf16(b.x, b.y), hmul2(kv4.z, d2)), hadd2(pack_bf16(b.z, b.w), hmul2(kv4.w, d2))};
                const uint32_t xw[4] = {x4.x, x4.y, x4.z, x4.w};
                const uint4 m4 = *reinterpret_cast<const uint4*>(&sm.st[S_ + s / 2]);
                const float4 ra = *reinterpret_cast<const float4*>(&sm.st[s]), rb4 = *reinterpret_cast<const float4*>(&sm.st[s + 4]);
                const uint32_t mw[4] = {m4.x, m4.y, m4.z, m4.w};
                const float rw[8] = {ra.x, ra.y, ra.z, ra.w, rb4.x, rb4.y, rb4.z, rb4.w};
                uint32_t o[4];
#pragma unroll
                for (int i = 0; i < 4; i++) {
                    const uint32_t d = hsub2(xw[i], mw[i]);
                    const uint32_t qn = pack_bf16(bf_lo(d) * rw[2 * i], bf_hi(d) * rw[2 * i + 1]);
                    o[i] = hadd2(xw[i], hmul2(qn, y2[i]));
                }
                *reinterpret_cast<uint4*>(dst + s) = make_uint4(o[0], o[1], o[2], o[3]);
            }
        }
        TM(0, 7);
    } else {
        cluster_wait();
        named_bar(6, 352);
        const uint32_t hbar = bar + 16;
        if (warp < 10) {
            {
                const int rr = 8 * (warp - 8);
                uint32_t xq[4][2][8];
#pragma unroll
                for (int r = 0; r < 8; r++) {
                    const uint4 qa = ldg128(q + (size_t)(16 * bid + rr + r) * D_ + 8 * lane);
                    const uint4 qb = ldg128(q + (size_t)(16 * bid + rr + r) * D_ + 8 * (lane + 32));
                    uint32_t* x = xq[r >> 1][r & 1];
                    x[0] = qa.x; x[1] = qa.y; x[2] = qa.z; x[3] = qa.w; x[4] = qb.x; x[5] = qb.y; x[6] = qb.z; x[7] = qb.w;
                }
#pragma unroll
                for (int r2 = 0; r2 < 4; r2++) {
                    float2 sa[2];
                    ln_stats2(xq[r2], sa);
                    if (lane == 0) {
                        *reinterpret_cast<float2*>(&g_st1[16 * bid + rr + 2 * r2]) = make_float2(sa[0].y, sa[1].y);
                        reinterpret_cast<uint32_t*>(&g_st1[S_])[(16 * bid + rr) / 2 + r2] = pack_bf16(sa[0].x, sa[1].x);
                    }
                }
            }
            if (lane == 0) { __threadfence(); atomicAdd(&g_cnt, 1u); }
            if (warp == 9) return;
            if (lane == 0) {
                unsigned int c; int spins = 0;
                while (true) {
                    asm volatile("ld.acquire.gpu.global.u32 %0, [%1];" : "=r"(c) : "l"(&g_cnt) : "memory");
                    if (c >= 2 * gridDim.x || ++spins > (1 << 22)) break;
                    __nanosleep(200);
                }
                asm volatile("fence.proxy.async;" ::: "memory");
                mbar_expect_tx(hbar + 8, 12288);
                asm volatile("cp.async.bulk.shared::cluster.global.mbarrier::complete_tx::bytes [%0], [%1], %2, [%3];"
                    :: "r"(smem_u32(&sm.st[0])), "l"(&g_st1[0]), "r"(12288), "r"(hbar + 8) : "memory");
            }
            mbar_wait(hbar + 8, 0);
            named_bar(7, 288);
        } else {
            if (lane == 0) asm volatile("cp.async.bulk.prefetch.L2.global [%0], %1;" :: "l"(wd + (size_t)bid * 7168), "r"(14336) : "memory");
            if (bid < 112) {
                if (lane == 0) {
                    mbar_expect_tx(hbar, 32768);
                    const CUtensorMap* mw = (bid < 56) ? &mapWg : &mapWu;
                    const int col = 32 * ((bid < 56) ? bid : bid - 56);
                    tma_load_2d(smem_u32(&sm.wS[0][0]), mw, hbar, col, 0);
                    tma_load_2d(smem_u32(&sm.wS[256][0]), mw, hbar, col, 256);
                }
                mbar_wait(hbar, 0);
                const int cq = lane & 3, rgp = lane >> 2;
                float cs[8];
#pragma unroll
                for (int i = 0; i < 8; i++) cs[i] = 0.f;
#pragma unroll 4
                for (int r = 0; r < 64; r++) {
                    const uint4 w = sm.wS[r * 8 + rgp][cq];
                    cs[0] += bf_lo(w.x); cs[1] += bf_hi(w.x); cs[2] += bf_lo(w.y); cs[3] += bf_hi(w.y);
                    cs[4] += bf_lo(w.z); cs[5] += bf_hi(w.z); cs[6] += bf_lo(w.w); cs[7] += bf_hi(w.w);
                }
#pragma unroll
                for (int i = 0; i < 8; i++) {
                    cs[i] += __shfl_xor_sync(0xffffffffu, cs[i], 4);
                    cs[i] += __shfl_xor_sync(0xffffffffu, cs[i], 8);
                    cs[i] += __shfl_xor_sync(0xffffffffu, cs[i], 16);
                }
                if (lane < 4) {
                    *reinterpret_cast<float4*>(&g_colsum[32 * bid + lane * 8]) = make_float4(cs[0], cs[1], cs[2], cs[3]);
                    *reinterpret_cast<float4*>(&g_colsum[32 * bid + lane * 8 + 4]) = make_float4(cs[4], cs[5], cs[6], cs[7]);
                }
            }
        }
    }
#undef TMT
}

constexpr int G1_THREADS = 384;
constexpr int G1_STAGES = 3;
constexpr int G1_A_BYTES = 8 * 16384;
constexpr int G1_B_STAGE = 32768;
constexpr int G1_OFF_B = G1_A_BYTES;
constexpr int G1_OFF_STATS = G1_OFF_B + G1_STAGES * G1_B_STAGE;
constexpr int G1_OFF_CS = G1_OFF_STATS + 1024;
constexpr int G1_OFF_BAR = G1_OFF_CS + 1792;
constexpr int G1_SMEM = G1_OFF_BAR + 128;

__device__ __forceinline__ float tanh_fast(float x) { float t; asm("tanh.approx.f32 %0, %1;" : "=f"(t) : "f"(x)); return t; }

template <int NT>
__device__ __forceinline__ void g1_math(const float (&acc)[NT * 8], const float* cs_g, const float* cs_u, float2 st0, float2 st1, uint32_t (&P)[NT * 2], int t) {
    const float r0 = st0.y, r1 = st1.y, m0 = -st0.x * st0.y, m1 = -st1.x * st1.y;
#pragma unroll
    for (int j = 0; j < NT; j++) {
        const float2 cg = *reinterpret_cast<const float2*>(cs_g + 8 * j + 2 * t);
        const float2 cu = *reinterpret_cast<const float2*>(cs_u + 8 * j + 2 * t);
        float r[4];
#pragma unroll
        for (int e = 0; e < 4; e++) {
            const float rr = (e < 2) ? r0 : r1, mm = (e < 2) ? m0 : m1;
            const float gh = fmaf(acc[4 * j + e], 0.5f * rr, (0.5f * mm) * ((e & 1) ? cg.y : cg.x));
            const float uv = fmaf(acc[4 * (NT + j) + e], rr, mm * ((e & 1) ? cu.y : cu.x));
            r[e] = fmaf(tanh_fast(gh), 0.5f, 0.5f) * uv;
        }
        P[2 * j] = pack_bf16(r[0], r[1]);
        P[2 * j + 1] = pack_bf16(r[2], r[3]);
    }
}
template <int NT>
__device__ __forceinline__ void g1_store(uint32_t (&P)[NT * 2], bf16* out0, int t) {
#pragma unroll
    for (int j0 = 0; j0 < NT; j0 += 4) {
        quad_transpose(P[2 * j0], P[2 * j0 + 2], P[2 * j0 + 4], P[2 * j0 + 6], t);
        quad_transpose(P[2 * j0 + 1], P[2 * j0 + 3], P[2 * j0 + 5], P[2 * j0 + 7], t);
        *reinterpret_cast<uint4*>(out0 + 8 * (j0 + t)) = make_uint4(P[2 * j0], P[2 * j0 + 2], P[2 * j0 + 4], P[2 * j0 + 6]);
        *reinterpret_cast<uint4*>(out0 + 8 * F_ + 8 * (j0 + t)) = make_uint4(P[2 * j0 + 1], P[2 * j0 + 3], P[2 * j0 + 5], P[2 * j0 + 7]);
    }
}

__global__ void __cluster_dims__(2, 1, 1) __launch_bounds__(G1_THREADS, 1)
gemm1_kernel(const __grid_constant__ CUtensorMap mapA, const __grid_constant__ CUtensorMap mapG4, const __grid_constant__ CUtensorMap mapU4,
             const __grid_constant__ CUtensorMap mapG3, const __grid_constant__ CUtensorMap mapU3) {
    extern __shared__ __align__(1024) uint8_t smem_raw[];
    const uint32_t sb = smem_u32(smem_raw);
    const int tid = threadIdx.x, lane = tid & 31, warp = tid >> 5, wgi = tid >> 7;
    const int rank = blockIdx.x & 1;
    const int cb = blockIdx.x & 7, rb = blockIdx.x >> 3;
#define TMT 128
    TM(2, 0);
    pdl_launch();
    if (tid == 32) { prefetch_map(&mapA); prefetch_map(&mapG3); prefetch_map(&mapU3); }
    const uint32_t barA = sb + G1_OFF_BAR;
    const uint32_t barF = barA + 64;
    const uint32_t barE = barF + 8 * G1_STAGES;
    const uint32_t barS = barE + 8 * G1_STAGES;
    if (tid == 0) {
        for (int i = 0; i < 8; i++) mbar_init(barA + 8 * i, 1);
        for (int i = 0; i < G1_STAGES; i++) { mbar_init(barF + 8 * i, 1); mbar_init(barE + 8 * i, 2); }
        mbar_init(barS, 1);
        for (int i = 0; i < 8; i++) mbar_expect_tx(barA + 8 * i, 16384);
        asm volatile("fence.mbarrier_init.release.cluster;" ::: "memory");
    }
    __syncthreads();
    cluster_arrive_relaxed();

    if (wgi == 0) {
        reg_dealloc<40>();
        if (warp == 0) {
            if (lane == 0) {
                int st = 0, ph = 1;
                for (int it = 0; it < 16; it++) {
                    const int kc = it & 7;
                    mbar_wait(barE + 8 * st, ph);
                    const uint32_t dst = sb + G1_OFF_B + st * G1_B_STAGE;
                    if (it < 8) {
                        mbar_expect_tx(barF + 8 * st, 32768);
                        tma_load_3d(dst, &mapG4, barF + 8 * st, 0, kc * 64, cb * 7);
                        tma_load_3d(dst + 16384, &mapU4, barF + 8 * st, 0, kc * 64, cb * 7);
                    } else {
                        mbar_expect_tx(barF + 8 * st, 24576);
                        tma_load_3d(dst, &mapG3, barF + 8 * st, 0, kc * 64, cb * 7 + 4);
                        tma_load_3d(dst + 12288, &mapU3, barF + 8 * st, 0, kc * 64, cb * 7 + 4);
                    }
                    if (++st == G1_STAGES) { st = 0; ph ^= 1; }
                }
            }
            __syncwarp();
            cluster_wait();
        } else if (warp == 1) {
            cluster_wait();
            pdl_wait();
            if (lane < 4) {
                const int c = 2 * lane + rank;
                tma_load_3d_mc(sb + c * 16384, &mapA, barA + 8 * c, 0, c * 64, rb * 2, (uint16_t)3);
            }
            __syncwarp();
            float* cs = reinterpret_cast<float*>(smem_raw + G1_OFF_CS);
            for (int i = lane; i < 448; i += 32) cs[i] = __ldcg((i < 224) ? &g_colsum[cb * 224 + i] : &g_colsum[F_ + cb * 224 + (i - 224)]);
            __syncwarp();
            if (lane == 0) mbar_arrive(barS);
        } else {
            cluster_wait();
        }
    } else {
        reg_alloc<232>();
        cluster_wait();
        const int cw = wgi - 1;
        const int g = lane >> 2, t = lane & 3, wl = warp & 3, tl = tid & 127;
        bf16* outp = g_hh + (size_t)(rb * 128 + cw * 64 + wl * 16 + g) * F_ + cb * 224;
        const float* cs = reinterpret_cast<const float*>(smem_raw + G1_OFF_CS);
        int st = 0, ph = 0;
        float2 st0, st1;
        uint32_t P1[32];
        {
            float acc[128];
            const int kq = lane >> 3, mp = lane & 7;
            const uint8_t* sbase = smem_raw + cw * 8192 + kq * 128 + (mp & 3) * 4;
            const int mc = 2 * wl + (mp >> 2);
            float p0 = 0.f, p1 = 0.f, s0 = 0.f, s1 = 0.f, q0 = 0.f, q1 = 0.f;
#pragma unroll 1
            for (int kc = 0; kc < 8; kc++) {
                mbar_wait(barA + 8 * kc, 0);
                mbar_wait(barF + 8 * st, ph);
                if (tl == 0 && cw == 0) TR(1, kc);
                wgmma_fence();
                const uint32_t aaddr = sb + kc * 16384 + cw * 8192;
                const uint32_t baddr = sb + G1_OFF_B + st * G1_B_STAGE;
#pragma unroll
                for (int kk = 0; kk < 4; kk++)
                    wgmma_m64n256k16_ss(acc, make_desc(aaddr + kk * 2048, 8192, 1024, 1), make_desc(baddr + kk * 1024, 4096, 512, 2), (kc | kk) != 0);
                wgmma_commit();
                if (kc == 0) {
                    const uint32_t w = *reinterpret_cast<const uint32_t*>(smem_raw + cw * 8192 + (mc << 4) + (mp & 3) * 4);
                    p0 = bf_lo(w); p1 = bf_hi(w);
                }
#pragma unroll
                for (int i = 0; i < 16; i++) {
                    const int kr = 4 * i;
                    const uint32_t w = *reinterpret_cast<const uint32_t*>(sbase + kc * 16384 + kr * 128 + ((mc ^ ((kr + kq) & 7)) << 4));
                    const float d0 = bf_lo(w) - p0, d1 = bf_hi(w) - p1;
                    s0 += d0; s1 += d1; q0 = fmaf(d0, d0, q0); q1 = fmaf(d1, d1, q1);
                }
                wgmma_wait<0>();
                if (tl == 0) mbar_arrive(barE + 8 * st);
                if (++st == G1_STAGES) { st = 0; ph ^= 1; }
            }
            TM(2, 1);
            {
#pragma unroll
                for (int o = 8; o <= 16; o <<= 1) {
                    s0 += __shfl_xor_sync(0xffffffffu, s0, o); s1 += __shfl_xor_sync(0xffffffffu, s1, o);
                    q0 += __shfl_xor_sync(0xffffffffu, q0, o); q1 += __shfl_xor_sync(0xffffffffu, q1, o);
                }
                const float md0 = s0 * (1.0f / D_), md1 = s1 * (1.0f / D_);
                const float v0 = bf16r(fmaxf(fmaf(-md0, md0, q0 * (1.0f / D_)), 0.f)), v1 = bf16r(fmaxf(fmaf(-md1, md1, q1 * (1.0f / D_)), 0.f));
                const float ma = bf16r(p0 + md0), mb = bf16r(p1 + md1);
                const float ra = 1.0f / bf16r(sqrtf(bf16r(v0 + 1e-5f))), rbb = 1.0f / bf16r(sqrtf(bf16r(v1 + 1e-5f)));
                const float mA = __shfl_sync(0xffffffffu, ma, g >> 1), mB = __shfl_sync(0xffffffffu, mb, g >> 1);
                const float rA = __shfl_sync(0xffffffffu, ra, g >> 1), rB = __shfl_sync(0xffffffffu, rbb, g >> 1);
                const float mC = __shfl_sync(0xffffffffu, ma, 4 + (g >> 1)), mD = __shfl_sync(0xffffffffu, mb, 4 + (g >> 1));
                const float rC = __shfl_sync(0xffffffffu, ra, 4 + (g >> 1)), rD = __shfl_sync(0xffffffffu, rbb, 4 + (g >> 1));
                st0 = (g & 1) ? make_float2(mB, rB) : make_float2(mA, rA);
                st1 = (g & 1) ? make_float2(mD, rD) : make_float2(mC, rC);
            }
            mbar_wait(barS, 0);
            TM(2, 5);
            g1_math<16>(acc, cs, cs + 224, st0, st1, P1, t);
            TM(2, 2);
        }
        {
            float acc[96];
#pragma unroll 1
            for (int kc = 0; kc < 8; kc++) {
                mbar_wait(barF + 8 * st, ph);
                if (tl == 0 && cw == 0) TR(1, 8 + kc);
                wgmma_fence();
                const uint32_t aaddr = sb + kc * 16384 + cw * 8192;
                const uint32_t baddr = sb + G1_OFF_B + st * G1_B_STAGE;
#pragma unroll
                for (int kk = 0; kk < 4; kk++)
                    wgmma_m64n192k16_ss(acc, make_desc(aaddr + kk * 2048, 8192, 1024, 1), make_desc(baddr + kk * 1024, 4096, 512, 2), (kc | kk) != 0);
                wgmma_commit();
                if (kc == 0) g1_store<16>(P1, outp, t);
                wgmma_wait<0>();
                if (tl == 0) mbar_arrive(barE + 8 * st);
                if (++st == G1_STAGES) { st = 0; ph ^= 1; }
            }
            TM(2, 3);
            uint32_t P2[24];
            g1_math<12>(acc, cs + 128, cs + 224 + 128, st0, st1, P2, t);
            g1_store<12>(P2, outp + 128, t);
            TM(2, 4);
        }
    }
}

constexpr int G2_THREADS = 384;
constexpr int G2_STAGES = 6;
constexpr int G2_STAGE = 32768;
constexpr int G2_OFF_X = G2_STAGES * G2_STAGE;
constexpr int G2_OFF_BAR = G2_OFF_X + 32768;
constexpr int G2_SMEM = G2_OFF_BAR + 128;
constexpr int G2_KSTEPS = 14;

__device__ __forceinline__ void ldsm_x4_t(uint32_t& r0, uint32_t& r1, uint32_t& r2, uint32_t& r3, uint32_t addr) {
    asm volatile("ldmatrix.sync.aligned.m8n8.x4.trans.shared.b16 {%0,%1,%2,%3}, [%4];" : "=r"(r0), "=r"(r1), "=r"(r2), "=r"(r3) : "r"(addr) : "memory");
}

__global__ void __cluster_dims__(2, 1, 1) __launch_bounds__(G2_THREADS, 1)
gemm2_kernel(const __grid_constant__ CUtensorMap mapHH, const __grid_constant__ CUtensorMap mapWd, const __grid_constant__ CUtensorMap mapH,
             bf16* __restrict__ out) {
    extern __shared__ __align__(1024) uint8_t smem_raw[];
    const uint32_t sb = smem_u32(smem_raw);
    const int tid = threadIdx.x, lane = tid & 31, warp = tid >> 5, wgi = tid >> 7;
    const int ks = blockIdx.x & 1, nb = (blockIdx.x >> 1) & 3, rb = blockIdx.x >> 3;
    TM(3, 0);
    if (tid == 32) { prefetch_map(&mapHH); prefetch_map(&mapH); }
    const uint32_t barF = sb + G2_OFF_BAR;
    const uint32_t barE = barF + 8 * G2_STAGES;
    const uint32_t barX = barE + 8 * G2_STAGES;
    if (tid == 0) {
        for (int i = 0; i < G2_STAGES; i++) { mbar_init(barF + 8 * i, 1); mbar_init(barE + 8 * i, 2); }
        mbar_init(barX, 1);
        asm volatile("fence.mbarrier_init.release.cluster;" ::: "memory");
        mbar_expect_tx(barX, 32768);
        for (int it = 0; it < G2_STAGES; it++) {
            mbar_expect_tx(barF + 8 * it, 32768);
            tma_load_3d(sb + it * G2_STAGE + 16384, &mapWd, barF + 8 * it, 0, ks * 896 + it * 64, nb * 2);
        }
    }
    __syncthreads();
    cluster_arrive_relaxed();

    if (wgi == 0) {
        if (tid == 0) {
            pdl_wait();
            for (int it = 0; it < G2_STAGES; it++)
                tma_load_2d(sb + it * G2_STAGE, &mapHH, barF + 8 * it, ks * 896 + it * 64, rb * 128);
            if (blockIdx.x == 0) g_cnt = 0u;
            int st = 0, ph = 0;
            for (int it = G2_STAGES; it < G2_KSTEPS; it++) {
                mbar_wait(barE + 8 * st, ph);
                const uint32_t dst = sb + st * G2_STAGE;
                const int k0 = ks * 896 + it * 64;
                mbar_expect_tx(barF + 8 * st, 32768);
                tma_load_2d(dst, &mapHH, barF + 8 * st, k0, rb * 128);
                tma_load_3d(dst + 16384, &mapWd, barF + 8 * st, 0, k0, nb * 2);
                if (++st == G2_STAGES) { st = 0; ph ^= 1; }
            }
            mbar_wait(barE + 8 * st, ph);
            mbar_expect_tx(barF + 8 * st, 16384);
            tma_load_2d(sb + st * G2_STAGE, &mapH, barF + 8 * st, rb * 128 + ks * 64, nb * 128);
        }
        __syncwarp();
        cluster_wait();
    } else {
        const int cw = wgi - 1;
        const int g = lane >> 2, t = lane & 3, wl = warp & 3;
        const int tl = tid & 127;
        int st = 0, ph = 0;
        float acc[64];
#pragma unroll 1
        for (int it = 0; it < G2_KSTEPS; it++) {
            mbar_wait(barF + 8 * st, ph);
            if (it == 0) TM(3, 1);
            wgmma_fence();
            const uint32_t aaddr = sb + st * G2_STAGE + cw * 8192;
            const uint32_t baddr = sb + st * G2_STAGE + 16384;
#pragma unroll
            for (int kk = 0; kk < 4; kk++)
                wgmma_m64n128k16_ss(acc, make_desc(aaddr + kk * 32, 16, 1024, 1), make_desc(baddr + kk * 2048, 8192, 1024, 1), (it | kk) != 0);
            wgmma_commit();
            wgmma_wait<0>();
            if (tl == 0) mbar_arrive(barE + 8 * st);
            if (++st == G2_STAGES) { st = 0; ph ^= 1; }
        }
        TM(3, 2);
        cluster_wait();
        if (cw != ks) {
            const uint32_t dst = mapa(sb + G2_OFF_X + tl * 16, (uint32_t)(ks ^ 1));
            const uint32_t rbar = mapa(barX, (uint32_t)(ks ^ 1));
#pragma unroll
            for (int i = 0; i < 16; i++) st_async_v4f(dst + i * 2048, acc[4 * i], acc[4 * i + 1], acc[4 * i + 2], acc[4 * i + 3], rbar);
        } else {
            const float4* xb = reinterpret_cast<const float4*>(smem_raw + G2_OFF_X) + tl;
            const int row0 = rb * 128 + cw * 64 + wl * 16 + g;
            bf16* o0 = out + (size_t)row0 * D_ + nb * 128;
            uint32_t ha[16], hb[16];
            mbar_wait(barF + 8 * st, ph);
            {
                const int chl = 8 * (lane >> 4) + (lane & 7), sb8 = 2 * wl + ((lane >> 3) & 1);
                const uint32_t hbase = sb + st * G2_STAGE + chl * 128 + ((sb8 ^ (lane & 7)) << 4);
#pragma unroll
                for (int j = 0; j < 16; j += 2) ldsm_x4_t(ha[j], hb[j], ha[j + 1], hb[j + 1], hbase + j * 1024);
            }
            mbar_wait_cluster(barX, 0);
            TM(3, 4);
#pragma unroll
            for (int j0 = 0; j0 < 16; j0 += 4) {
                uint32_t P0[4], P1[4];
#pragma unroll
                for (int jj = 0; jj < 4; jj++) {
                    const int j = j0 + jj;
                    const float4 x = xb[j * 128];
                    P0[jj] = hadd2(ha[j], pack_bf16(acc[4 * j] + x.x, acc[4 * j + 1] + x.y));
                    P1[jj] = hadd2(hb[j], pack_bf16(acc[4 * j + 2] + x.z, acc[4 * j + 3] + x.w));
                }
                quad_transpose(P0[0], P0[1], P0[2], P0[3], t);
                quad_transpose(P1[0], P1[1], P1[2], P1[3], t);
                *reinterpret_cast<uint4*>(o0 + 8 * (j0 + t)) = make_uint4(P0[0], P0[1], P0[2], P0[3]);
                *reinterpret_cast<uint4*>(o0 + 8 * D_ + 8 * (j0 + t)) = make_uint4(P1[0], P1[1], P1[2], P1[3]);
            }
        }
        TM(3, 5);
    }
#undef TMT
}

typedef CUresult (*EncodeFn)(CUtensorMap*, CUtensorMapDataType, cuuint32_t, void*, const cuuint64_t*, const cuuint64_t*,
                             const cuuint32_t*, const cuuint32_t*, CUtensorMapInterleave, CUtensorMapSwizzle,
                             CUtensorMapL2promotion, CUtensorMapFloatOOBfill);

static void enc2d(EncodeFn enc, CUtensorMap* m, const void* p, int rows, int cols, int brows, int bcols, int pitch = 0) {
    cuuint64_t dims[2] = {(cuuint64_t)cols, (cuuint64_t)rows};
    cuuint64_t strides[1] = {(cuuint64_t)(pitch ? pitch : cols) * 2};
    cuuint32_t box[2] = {(cuuint32_t)bcols, (cuuint32_t)brows};
    cuuint32_t es[2] = {1, 1};
    enc(m, CU_TENSOR_MAP_DATA_TYPE_BFLOAT16, 2, const_cast<void*>(p), dims, strides, box, es, CU_TENSOR_MAP_INTERLEAVE_NONE,
        bcols == 32 ? CU_TENSOR_MAP_SWIZZLE_64B : CU_TENSOR_MAP_SWIZZLE_128B, CU_TENSOR_MAP_L2_PROMOTION_L2_128B, CU_TENSOR_MAP_FLOAT_OOB_FILL_NONE);
}
static void enc2d_plain(EncodeFn enc, CUtensorMap* m, const void* p, int rows, int cols, int brows, int bcols) {
    cuuint64_t dims[2] = {(cuuint64_t)cols, (cuuint64_t)rows};
    cuuint64_t strides[1] = {(cuuint64_t)cols * 2};
    cuuint32_t box[2] = {(cuuint32_t)bcols, (cuuint32_t)brows};
    cuuint32_t es[2] = {1, 1};
    enc(m, CU_TENSOR_MAP_DATA_TYPE_BFLOAT16, 2, const_cast<void*>(p), dims, strides, box, es, CU_TENSOR_MAP_INTERLEAVE_NONE,
        CU_TENSOR_MAP_SWIZZLE_NONE, CU_TENSOR_MAP_L2_PROMOTION_L2_128B, CU_TENSOR_MAP_FLOAT_OOB_FILL_NONE);
}
static void enc3d(EncodeFn enc, CUtensorMap* m, const void* p, int rows, int cols, int atom, int brows, int natoms, int pitch = 0) {
    cuuint64_t dims[3] = {(cuuint64_t)atom, (cuuint64_t)rows, (cuuint64_t)(cols / atom)};
    cuuint64_t strides[2] = {(cuuint64_t)(pitch ? pitch : cols) * 2, (cuuint64_t)atom * 2};
    cuuint32_t box[3] = {(cuuint32_t)atom, (cuuint32_t)brows, (cuuint32_t)natoms};
    cuuint32_t es[3] = {1, 1, 1};
    enc(m, CU_TENSOR_MAP_DATA_TYPE_BFLOAT16, 3, const_cast<void*>(p), dims, strides, box, es, CU_TENSOR_MAP_INTERLEAVE_NONE,
        atom == 32 ? CU_TENSOR_MAP_SWIZZLE_64B : CU_TENSOR_MAP_SWIZZLE_128B, CU_TENSOR_MAP_L2_PROMOTION_L2_128B, CU_TENSOR_MAP_FLOAT_OOB_FILL_NONE);
}

extern "C" void kernel_launch(void* const* d_in, const int* in_sizes, int n_in, void* d_out, int out_size) {
    const bf16* q = (const bf16*)d_in[0];
    const bf16* k = (const bf16*)d_in[1];
    const bf16* v = (const bf16*)d_in[2];
    const bf16* shift_k = (const bf16*)d_in[3];
    const bf16* ssm_k = (const bf16*)d_in[4];
    const bf16* ssm_D = (const bf16*)d_in[5];
    const bf16* wg = (const bf16*)d_in[7];
    const bf16* wu = (const bf16*)d_in[8];
    const bf16* wd = (const bf16*)d_in[9];
    bf16* out = (bf16*)d_out;

    static EncodeFn enc = nullptr;
    static void *p_hT = nullptr, *p_hh = nullptr;
    if (!enc) {
        void* fn = nullptr; cudaDriverEntryPointQueryResult qr;
        cudaGetDriverEntryPoint("cuTensorMapEncodeTiled", &fn, cudaEnableDefault, &qr);
        enc = (EncodeFn)fn;
        cudaGetSymbolAddress(&p_hT, g_hT);
        cudaGetSymbolAddress(&p_hh, g_hh);
        cudaFuncSetAttribute(conv_kernel, cudaFuncAttributeMaxDynamicSharedMemorySize, (int)sizeof(K1Smem));
        cudaFuncSetAttribute(gemm1_kernel, cudaFuncAttributeMaxDynamicSharedMemorySize, G1_SMEM);
        cudaFuncSetAttribute(gemm2_kernel, cudaFuncAttributeMaxDynamicSharedMemorySize, G2_SMEM);
    }
    CUtensorMap mA, mG64, mU64, mG32, mU32, mHH, mWd, mH, mWgp, mWup;
    enc2d_plain(enc, &mWgp, wg, D_, F_, 256, 32);
    enc2d_plain(enc, &mWup, wu, D_, F_, 256, 32);
    enc3d(enc, &mA, p_hT, D_, S_, 64, 64, 2, HT_PITCH);
    enc2d(enc, &mH, p_hT, D_, S_, 128, 64, HT_PITCH);
    enc3d(enc, &mG64, wg, D_, F_, 32, 64, 4);
    enc3d(enc, &mU64, wu, D_, F_, 32, 64, 4);
    enc3d(enc, &mG32, wg, D_, F_, 32, 64, 3);
    enc3d(enc, &mU32, wu, D_, F_, 32, 64, 3);
    enc2d(enc, &mHH, p_hh, S_, F_, 128, 64);
    enc3d(enc, &mWd, wd, F_, D_, 64, 64, 2);

    cudaStream_t st = cudaStreamPerThread;
    cudaLaunchAttribute at[1];
    at[0].id = cudaLaunchAttributeProgrammaticStreamSerialization;
    at[0].val.programmaticStreamSerializationAllowed = 1;
    cudaLaunchConfig_t cfg = {};
    cfg.stream = st; cfg.attrs = at; cfg.numAttrs = 1;
    conv_kernel<<<128, K1_THREADS, sizeof(K1Smem), st>>>(q, k, v, shift_k, ssm_k, ssm_D, mWgp, mWup, wd);
    cfg.gridDim = dim3(128); cfg.blockDim = dim3(G1_THREADS); cfg.dynamicSmemBytes = G1_SMEM;
    cudaLaunchKernelEx(&cfg, gemm1_kernel, mA, mG64, mU64, mG32, mU32);
    cfg.gridDim = dim3(128); cfg.blockDim = dim3(G2_THREADS); cfg.dynamicSmemBytes = G2_SMEM;
    cudaLaunchKernelEx(&cfg, gemm2_kernel, mHH, mWd, mH, out);
}
```

```cpp
#include <cuda_runtime.h>
#include <cuda_bf16.h>
#include <cuda.h>
#include <stdint.h>

typedef __nv_bfloat16 bf16;
constexpr int S_ = 2048, D_ = 512, F_ = 1792;

constexpr int HT_PITCH = S_ + 64;
__device__ __align__(128) bf16 g_hT[D_ * HT_PITCH];
__device__ bf16 g_hh[S_ * F_];
__device__ __align__(128) float g_st1[S_ + S_ / 2];
__device__ float g_colsum[2 * F_];
__device__ unsigned int g_cnt;

#define TM(k, i)
#define TR(k, i)
__device__ __forceinline__ uint32_t smem_u32(const void* p) { return (uint32_t)__cvta_generic_to_shared(p); }
__device__ __forceinline__ float bf16r(float x) { return __bfloat162float(__float2bfloat16_rn(x)); }
__device__ __forceinline__ float bf_lo(uint32_t w) { return __uint_as_float(w << 16); }
__device__ __forceinline__ float bf_hi(uint32_t w) { return __uint_as_float(w & 0xffff0000u); }
__device__ __forceinline__ uint32_t pack_bf16(float lo, float hi) {
    __nv_bfloat162 v = __floats2bfloat162_rn(lo, hi);
    return *reinterpret_cast<uint32_t*>(&v);
}
__device__ __forceinline__ uint32_t hmul2(uint32_t a, uint32_t b) {
    __nv_bfloat162 r = __hmul2_rn(*reinterpret_cast<__nv_bfloat162*>(&a), *reinterpret_cast<__nv_bfloat162*>(&b));
    return *reinterpret_cast<uint32_t*>(&r);
}
__device__ __forceinline__ uint32_t hadd2(uint32_t a, uint32_t b) {
    __nv_bfloat162 r = __hadd2_rn(*reinterpret_cast<__nv_bfloat162*>(&a), *reinterpret_cast<__nv_bfloat162*>(&b));
    return *reinterpret_cast<uint32_t*>(&r);
}
__device__ __forceinline__ uint4 ldg128(const void* p) {
    uint4 r; asm volatile("ld.global.nc.v4.u32 {%0,%1,%2,%3}, [%4];" : "=r"(r.x), "=r"(r.y), "=r"(r.z), "=r"(r.w) : "l"(p)); return r;
}
__device__ __forceinline__ uint4 ldcg128(const void* p) {
    uint4 r; asm volatile("ld.global.cg.v4.u32 {%0,%1,%2,%3}, [%4];" : "=r"(r.x), "=r"(r.y), "=r"(r.z), "=r"(r.w) : "l"(p)); return r;
}
__device__ __forceinline__ uint32_t ldg16(const void* p) {
    unsigned short r; asm volatile("ld.global.nc.u16 %0, [%1];" : "=h"(r) : "l"(p)); return (uint32_t)r;
}
__device__ __forceinline__ void mbar_init(uint32_t bar, int cnt) { asm volatile("mbarrier.init.shared::cta.b64 [%0], %1;" :: "r"(bar), "r"(cnt)); }
__device__ __forceinline__ void mbar_expect_tx(uint32_t bar, uint32_t bytes) { asm volatile("mbarrier.arrive.expect_tx.shared::cta.b64 _, [%0], %1;" :: "r"(bar), "r"(bytes) : "memory"); }
__device__ __forceinline__ void mbar_arrive(uint32_t bar) { asm volatile("mbarrier.arrive.shared::cta.b64 _, [%0];" :: "r"(bar) : "memory"); }
__device__ __forceinline__ void mbar_arrive_cluster(uint32_t bar, uint32_t cta) {
    asm volatile("{\n.reg .b32 ra;\nmapa.shared::cluster.u32 ra, %0, %1;\nmbarrier.arrive.shared::cluster.b64 _, [ra];\n}" :: "r"(bar), "r"(cta) : "memory");
}
__device__ __forceinline__ void mbar_wait(uint32_t bar, uint32_t parity) {
    asm volatile("{\n.reg .pred P1;\nLAB_WAIT:\nmbarrier.try_wait.parity.shared::cta.b64 P1, [%0], %1;\n@P1 bra DONE;\nbra LAB_WAIT;\nDONE:\n}" :: "r"(bar), "r"(parity) : "memory");
}
__device__ __forceinline__ void mbar_wait_cluster(uint32_t bar, uint32_t parity) {
    asm volatile("{\n.reg .pred P1;\nLAB_WAIT:\nmbarrier.try_wait.parity.acquire.cluster.shared::cta.b64 P1, [%0], %1;\n@P1 bra DONE;\nbra LAB_WAIT;\nDONE:\n}" :: "r"(bar), "r"(parity) : "memory");
}
__device__ __forceinline__ void tma_load_2d(uint32_t dst, const CUtensorMap* map, uint32_t bar, int c0, int c1) {
    asm volatile("cp.async.bulk.tensor.2d.shared::cluster.global.mbarrier::complete_tx::bytes [%0], [%1, {%3, %4}], [%2];"
        :: "r"(dst), "l"(map), "r"(bar), "r"(c0), "r"(c1) : "memory");
}
__device__ __forceinline__ void tma_load_2d_mc(uint32_t dst, const CUtensorMap* map, uint32_t bar, int c0, int c1, uint16_t mask) {
    asm volatile("cp.async.bulk.tensor.2d.shared::cluster.global.mbarrier::complete_tx::bytes.multicast::cluster [%0], [%1, {%3, %4}], [%2], %5;"
        :: "r"(dst), "l"(map), "r"(bar), "r"(c0), "r"(c1), "h"(mask) : "memory");
}
__device__ __forceinline__ void tma_load_3d_mc(uint32_t dst, const CUtensorMap* map, uint32_t bar, int c0, int c1, int c2, uint16_t mask) {
    asm volatile("cp.async.bulk.tensor.3d.shared::cluster.global.mbarrier::complete_tx::bytes.multicast::cluster [%0], [%1, {%3, %4, %5}], [%2], %6;"
        :: "r"(dst), "l"(map), "r"(bar), "r"(c0), "r"(c1), "r"(c2), "h"(mask) : "memory");
}
__device__ __forceinline__ void tma_load_3d(uint32_t dst, const CUtensorMap* map, uint32_t bar, int c0, int c1, int c2) {
    asm volatile("cp.async.bulk.tensor.3d.shared::cluster.global.mbarrier::complete_tx::bytes [%0], [%1, {%3, %4, %5}], [%2];"
        :: "r"(dst), "l"(map), "r"(bar), "r"(c0), "r"(c1), "r"(c2) : "memory");
}
__device__ __forceinline__ void cluster_arrive() { asm volatile("barrier.cluster.arrive.aligned;" ::: "memory"); }
__device__ __forceinline__ void cluster_arrive_relaxed() { asm volatile("barrier.cluster.arrive.relaxed.aligned;" ::: "memory"); }
__device__ __forceinline__ void cluster_wait() { asm volatile("barrier.cluster.wait.aligned;" ::: "memory"); }
__device__ __forceinline__ uint32_t mapa(uint32_t addr, uint32_t cta) {
    uint32_t r; asm volatile("mapa.shared::cluster.u32 %0, %1, %2;" : "=r"(r) : "r"(addr), "r"(cta)); return r;
}
__device__ __forceinline__ void st_async_v2(uint32_t addr, uint32_t a, uint32_t b, uint32_t rbar) {
    asm volatile("st.async.weak.shared::cluster.mbarrier::complete_tx::bytes.v2.b32 [%0], {%1, %2}, [%3];" :: "r"(addr), "r"(a), "r"(b), "r"(rbar) : "memory");
}
__device__ __forceinline__ void st_async_v4f(uint32_t addr, float a, float b, float c, float d, uint32_t rbar) {
    asm volatile("st.async.weak.shared::cluster.mbarrier::complete_tx::bytes.v4.f32 [%0], {%1, %2, %3, %4}, [%5];" :: "r"(addr), "f"(a), "f"(b), "f"(c), "f"(d), "r"(rbar) : "memory");
}
__device__ __forceinline__ void wgmma_fence() { asm volatile("wgmma.fence.sync.aligned;" ::: "memory"); }
__device__ __forceinline__ void wgmma_commit() { asm volatile("wgmma.commit_group.sync.aligned;" ::: "memory"); }
template <int N> __device__ __forceinline__ void wgmma_wait() { asm volatile("wgmma.wait_group.sync.aligned %0;" :: "n"(N) : "memory"); }
__device__ __forceinline__ uint64_t make_desc(uint32_t addr, uint32_t lbo_bytes, uint32_t sbo_bytes, uint32_t layout) {
    return (uint64_t)((addr & 0x3FFFF) >> 4) | ((uint64_t)(lbo_bytes >> 4) << 16) | ((uint64_t)(sbo_bytes >> 4) << 32) | ((uint64_t)layout << 62);
}
template <int R> __device__ __forceinline__ void reg_alloc() { asm volatile("setmaxnreg.inc.sync.aligned.u32 %0;" :: "n"(R)); }
template <int R> __device__ __forceinline__ void reg_dealloc() { asm volatile("setmaxnreg.dec.sync.aligned.u32 %0;" :: "n"(R)); }
__device__ __forceinline__ void pdl_launch() { asm volatile("griddepcontrol.launch_dependents;" ::: "memory"); }
__device__ __forceinline__ void pdl_wait() { asm volatile("griddepcontrol.wait;" ::: "memory"); }
__device__ __forceinline__ void prefetch_map(const CUtensorMap* m) { asm volatile("prefetch.tensormap [%0];" :: "l"(m) : "memory"); }
__device__ __forceinline__ void named_bar(int id, int n) { asm volatile("bar.sync %0, %1;" :: "r"(id), "r"(n) : "memory"); }

__device__ __forceinline__ void wgmma_m64n256k16_ss(float (&d)[128], uint64_t descA, uint64_t descB, int scaleD) {
    asm volatile("{\n.reg .pred p;\nsetp.ne.b32 p, %130, 0;\n"
        "wgmma.mma_async.sync.aligned.m64n256k16.f32.bf16.bf16 {%0, %1, %2, %3, %4, %5, %6, %7, %8, %9, %10, %11, %12, %13, %14, %15, %16, %17, %18, %19, %20, %21, %22, %23, %24, %25, %26, %27, %28, %29, %30, %31, %32, %33, %34, %35, %36, %37, %38, %39, %40, %41, %42, %43, %44, %45, %46, %47, %48, %49, %50, %51, %52, %53, %54, %55, %56, %57, %58, %59, %60, %61, %62, %63, %64, %65, %66, %67, %68, %69, %70, %71, %72, %73, %74, %75, %76, %77, %78, %79, %80, %81, %82, %83, %84, %85, %86, %87, %88, %89, %90, %91, %92, %93, %94, %95, %96, %97, %98, %99, %100, %101, %102, %103, %104, %105, %106, %107, %108, %109, %110, %111, %112, %113, %114, %115, %116, %117, %118, %119, %120, %121, %122, %123, %124, %125, %126, %127}, %128, %129, p, 1, 1, 1, 1;\n}\n"
        : "+f"(d[0]), "+f"(d[1]), "+f"(d[2]), "+f"(d[3]), "+f"(d[4]), "+f"(d[5]), "+f"(d[6]), "+f"(d[7]), "+f"(d[8]), "+f"(d[9]), "+f"(d[10]), "+f"(d[11]), "+f"(d[12]), "+f"(d[13]), "+f"(d[14]), "+f"(d[15]), "+f"(d[16]), "+f"(d[17]), "+f"(d[18]), "+f"(d[19]), "+f"(d[20]), "+f"(d[21]), "+f"(d[22]), "+f"(d[23]), "+f"(d[24]), "+f"(d[25]), "+f"(d[26]), "+f"(d[27]), "+f"(d[28]), "+f"(d[29]), "+f"(d[30]), "+f"(d[31]), "+f"(d[32]), "+f"(d[33]), "+f"(d[34]), "+f"(d[35]), "+f"(d[36]), "+f"(d[37]), "+f"(d[38]), "+f"(d[39]), "+f"(d[40]), "+f"(d[41]), "+f"(d[42]), "+f"(d[43]), "+f"(d[44]), "+f"(d[45]), "+f"(d[46]), "+f"(d[47]), "+f"(d[48]), "+f"(d[49]), "+f"(d[50]), "+f"(d[51]), "+f"(d[52]), "+f"(d[53]), "+f"(d[54]), "+f"(d[55]), "+f"(d[56]), "+f"(d[57]), "+f"(d[58]), "+f"(d[59]), "+f"(d[60]), "+f"(d[61]), "+f"(d[62]), "+f"(d[63]), "+f"(d[64]), "+f"(d[65]), "+f"(d[66]), "+f"(d[67]), "+f"(d[68]), "+f"(d[69]), "+f"(d[70]), "+f"(d[71]), "+f"(d[72]), "+f"(d[73]), "+f"(d[74]), "+f"(d[75]), "+f"(d[76]), "+f"(d[77]), "+f"(d[78]), "+f"(d[79]), "+f"(d[80]), "+f"(d[81]), "+f"(d[82]), "+f"(d[83]), "+f"(d[84]), "+f"(d[85]), "+f"(d[86]), "+f"(d[87]), "+f"(d[88]), "+f"(d[89]), "+f"(d[90]), "+f"(d[91]), "+f"(d[92]), "+f"(d[93]), "+f"(d[94]), "+f"(d[95]), "+f"(d[96]), "+f"(d[97]), "+f"(d[98]), "+f"(d[99]), "+f"(d[100]), "+f"(d[101]), "+f"(d[102]), "+f"(d[103]), "+f"(d[104]), "+f"(d[105]), "+f"(d[106]), "+f"(d[107]), "+f"(d[108]), "+f"(d[109]), "+f"(d[110]), "+f"(d[111]), "+f"(d[112]), "+f"(d[113]), "+f"(d[114]), "+f"(d[115]), "+f"(d[116]), "+f"(d[117]), "+f"(d[118]), "+f"(d[119]), "+f"(d[120]), "+f"(d[121]), "+f"(d[122]), "+f"(d[123]), "+f"(d[124]), "+f"(d[125]), "+f"(d[126]), "+f"(d[127])
        : "l"(descA), "l"(descB), "r"(scaleD));
}

__device__ __forceinline__ void wgmma_m64n192k16_ss(float (&d)[96], uint64_t descA, uint64_t descB, int scaleD) {
    asm volatile("{\n.reg .pred p;\nsetp.ne.b32 p, %98, 0;\n"
        "wgmma.mma_async.sync.aligned.m64n192k16.f32.bf16.bf16 {%0, %1, %2, %3, %4, %5, %6, %7, %8, %9, %10, %11, %12, %13, %14, %15, %16, %17, %18, %19, %20, %21, %22, %23, %24, %25, %26, %27, %28, %29, %30, %31, %32, %33, %34, %35, %36, %37, %38, %39, %40, %41, %42, %43, %44, %45, %46, %47, %48, %49, %50, %51, %52, %53, %54, %55, %56, %57, %58, %59, %60, %61, %62, %63, %64, %65, %66, %67, %68, %69, %70, %71, %72, %73, %74, %75, %76, %77, %78, %79, %80, %81, %82, %83, %84, %85, %86, %87, %88, %89, %90, %91, %92, %93, %94, %95}, %96, %97, p, 1, 1, 1, 1;\n}\n"
        : "+f"(d[0]), "+f"(d[1]), "+f"(d[2]), "+f"(d[3]), "+f"(d[4]), "+f"(d[5]), "+f"(d[6]), "+f"(d[7]), "+f"(d[8]), "+f"(d[9]), "+f"(d[10]), "+f"(d[11]), "+f"(d[12]), "+f"(d[13]), "+f"(d[14]), "+f"(d[15]), "+f"(d[16]), "+f"(d[17]), "+f"(d[18]), "+f"(d[19]), "+f"(d[20]), "+f"(d[21]), "+f"(d[22]), "+f"(d[23]), "+f"(d[24]), "+f"(d[25]), "+f"(d[26]), "+f"(d[27]), "+f"(d[28]), "+f"(d[29]), "+f"(d[30]), "+f"(d[31]), "+f"(d[32]), "+f"(d[33]), "+f"(d[34]), "+f"(d[35]), "+f"(d[36]), "+f"(d[37]), "+f"(d[38]), "+f"(d[39]), "+f"(d[40]), "+f"(d[41]), "+f"(d[42]), "+f"(d[43]), "+f"(d[44]), "+f"(d[45]), "+f"(d[46]), "+f"(d[47]), "+f"(d[48]), "+f"(d[49]), "+f"(d[50]), "+f"(d[51]), "+f"(d[52]), "+f"(d[53]), "+f"(d[54]), "+f"(d[55]), "+f"(d[56]), "+f"(d[57]), "+f"(d[58]), "+f"(d[59]), "+f"(d[60]), "+f"(d[61]), "+f"(d[62]), "+f"(d[63]), "+f"(d[64]), "+f"(d[65]), "+f"(d[66]), "+f"(d[67]), "+f"(d[68]), "+f"(d[69]), "+f"(d[70]), "+f"(d[71]), "+f"(d[72]), "+f"(d[73]), "+f"(d[74]), "+f"(d[75]), "+f"(d[76]), "+f"(d[77]), "+f"(d[78]), "+f"(d[79]), "+f"(d[80]), "+f"(d[81]), "+f"(d[82]), "+f"(d[83]), "+f"(d[84]), "+f"(d[85]), "+f"(d[86]), "+f"(d[87]), "+f"(d[88]), "+f"(d[89]), "+f"(d[90]), "+f"(d[91]), "+f"(d[92]), "+f"(d[93]), "+f"(d[94]), "+f"(d[95])
        : "l"(descA), "l"(descB), "r"(scaleD));
}

__device__ __forceinline__ void wgmma_m64n128k16_ss(float (&d)[64], uint64_t descA, uint64_t descB, int scaleD) {
    asm volatile("{\n.reg .pred p;\nsetp.ne.b32 p, %66, 0;\n"
        "wgmma.mma_async.sync.aligned.m64n128k16.f32.bf16.bf16 {%0, %1, %2, %3, %4, %5, %6, %7, %8, %9, %10, %11, %12, %13, %14, %15, %16, %17, %18, %19, %20, %21, %22, %23, %24, %25, %26, %27, %28, %29, %30, %31, %32, %33, %34, %35, %36, %37, %38, %39, %40, %41, %42, %43, %44, %45, %46, %47, %48, %49, %50, %51, %52, %53, %54, %55, %56, %57, %58, %59, %60, %61, %62, %63}, %64, %65, p, 1, 1, 0, 1;\n}\n"
        : "+f"(d[0]), "+f"(d[1]), "+f"(d[2]), "+f"(d[3]), "+f"(d[4]), "+f"(d[5]), "+f"(d[6]), "+f"(d[7]), "+f"(d[8]), "+f"(d[9]), "+f"(d[10]), "+f"(d[11]), "+f"(d[12]), "+f"(d[13]), "+f"(d[14]), "+f"(d[15]), "+f"(d[16]), "+f"(d[17]), "+f"(d[18]), "+f"(d[19]), "+f"(d[20]), "+f"(d[21]), "+f"(d[22]), "+f"(d[23]), "+f"(d[24]), "+f"(d[25]), "+f"(d[26]), "+f"(d[27]), "+f"(d[28]), "+f"(d[29]), "+f"(d[30]), "+f"(d[31]), "+f"(d[32]), "+f"(d[33]), "+f"(d[34]), "+f"(d[35]), "+f"(d[36]), "+f"(d[37]), "+f"(d[38]), "+f"(d[39]), "+f"(d[40]), "+f"(d[41]), "+f"(d[42]), "+f"(d[43]), "+f"(d[44]), "+f"(d[45]), "+f"(d[46]), "+f"(d[47]), "+f"(d[48]), "+f"(d[49]), "+f"(d[50]), "+f"(d[51]), "+f"(d[52]), "+f"(d[53]), "+f"(d[54]), "+f"(d[55]), "+f"(d[56]), "+f"(d[57]), "+f"(d[58]), "+f"(d[59]), "+f"(d[60]), "+f"(d[61]), "+f"(d[62]), "+f"(d[63])
        : "l"(descA), "l"(descB), "r"(scaleD));
}

__device__ __forceinline__ void quad_transpose(uint32_t& r0, uint32_t& r1, uint32_t& r2, uint32_t& r3, int t) {
    const bool o1 = t & 1, o2 = t & 2;
    uint32_t x, y;
    x = o1 ? r0 : r1; y = __shfl_xor_sync(0xffffffffu, x, 1); if (o1) r0 = y; else r1 = y;
    x = o1 ? r2 : r3; y = __shfl_xor_sync(0xffffffffu, x, 1); if (o1) r2 = y; else r3 = y;
    x = o2 ? r0 : r2; y = __shfl_xor_sync(0xffffffffu, x, 2); if (o2) r0 = y; else r2 = y;
    x = o2 ? r1 : r3; y = __shfl_xor_sync(0xffffffffu, x, 2); if (o2) r1 = y; else r3 = y;
}

__device__ __forceinline__ float warp_sum(float s) {
#pragma unroll
    for (int o = 16; o > 0; o >>= 1) s += __shfl_xor_sync(0xffffffffu, s, o);
    return s;
}
__device__ __forceinline__ uint32_t hsub2(uint32_t a, uint32_t b) {
    __nv_bfloat162 r = __hsub2_rn(*reinterpret_cast<__nv_bfloat162*>(&a), *reinterpret_cast<__nv_bfloat162*>(&b));
    return *reinterpret_cast<uint32_t*>(&r);
}
__device__ __forceinline__ void ln_stats2(const uint32_t (&x)[2][8], float2 (&st)[2]) {
    float piv[2], s[2], ss[2];
#pragma unroll
    for (int r = 0; r < 2; r++) piv[r] = __shfl_sync(0xffffffffu, bf_lo(x[r][0]), 0);
#pragma unroll
    for (int r = 0; r < 2; r++) {
        float s0 = 0.f, s1 = 0.f, q0 = 0.f, q1 = 0.f;
#pragma unroll
        for (int i = 0; i < 8; i++) {
            const float d0 = bf_lo(x[r][i]) - piv[r], d1 = bf_hi(x[r][i]) - piv[r];
            s0 += d0; s1 += d1; q0 = fmaf(d0, d0, q0); q1 = fmaf(d1, d1, q1);
        }
        s[r] = s0 + s1; ss[r] = q0 + q1;
    }
#pragma unroll
    for (int o = 16; o > 0; o >>= 1) {
#pragma unroll
        for (int r = 0; r < 2; r++) { s[r] += __shfl_xor_sync(0xffffffffu, s[r], o); ss[r] += __shfl_xor_sync(0xffffffffu, ss[r], o); }
    }
#pragma unroll
    for (int r = 0; r < 2; r++) {
        const float md = s[r] * (1.0f / D_);
        const float var = bf16r(fmaxf(fmaf(-md, md, ss[r] * (1.0f / D_)), 0.f));
        st[r] = make_float2(bf16r(piv[r] + md), 1.0f / bf16r(sqrtf(bf16r(var + 1e-5f))));
    }
}
__device__ __forceinline__ void ln_apply(const uint32_t (&x)[8], float2 st, uint32_t (&o)[8]) {
    const uint32_t m2 = pack_bf16(st.x, st.x);
#pragma unroll
    for (int i = 0; i < 8; i++) {
        const uint32_t d = hsub2(x[i], m2);
        o[i] = pack_bf16(bf_lo(d) * st.y, bf_hi(d) * st.y);
    }
}

constexpr int K1_THREADS = 352;
constexpr int UT_PAD = 128;
constexpr int UT_LEN = UT_PAD + S_;
constexpr int KR_LEN = 2080;
constexpr int YP_LEN = S_ + (S_ / 32) * 8;

struct __align__(128) K1Smem {
    bf16 uT[4][UT_LEN];
    bf16 xT[4][S_];
    bf16 kr[4][2][KR_LEN];
    float yP[4][YP_LEN];
    alignas(128) float st[S_ + S_ / 2];
    alignas(128) uint4 wS[512][4];
    float red[8][32];
    uint64_t bar, bar2, bar3, bar4;
};

__device__ __forceinline__ void mma16816(float (&c)[4], uint32_t a0, uint32_t a1, uint32_t a2, uint32_t a3, uint32_t b0, uint32_t b1) {
    asm volatile("mma.sync.aligned.m16n8k16.row.col.f32.bf16.bf16.f32 {%0,%1,%2,%3}, {%4,%5,%6,%7}, {%8,%9}, {%0,%1,%2,%3};"
        : "+f"(c[0]), "+f"(c[1]), "+f"(c[2]), "+f"(c[3])
        : "r"(a0), "r"(a1), "r"(a2), "r"(a3), "r"(b0), "r"(b1));
}
__device__ __forceinline__ void ldsm_x4(uint32_t& r0, uint32_t& r1, uint32_t& r2, uint32_t& r3, uint32_t addr) {
    asm volatile("ldmatrix.sync.aligned.m8n8.x4.shared.b16 {%0,%1,%2,%3}, [%4];" : "=r"(r0), "=r"(r1), "=r"(r2), "=r"(r3) : "r"(addr) : "memory");
}

__device__ __forceinline__ void conv_mma(const bf16* uTc, const bf16* krlane, float (&acc)[16][4], int lane, int half) {
    const int lrow = lane & 7, lk = (lane >> 3) & 1, lt = lane >> 4;
    const uint32_t ubase = smem_u32(uTc) + (UT_PAD + 16 * (8 * lt + lrow) + 8 * lk) * 2;
#pragma unroll 1
    for (int pp = 0; pp < 4; pp++) {
        const int p = half * 4 + pp;
        uint32_t U[16][2];
#pragma unroll
        for (int j = 0; j < 16; j += 2) ldsm_x4(U[j][0], U[j][1], U[j + 1][0], U[j + 1][1], ubase + (j * 128 - p * 16) * 2);
        const uint32_t* kp = reinterpret_cast<const uint32_t*>(krlane - 16 * p);
        const volatile uint32_t* kpv = kp;
        uint32_t a0 = kp[0], a1 = kp[-4], a2 = kp[4], a3 = kpv[0];
#pragma unroll
        for (int q = 0; q < 16; q++) {
            uint32_t b0 = 0, b1 = 0, b2 = 0, b3 = 0;
            if (q < 15) { b0 = kp[-64 * (q + 1)]; b1 = kp[-64 * (q + 1) - 4]; b2 = kp[-64 * (q + 1) + 4]; b3 = kpv[-64 * (q + 1)]; }
#pragma unroll
            for (int n = 15; n >= q; n--) mma16816(acc[n], a0, a1, a2, a3, U[n - q][0], U[n - q][1]);
            a0 = b0; a1 = b1; a2 = b2; a3 = b3;
        }
    }
}

__device__ __forceinline__ void cp_async16(uint32_t dst, const void* src) {
    asm volatile("cp.async.cg.shared.global [%0], [%1], 16;" :: "r"(dst), "l"(src) : "memory");
}

__global__ void __cluster_dims__(2, 1, 1) __launch_bounds__(K1_THREADS, 1)
conv_kernel(const bf16* __restrict__ q, const bf16* __restrict__ k, const bf16* __restrict__ v,
            const bf16* __restrict__ shift_k, const bf16* __restrict__ ssm_k, const bf16* __restrict__ ssm_D,
            const __grid_constant__ CUtensorMap mapWg, const __grid_constant__ CUtensorMap mapWu, const bf16* __restrict__ wd) {
    extern __shared__ __align__(1024) uint8_t smem_raw[];
    pdl_launch();
    K1Smem& sm = *reinterpret_cast<K1Smem*>(smem_raw);
    const int tid = threadIdx.x, lane = tid & 31, warp = tid >> 5;
    const int bid = blockIdx.x;
    const int rank = bid & 1;
    const int c0 = 8 * (bid >> 1);
    const int cown = c0 + 4 * rank;
#define TMT 0
    TM(0, 0);
    const uint32_t bar = smem_u32(&sm.bar);
    if (tid == 0) {
        mbar_init(bar, 1);
        mbar_init(bar + 8, 1);
        mbar_init(bar + 16, 1);
        mbar_init(bar + 24, 1);
        asm volatile("fence.mbarrier_init.release.cluster;" ::: "memory");
        mbar_expect_tx(bar, 1024 * 4 * 2);
        mbar_expect_tx(bar + 8, 1024 * 4 * 2);
    }
    cluster_arrive_relaxed();

    if (warp < 8) {
        const int s0 = 1024 * rank + 4 * tid;
        uint4 kk[7], vv[4], qq[4], sw[4];
#pragma unroll
        for (int i = 0; i < 4; i++) kk[3 + i] = ldg128(k + (size_t)(s0 + i) * D_ + c0);
#pragma unroll
        for (int i = 0; i < 4; i++) vv[i] = ldg128(v + (size_t)(s0 + i) * D_ + c0);
        if (lane == 0) {
#pragma unroll
            for (int i = 0; i < 3; i++) {
                const int s = s0 - 3 + i;
                kk[i] = make_uint4(0, 0, 0, 0);
                if (s >= 0) kk[i] = ldg128(k + (size_t)s * D_ + c0);
            }
        }
#pragma unroll
        for (int i = 0; i < 4; i++) sw[i] = ldg128(shift_k + (size_t)c0 * 4 + 8 * i);
        uint4 kq[4]; uint32_t nx[4];
#pragma unroll
        for (int c = 0; c < 4; c++) {
            const bf16* kr = ssm_k + (size_t)(cown + c) * S_;
            kq[c] = ldg128(kr + 8 * tid);
            nx[c] = 0u;
            if (tid < 255) nx[c] = ldg16(kr + 8 * tid + 8);
        }
        const uint32_t dval = ldg16(ssm_D + cown + (warp >> 1));
        if (tid < 64) *reinterpret_cast<uint4*>(&sm.uT[tid >> 4][(tid & 15) * 8]) = make_uint4(0, 0, 0, 0);
#pragma unroll
        for (int i = 0; i < 3; i++) {
            uint4 t;
            t.x = __shfl_up_sync(0xffffffffu, kk[4 + i].x, 1); t.y = __shfl_up_sync(0xffffffffu, kk[4 + i].y, 1);
            t.z = __shfl_up_sync(0xffffffffu, kk[4 + i].z, 1); t.w = __shfl_up_sync(0xffffffffu, kk[4 + i].w, 1);
            if (lane != 0) kk[i] = t;
        }
        uint32_t kvw[4][4];
        const uint32_t* kkw = reinterpret_cast<const uint32_t*>(kk);
        const uint32_t* vvw = reinterpret_cast<const uint32_t*>(vv);
        const uint32_t* qqw = reinterpret_cast<const uint32_t*>(qq);
#pragma unroll
        for (int i2 = 0; i2 < 4; i2++) {
            const uint32_t t0 = __byte_perm(sw[i2].x, sw[i2].z, 0x5410), t1 = __byte_perm(sw[i2].x, sw[i2].z, 0x7632);
            const uint32_t t2 = __byte_perm(sw[i2].y, sw[i2].w, 0x5410), t3 = __byte_perm(sw[i2].y, sw[i2].w, 0x7632);
#pragma unroll
            for (int r = 0; r < 4; r++) {
                uint32_t a = hmul2(kkw[(r + 0) * 4 + i2], t3);
                a = hadd2(a, hmul2(kkw[(r + 1) * 4 + i2], t2));
                a = hadd2(a, hmul2(kkw[(r + 2) * 4 + i2], t1));
                a = hadd2(a, hmul2(kkw[(r + 3) * 4 + i2], t0));
                kvw[r][i2] = hmul2(a, vvw[r * 4 + i2]);
            }
        }
        TM(0, 1);
        cluster_wait();
        const uint32_t rbar = mapa(bar, (uint32_t)(rank ^ 1));
#pragma unroll
        for (int i2 = 0; i2 < 4; i2++) {
#pragma unroll
            for (int e = 0; e < 2; e++) {
                const uint32_t sel = e ? 0x7632 : 0x5410;
                const uint32_t w0 = __byte_perm(kvw[0][i2], kvw[1][i2], sel), w1 = __byte_perm(kvw[2][i2], kvw[3][i2], sel);
                const int cc = 2 * i2 + e;
                if ((cc >> 2) == rank) *reinterpret_cast<uint2*>(&sm.uT[cc & 3][UT_PAD + s0]) = make_uint2(w0, w1);
                else st_async_v2(mapa(smem_u32(&sm.uT[cc & 3][UT_PAD + s0]), (uint32_t)(rank ^ 1)), w0, w1, rbar);
            }
        }
#pragma unroll
        for (int c = 0; c < 4; c++) {
            uint4 a, b;
            a.x = __byte_perm(kq[c].w, 0, 0x1032); a.y = __byte_perm(kq[c].z, 0, 0x1032);
            a.z = __byte_perm(kq[c].y, 0, 0x1032); a.w = __byte_perm(kq[c].x, 0, 0x1032);
            b.x = __byte_perm(nx[c], kq[c].w, 0x7610); b.y = __byte_perm(kq[c].w, kq[c].z, 0x7610);
            b.z = __byte_perm(kq[c].z, kq[c].y, 0x7610); b.w = __byte_perm(kq[c].y, kq[c].x, 0x7610);
            *reinterpret_cast<uint4*>(&sm.kr[c][0][2040 - 8 * tid]) = a;
            *reinterpret_cast<uint4*>(&sm.kr[c][1][2040 - 8 * tid]) = b;
            if (tid == 0) {
                *reinterpret_cast<uint4*>(&sm.kr[c][1][2048]) = make_uint4(kq[c].x & 0xffffu, 0, 0, 0);
            } else if (tid < 8) {
                if (tid < 4) *reinterpret_cast<uint4*>(&sm.kr[c][1][2048 + 8 * tid]) = make_uint4(0, 0, 0, 0);
                else *reinterpret_cast<uint4*>(&sm.kr[c][0][2048 + 8 * (tid - 4)]) = make_uint4(0, 0, 0, 0);
            }
        }
#pragma unroll
        for (int i = 0; i < 4; i++) qq[i] = ldg128(q + (size_t)(s0 + i) * D_ + c0);
        TM(0, 3);
        named_bar(6, 352);
        mbar_wait_cluster(bar, 0);
        TM(0, 4);

        const int ch = warp >> 1, half = warp & 1;
        const int g = lane >> 2, t = lane & 3;
        float acc[16][4];
#pragma unroll
        for (int i = 0; i < 16; i++) { acc[i][0] = acc[i][1] = acc[i][2] = acc[i][3] = 0.f; }
        const bf16* krlane = (g & 1) ? &sm.kr[ch][0][2047 - g + 2 * t] : &sm.kr[ch][1][2048 - g + 2 * t];
        conv_mma(sm.uT[ch], krlane, acc, lane, half);
        TM(0, 5);
#pragma unroll
        for (int i2 = 0; i2 < 4; i2++) {
#pragma unroll
            for (int e = 0; e < 2; e++) {
                const uint32_t sel = e ? 0x7632 : 0x5410;
                const uint32_t w0 = __byte_perm(qqw[i2], qqw[4 + i2], sel), w1 = __byte_perm(qqw[8 + i2], qqw[12 + i2], sel);
                const int cc = 2 * i2 + e;
                if ((cc >> 2) == rank) *reinterpret_cast<uint2*>(&sm.xT[cc & 3][s0]) = make_uint2(w0, w1);
                else st_async_v2(mapa(smem_u32(&sm.xT[cc & 3][s0]), (uint32_t)(rank ^ 1)), w0, w1, rbar + 8);
            }
        }
        float* yp = &sm.yP[ch][40 * t + g];
        if (half) {
#pragma unroll
            for (int n = 0; n < 16; n++) {
                yp[160 * n] = acc[n][0];
                yp[160 * n + 16] = acc[n][1];
                yp[160 * n + 8] = acc[n][2];
                yp[160 * n + 24] = acc[n][3];
            }
        }
        named_bar(1 + ch, 64);
        if (!half) {
#pragma unroll
            for (int n = 0; n < 16; n++) {
                yp[160 * n] += acc[n][0];
                yp[160 * n + 16] += acc[n][1];
                yp[160 * n + 8] += acc[n][2];
                yp[160 * n + 24] += acc[n][3];
            }
        }
        named_bar(7, 288);
        mbar_wait_cluster(bar + 8, 0);
        TM(0, 6);
        {
            const int tt = tid & 63;
            bf16* dst = g_hT + (size_t)(cown + ch) * HT_PITCH;
            const uint32_t d2 = dval * 0x10001u;
#pragma unroll
            for (int j = 0; j < 4; j++) {
                const int s = (j * 64 + tt) * 8;
                const float* src = &sm.yP[ch][s + (s >> 5) * 8];
                const float4 a = *reinterpret_cast<const float4*>(src), b = *reinterpret_cast<const float4*>(src + 4);
                const uint4 kv4 = *reinterpret_cast<const uint4*>(&sm.uT[ch][UT_PAD + s]);
                const uint4 x4 = *reinterpret_cast<const uint4*>(&sm.xT[ch][s]);
                const uint32_t y2[4] = {hadd2(pack_bf16(a.x, a.y), hmul2(kv4.x, d2)), hadd2(pack_bf16(a.z, a.w), hmul2(kv4.y, d2)),
                                        hadd2(pack_bf16(b.x, b.y), hmul2(kv4.z, d2)), hadd2(pack_bf16(b.z, b.w), hmul2(kv4.w, d2))};
                const uint32_t xw[4] = {x4.x, x4.y, x4.z, x4.w};
                const uint4 m4 = *reinterpret_cast<const uint4*>(&sm.st[S_ + s / 2]);
                const float4 ra = *reinterpret_cast<const float4*>(&sm.st[s]), rb4 = *reinterpret_cast<const float4*>(&sm.st[s + 4]);
                const uint32_t mw[4] = {m4.x, m4.y, m4.z, m4.w};
                const float rw[8] = {ra.x, ra.y, ra.z, ra.w, rb4.x, rb4.y, rb4.z, rb4.w};
                uint32_t o[4];
#pragma unroll
                for (int i = 0; i < 4; i++) {
                    const uint32_t d = hsub2(xw[i], mw[i]);
                    const uint32_t qn = pack_bf16(bf_lo(d) * rw[2 * i], bf_hi(d) * rw[2 * i + 1]);
                    o[i] = hadd2(xw[i], hmul2(qn, y2[i]));
                }
                *reinterpret_cast<uint4*>(dst + s) = make_uint4(o[0], o[1], o[2], o[3]);
            }
        }
        TM(0, 7);
    } else {
        cluster_wait();
        named_bar(6, 352);
        const uint32_t hbar = bar + 16;
        if (warp < 10) {
            {
                const int rr = 8 * (warp - 8);
                uint32_t xq[4][2][8];
#pragma unroll
                for (int r = 0; r < 8; r++) {
                    const uint4 qa = ldg128(q + (size_t)(16 * bid + rr + r) * D_ + 8 * lane);
                    const uint4 qb = ldg128(q + (size_t)(16 * bid + rr + r) * D_ + 8 * (lane + 32));
                    uint32_t* x = xq[r >> 1][r & 1];
                    x[0] = qa.x; x[1] = qa.y; x[2] = qa.z; x[3] = qa.w; x[4] = qb.x; x[5] = qb.y; x[6] = qb.z; x[7] = qb.w;
                }
#pragma unroll
                for (int r2 = 0; r2 < 4; r2++) {
                    float2 sa[2];
                    ln_stats2(xq[r2], sa);
                    if (lane == 0) {
                        *reinterpret_cast<float2*>(&g_st1[16 * bid + rr + 2 * r2]) = make_float2(sa[0].y, sa[1].y);
                        reinterpret_cast<uint32_t*>(&g_st1[S_])[(16 * bid + rr) / 2 + r2] = pack_bf16(sa[0].x, sa[1].x);
                    }
                }
            }
            if (lane == 0) { __threadfence(); atomicAdd(&g_cnt, 1u); }
            if (warp == 9) return;
            if (lane == 0) {
                unsigned int c; int spins = 0;
                while (true) {
                    asm volatile("ld.acquire.gpu.global.u32 %0, [%1];" : "=r"(c) : "l"(&g_cnt) : "memory");
                    if (c >= 2 * gridDim.x || ++spins > (1 << 22)) break;
                    __nanosleep(200);
                }
                asm volatile("fence.proxy.async;" ::: "memory");
                mbar_expect_tx(hbar + 8, 12288);
                asm volatile("cp.async.bulk.shared::cluster.global.mbarrier::complete_tx::bytes [%0], [%1], %2, [%3];"
                    :: "r"(smem_u32(&sm.st[0])), "l"(&g_st1[0]), "r"(12288), "r"(hbar + 8) : "memory");
            }
            mbar_wait(hbar + 8, 0);
            named_bar(7, 288);
        } else {
            if (lane == 0) asm volatile("cp.async.bulk.prefetch.L2.global [%0], %1;" :: "l"(wd + (size_t)bid * 7168), "r"(14336) : "memory");
            if (bid < 112) {
                if (lane == 0) {
                    mbar_expect_tx(hbar, 32768);
                    const CUtensorMap* mw = (bid < 56) ? &mapWg : &mapWu;
                    const int col = 32 * ((bid < 56) ? bid : bid - 56);
                    tma_load_2d(smem_u32(&sm.wS[0][0]), mw, hbar, col, 0);
                    tma_load_2d(smem_u32(&sm.wS[256][0]), mw, hbar, col, 256);
                }
                mbar_wait(hbar, 0);
                const int cq = lane & 3, rgp = lane >> 2;
                float cs[8];
#pragma unroll
                for (int i = 0; i < 8; i++) cs[i] = 0.f;
#pragma unroll 4
                for (int r = 0; r < 64; r++) {
                    const uint4 w = sm.wS[r * 8 + rgp][cq];
                    cs[0] += bf_lo(w.x); cs[1] += bf_hi(w.x); cs[2] += bf_lo(w.y); cs[3] += bf_hi(w.y);
                    cs[4] += bf_lo(w.z); cs[5] += bf_hi(w.z); cs[6] += bf_lo(w.w); cs[7] += bf_hi(w.w);
                }
#pragma unroll
                for (int i = 0; i < 8; i++) {
                    cs[i] += __shfl_xor_sync(0xffffffffu, cs[i], 4);
                    cs[i] += __shfl_xor_sync(0xffffffffu, cs[i], 8);
                    cs[i] += __shfl_xor_sync(0xffffffffu, cs[i], 16);
                }
                if (lane < 4) {
                    *reinterpret_cast<float4*>(&g_colsum[32 * bid + lane * 8]) = make_float4(cs[0], cs[1], cs[2], cs[3]);
                    *reinterpret_cast<float4*>(&g_colsum[32 * bid + lane * 8 + 4]) = make_float4(cs[4], cs[5], cs[6], cs[7]);
                }
            }
        }
    }
#undef TMT
}

constexpr int G1_THREADS = 384;
constexpr int G1_STAGES = 3;
constexpr int G1_A_BYTES = 8 * 16384;
constexpr int G1_B_STAGE = 32768;
constexpr int G1_OFF_B = G1_A_BYTES;
constexpr int G1_OFF_STATS = G1_OFF_B + G1_STAGES * G1_B_STAGE;
constexpr int G1_OFF_CS = G1_OFF_STATS + 1024;
constexpr int G1_OFF_BAR = G1_OFF_CS + 1792;
constexpr int G1_SMEM = G1_OFF_BAR + 128;

__device__ __forceinline__ float tanh_fast(float x) { float t; asm("tanh.approx.f32 %0, %1;" : "=f"(t) : "f"(x)); return t; }

template <int NT>
__device__ __forceinline__ void g1_math(const float (&acc)[NT * 8], const float* cs_g, const float* cs_u, float2 st0, float2 st1, uint32_t (&P)[NT * 2], int t) {
    const float r0 = st0.y, r1 = st1.y, m0 = -st0.x * st0.y, m1 = -st1.x * st1.y;
#pragma unroll
    for (int j = 0; j < NT; j++) {
        const float2 cg = *reinterpret_cast<const float2*>(cs_g + 8 * j + 2 * t);
        const float2 cu = *reinterpret_cast<const float2*>(cs_u + 8 * j + 2 * t);
        float r[4];
#pragma unroll
        for (int e = 0; e < 4; e++) {
            const float rr = (e < 2) ? r0 : r1, mm = (e < 2) ? m0 : m1;
            const float gh = fmaf(acc[4 * j + e], 0.5f * rr, (0.5f * mm) * ((e & 1) ? cg.y : cg.x));
            const float uv = fmaf(acc[4 * (NT + j) + e], rr, mm * ((e & 1) ? cu.y : cu.x));
            r[e] = fmaf(tanh_fast(gh), 0.5f, 0.5f) * uv;
        }
        P[2 * j] = pack_bf16(r[0], r[1]);
        P[2 * j + 1] = pack_bf16(r[2], r[3]);
    }
}
template <int NT>
__device__ __forceinline__ void g1_store(uint32_t (&P)[NT * 2], bf16* out0, int t) {
#pragma unroll
    for (int j0 = 0; j0 < NT; j0 += 4) {
        quad_transpose(P[2 * j0], P[2 * j0 + 2], P[2 * j0 + 4], P[2 * j0 + 6], t);
        quad_transpose(P[2 * j0 + 1], P[2 * j0 + 3], P[2 * j0 + 5], P[2 * j0 + 7], t);
        *reinterpret_cast<uint4*>(out0 + 8 * (j0 + t)) = make_uint4(P[2 * j0], P[2 * j0 + 2], P[2 * j0 + 4], P[2 * j0 + 6]);
        *reinterpret_cast<uint4*>(out0 + 8 * F_ + 8 * (j0 + t)) = make_uint4(P[2 * j0 + 1], P[2 * j0 + 3], P[2 * j0 + 5], P[2 * j0 + 7]);
    }
}

__global__ void __cluster_dims__(2, 1, 1) __launch_bounds__(G1_THREADS, 1)
gemm1_kernel(const __grid_constant__ CUtensorMap mapA, const __grid_constant__ CUtensorMap mapG4, const __grid_constant__ CUtensorMap mapU4,
             const __grid_constant__ CUtensorMap mapG3, const __grid_constant__ CUtensorMap mapU3) {
    extern __shared__ __align__(1024) uint8_t smem_raw[];
    const uint32_t sb = smem_u32(smem_raw);
    const int tid = threadIdx.x, lane = tid & 31, warp = tid >> 5, wgi = tid >> 7;
    const int rank = blockIdx.x & 1;
    const int cb = blockIdx.x & 7, rb = blockIdx.x >> 3;
#define TMT 128
    TM(2, 0);
    pdl_launch();
    if (tid == 32) { prefetch_map(&mapA); prefetch_map(&mapG3); prefetch_map(&mapU3); }
    const uint32_t barA = sb + G1_OFF_BAR;
    const uint32_t barF = barA + 64;
    const uint32_t barE = barF + 8 * G1_STAGES;
    const uint32_t barS = barE + 8 * G1_STAGES;
    if (tid == 0) {
        for (int i = 0; i < 8; i++) mbar_init(barA + 8 * i, 1);
        for (int i = 0; i < G1_STAGES; i++) { mbar_init(barF + 8 * i, 1); mbar_init(barE + 8 * i, 2); }
        mbar_init(barS, 1);
        for (int i = 0; i < 8; i++) mbar_expect_tx(barA + 8 * i, 16384);
        asm volatile("fence.mbarrier_init.release.cluster;" ::: "memory");
    }
    __syncthreads();
    cluster_arrive_relaxed();

    if (wgi == 0) {
        reg_dealloc<40>();
        if (warp == 0) {
            cluster_wait();
            if (lane == 0) {
                int st = 0, ph = 1;
                for (int it = 0; it < 16; it++) {
                    const int kc = it & 7;
                    if (it == 1) {
                        pdl_wait();
                        for (int i = 0; i < 4; i++) {
                            const int c = 2 * i + rank;
                            tma_load_3d_mc(sb + c * 16384, &mapA, barA + 8 * c, 0, c * 64, rb * 2, (uint16_t)3);
                        }
                    }
                    mbar_wait(barE + 8 * st, ph);
                    const uint32_t dst = sb + G1_OFF_B + st * G1_B_STAGE;
                    if (it < 8) {
                        mbar_expect_tx(barF + 8 * st, 32768);
                        tma_load_3d(dst, &mapG4, barF + 8 * st, 0, kc * 64, cb * 7);
                        tma_load_3d(dst + 16384, &mapU4, barF + 8 * st, 0, kc * 64, cb * 7);
                    } else {
                        mbar_expect_tx(barF + 8 * st, 24576);
                        tma_load_3d(dst, &mapG3, barF + 8 * st, 0, kc * 64, cb * 7 + 4);
                        tma_load_3d(dst + 12288, &mapU3, barF + 8 * st, 0, kc * 64, cb * 7 + 4);
                    }
                    if (++st == G1_STAGES) { st = 0; ph ^= 1; }
                }
            }
            __syncwarp();
        } else if (warp == 1) {
            cluster_wait();
            pdl_wait();
            float* cs = reinterpret_cast<float*>(smem_raw + G1_OFF_CS);
            for (int i = lane; i < 448; i += 32) cs[i] = __ldcg((i < 224) ? &g_colsum[cb * 224 + i] : &g_colsum[F_ + cb * 224 + (i - 224)]);
            __syncwarp();
            if (lane == 0) mbar_arrive(barS);
        } else {
            cluster_wait();
        }
    } else {
        reg_alloc<232>();
        cluster_wait();
        const int cw = wgi - 1;
        const int g = lane >> 2, t = lane & 3, wl = warp & 3, tl = tid & 127;
        bf16* outp = g_hh + (size_t)(rb * 128 + cw * 64 + wl * 16 + g) * F_ + cb * 224;
        const float* cs = reinterpret_cast<const float*>(smem_raw + G1_OFF_CS);
        int st = 0, ph = 0;
        float2 st0, st1;
        uint32_t P1[32];
        {
            float acc[128];
            const int kq = lane >> 3, mp = lane & 7;
            const uint8_t* sbase = smem_raw + cw * 8192 + kq * 128 + (mp & 3) * 4;
            const int mc = 2 * wl + (mp >> 2);
            float p0 = 0.f, p1 = 0.f, s0 = 0.f, s1 = 0.f, q0 = 0.f, q1 = 0.f;
#pragma unroll 1
            for (int kc = 0; kc < 8; kc++) {
                mbar_wait(barA + 8 * kc, 0);
                mbar_wait(barF + 8 * st, ph);
                if (tl == 0 && cw == 0) TR(1, kc);
                wgmma_fence();
                const uint32_t aaddr = sb + kc * 16384 + cw * 8192;
                const uint32_t baddr = sb + G1_OFF_B + st * G1_B_STAGE;
#pragma unroll
                for (int kk = 0; kk < 4; kk++)
                    wgmma_m64n256k16_ss(acc, make_desc(aaddr + kk * 2048, 8192, 1024, 1), make_desc(baddr + kk * 1024, 4096, 512, 2), (kc | kk) != 0);
                wgmma_commit();
                if (kc == 0) {
                    const uint32_t w = *reinterpret_cast<const uint32_t*>(smem_raw + cw * 8192 + (mc << 4) + (mp & 3) * 4);
                    p0 = bf_lo(w); p1 = bf_hi(w);
                }
#pragma unroll
                for (int i = 0; i < 16; i++) {
                    const int kr = 4 * i;
                    const uint32_t w = *reinterpret_cast<const uint32_t*>(sbase + kc * 16384 + kr * 128 + ((mc ^ ((kr + kq) & 7)) << 4));
                    const float d0 = bf_lo(w) - p0, d1 = bf_hi(w) - p1;
                    s0 += d0; s1 += d1; q0 = fmaf(d0, d0, q0); q1 = fmaf(d1, d1, q1);
                }
                wgmma_wait<0>();
                if (tl == 0) mbar_arrive(barE + 8 * st);
                if (++st == G1_STAGES) { st = 0; ph ^= 1; }
            }
            TM(2, 1);
            {
#pragma unroll
                for (int o = 8; o <= 16; o <<= 1) {
                    s0 += __shfl_xor_sync(0xffffffffu, s0, o); s1 += __shfl_xor_sync(0xffffffffu, s1, o);
                    q0 += __shfl_xor_sync(0xffffffffu, q0, o); q1 += __shfl_xor_sync(0xffffffffu, q1, o);
                }
                const float md0 = s0 * (1.0f / D_), md1 = s1 * (1.0f / D_);
                const float v0 = bf16r(fmaxf(fmaf(-md0, md0, q0 * (1.0f / D_)), 0.f)), v1 = bf16r(fmaxf(fmaf(-md1, md1, q1 * (1.0f / D_)), 0.f));
                const float ma = bf16r(p0 + md0), mb = bf16r(p1 + md1);
                const float ra = 1.0f / bf16r(sqrtf(bf16r(v0 + 1e-5f))), rbb = 1.0f / bf16r(sqrtf(bf16r(v1 + 1e-5f)));
                const float mA = __shfl_sync(0xffffffffu, ma, g >> 1), mB = __shfl_sync(0xffffffffu, mb, g >> 1);
                const float rA = __shfl_sync(0xffffffffu, ra, g >> 1), rB = __shfl_sync(0xffffffffu, rbb, g >> 1);
                const float mC = __shfl_sync(0xffffffffu, ma, 4 + (g >> 1)), mD = __shfl_sync(0xffffffffu, mb, 4 + (g >> 1));
                const float rC = __shfl_sync(0xffffffffu, ra, 4 + (g >> 1)), rD = __shfl_sync(0xffffffffu, rbb, 4 + (g >> 1));
                st0 = (g & 1) ? make_float2(mB, rB) : make_float2(mA, rA);
                st1 = (g & 1) ? make_float2(mD, rD) : make_float2(mC, rC);
            }
            mbar_wait(barS, 0);
            TM(2, 5);
            g1_math<16>(acc, cs, cs + 224, st0, st1, P1, t);
            TM(2, 2);
        }
        {
            float acc[96];
#pragma unroll 1
            for (int kc = 0; kc < 8; kc++) {
                mbar_wait(barF + 8 * st, ph);
                if (tl == 0 && cw == 0) TR(1, 8 + kc);
                wgmma_fence();
                const uint32_t aaddr = sb + kc * 16384 + cw * 8192;
                const uint32_t baddr = sb + G1_OFF_B + st * G1_B_STAGE;
#pragma unroll
                for (int kk = 0; kk < 4; kk++)
                    wgmma_m64n192k16_ss(acc, make_desc(aaddr + kk * 2048, 8192, 1024, 1), make_desc(baddr + kk * 1024, 4096, 512, 2), (kc | kk) != 0);
                wgmma_commit();
                if (kc == 0) g1_store<16>(P1, outp, t);
                wgmma_wait<0>();
                if (tl == 0) mbar_arrive(barE + 8 * st);
                if (++st == G1_STAGES) { st = 0; ph ^= 1; }
            }
            TM(2, 3);
            uint32_t P2[24];
            g1_math<12>(acc, cs + 128, cs + 224 + 128, st0, st1, P2, t);
            g1_store<12>(P2, outp + 128, t);
            TM(2, 4);
        }
    }
}

constexpr int G2_THREADS = 384;
constexpr int G2_STAGES = 6;
constexpr int G2_STAGE = 32768;
constexpr int G2_OFF_X = G2_STAGES * G2_STAGE;
constexpr int G2_OFF_BAR = G2_OFF_X + 32768;
constexpr int G2_SMEM = G2_OFF_BAR + 128;
constexpr int G2_KSTEPS = 14;

__device__ __forceinline__ void ldsm_x4_t(uint32_t& r0, uint32_t& r1, uint32_t& r2, uint32_t& r3, uint32_t addr) {
    asm volatile("ldmatrix.sync.aligned.m8n8.x4.trans.shared.b16 {%0,%1,%2,%3}, [%4];" : "=r"(r0), "=r"(r1), "=r"(r2), "=r"(r3) : "r"(addr) : "memory");
}

__global__ void __cluster_dims__(2, 1, 1) __launch_bounds__(G2_THREADS, 1)
gemm2_kernel(const __grid_constant__ CUtensorMap mapHH, const __grid_constant__ CUtensorMap mapWd, const __grid_constant__ CUtensorMap mapH,
             bf16* __restrict__ out) {
    extern __shared__ __align__(1024) uint8_t smem_raw[];
    const uint32_t sb = smem_u32(smem_raw);
    const int tid = threadIdx.x, lane = tid & 31, warp = tid >> 5, wgi = tid >> 7;
    const int ks = blockIdx.x & 1, nb = (blockIdx.x >> 1) & 3, rb = blockIdx.x >> 3;
    TM(3, 0);
    if (tid == 32) { prefetch_map(&mapHH); prefetch_map(&mapH); }
    const uint32_t barF = sb + G2_OFF_BAR;
    const uint32_t barE = barF + 8 * G2_STAGES;
    const uint32_t barX = barE + 8 * G2_STAGES;
    if (tid == 0) {
        for (int i = 0; i < G2_STAGES; i++) { mbar_init(barF + 8 * i, 1); mbar_init(barE + 8 * i, 2); }
        mbar_init(barX, 1);
        asm volatile("fence.mbarrier_init.release.cluster;" ::: "memory");
        mbar_expect_tx(barX, 32768);
        for (int it = 0; it < 2; it++) {
            mbar_expect_tx(barF + 8 * it, 32768);
            tma_load_3d(sb + it * G2_STAGE + 16384, &mapWd, barF + 8 * it, 0, ks * 896 + it * 64, nb * 2);
        }
    }
    __syncthreads();
    cluster_arrive_relaxed();

    if (wgi == 0) {
        if (tid == 0) {
            pdl_wait();
            for (int it = 0; it < G2_STAGES; it++) {
                if (it >= 2) mbar_expect_tx(barF + 8 * it, 32768);
                tma_load_2d(sb + it * G2_STAGE, &mapHH, barF + 8 * it, ks * 896 + it * 64, rb * 128);
                if (it >= 2) tma_load_3d(sb + it * G2_STAGE + 16384, &mapWd, barF + 8 * it, 0, ks * 896 + it * 64, nb * 2);
            }
            if (blockIdx.x == 0) g_cnt = 0u;
            int st = 0, ph = 0;
            for (int it = G2_STAGES; it < G2_KSTEPS; it++) {
                mbar_wait(barE + 8 * st, ph);
                const uint32_t dst = sb + st * G2_STAGE;
                const int k0 = ks * 896 + it * 64;
                mbar_expect_tx(barF + 8 * st, 32768);
                tma_load_2d(dst, &mapHH, barF + 8 * st, k0, rb * 128);
                tma_load_3d(dst + 16384, &mapWd, barF + 8 * st, 0, k0, nb * 2);
                if (++st == G2_STAGES) { st = 0; ph ^= 1; }
            }
            mbar_wait(barE + 8 * st, ph);
            mbar_expect_tx(barF + 8 * st, 16384);
            tma_load_2d(sb + st * G2_STAGE, &mapH, barF + 8 * st, rb * 128 + ks * 64, nb * 128);
        }
        __syncwarp();
        cluster_wait();
    } else {
        const int cw = wgi - 1;
        const int g = lane >> 2, t = lane & 3, wl = warp & 3;
        const int tl = tid & 127;
        int st = 0, ph = 0;
        float acc[64];
#pragma unroll 1
        for (int it = 0; it < G2_KSTEPS; it++) {
            mbar_wait(barF + 8 * st, ph);
            if (it == 0) TM(3, 1);
            wgmma_fence();
            const uint32_t aaddr = sb + st * G2_STAGE + cw * 8192;
            const uint32_t baddr = sb + st * G2_STAGE + 16384;
#pragma unroll
            for (int kk = 0; kk < 4; kk++)
                wgmma_m64n128k16_ss(acc, make_desc(aaddr + kk * 32, 16, 1024, 1), make_desc(baddr + kk * 2048, 8192, 1024, 1), (it | kk) != 0);
            wgmma_commit();
            wgmma_wait<0>();
            if (tl == 0) mbar_arrive(barE + 8 * st);
            if (++st == G2_STAGES) { st = 0; ph ^= 1; }
        }
        TM(3, 2);
        cluster_wait();
        if (cw != ks) {
            const uint32_t dst = mapa(sb + G2_OFF_X + tl * 16, (uint32_t)(ks ^ 1));
            const uint32_t rbar = mapa(barX, (uint32_t)(ks ^ 1));
#pragma unroll
            for (int i = 0; i < 16; i++) st_async_v4f(dst + i * 2048, acc[4 * i], acc[4 * i + 1], acc[4 * i + 2], acc[4 * i + 3], rbar);
        } else {
            const float4* xb = reinterpret_cast<const float4*>(smem_raw + G2_OFF_X) + tl;
            const int row0 = rb * 128 + cw * 64 + wl * 16 + g;
            bf16* o0 = out + (size_t)row0 * D_ + nb * 128;
            uint32_t ha[16], hb[16];
            mbar_wait(barF + 8 * st, ph);
            {
                const int chl = 8 * (lane >> 4) + (lane & 7), sb8 = 2 * wl + ((lane >> 3) & 1);
                const uint32_t hbase = sb + st * G2_STAGE + chl * 128 + ((sb8 ^ (lane & 7)) << 4);
#pragma unroll
                for (int j = 0; j < 16; j += 2) ldsm_x4_t(ha[j], hb[j], ha[j + 1], hb[j + 1], hbase + j * 1024);
            }
            mbar_wait_cluster(barX, 0);
            TM(3, 4);
#pragma unroll
            for (int j0 = 0; j0 < 16; j0 += 4) {
                uint32_t P0[4], P1[4];
#pragma unroll
                for (int jj = 0; jj < 4; jj++) {
                    const int j = j0 + jj;
                    const float4 x = xb[j * 128];
                    P0[jj] = hadd2(ha[j], pack_bf16(acc[4 * j] + x.x, acc[4 * j + 1] + x.y));
                    P1[jj] = hadd2(hb[j], pack_bf16(acc[4 * j + 2] + x.z, acc[4 * j + 3] + x.w));
                }
                quad_transpose(P0[0], P0[1], P0[2], P0[3], t);
                quad_transpose(P1[0], P1[1], P1[2], P1[3], t);
                *reinterpret_cast<uint4*>(o0 + 8 * (j0 + t)) = make_uint4(P0[0], P0[1], P0[2], P0[3]);
                *reinterpret_cast<uint4*>(o0 + 8 * D_ + 8 * (j0 + t)) = make_uint4(P1[0], P1[1], P1[2], P1[3]);
            }
        }
        TM(3, 5);
    }
#undef TMT
}

typedef CUresult (*EncodeFn)(CUtensorMap*, CUtensorMapDataType, cuuint32_t, void*, const cuuint64_t*, const cuuint64_t*,
                             const cuuint32_t*, const cuuint32_t*, CUtensorMapInterleave, CUtensorMapSwizzle,
                             CUtensorMapL2promotion, CUtensorMapFloatOOBfill);

static void enc2d(EncodeFn enc, CUtensorMap* m, const void* p, int rows, int cols, int brows, int bcols, int pitch = 0) {
    cuuint64_t dims[2] = {(cuuint64_t)cols, (cuuint64_t)rows};
    cuuint64_t strides[1] = {(cuuint64_t)(pitch ? pitch : cols) * 2};
    cuuint32_t box[2] = {(cuuint32_t)bcols, (cuuint32_t)brows};
    cuuint32_t es[2] = {1, 1};
    enc(m, CU_TENSOR_MAP_DATA_TYPE_BFLOAT16, 2, const_cast<void*>(p), dims, strides, box, es, CU_TENSOR_MAP_INTERLEAVE_NONE,
        bcols == 32 ? CU_TENSOR_MAP_SWIZZLE_64B : CU_TENSOR_MAP_SWIZZLE_128B, CU_TENSOR_MAP_L2_PROMOTION_L2_128B, CU_TENSOR_MAP_FLOAT_OOB_FILL_NONE);
}
static void enc2d_plain(EncodeFn enc, CUtensorMap* m, const void* p, int rows, int cols, int brows, int bcols) {
    cuuint64_t dims[2] = {(cuuint64_t)cols, (cuuint64_t)rows};
    cuuint64_t strides[1] = {(cuuint64_t)cols * 2};
    cuuint32_t box[2] = {(cuuint32_t)bcols, (cuuint32_t)brows};
    cuuint32_t es[2] = {1, 1};
    enc(m, CU_TENSOR_MAP_DATA_TYPE_BFLOAT16, 2, const_cast<void*>(p), dims, strides, box, es, CU_TENSOR_MAP_INTERLEAVE_NONE,
        CU_TENSOR_MAP_SWIZZLE_NONE, CU_TENSOR_MAP_L2_PROMOTION_L2_128B, CU_TENSOR_MAP_FLOAT_OOB_FILL_NONE);
}
static void enc3d(EncodeFn enc, CUtensorMap* m, const void* p, int rows, int cols, int atom, int brows, int natoms, int pitch = 0) {
    cuuint64_t dims[3] = {(cuuint64_t)atom, (cuuint64_t)rows, (cuuint64_t)(cols / atom)};
    cuuint64_t strides[2] = {(cuuint64_t)(pitch ? pitch : cols) * 2, (cuuint64_t)atom * 2};
    cuuint32_t box[3] = {(cuuint32_t)atom, (cuuint32_t)brows, (cuuint32_t)natoms};
    cuuint32_t es[3] = {1, 1, 1};
    enc(m, CU_TENSOR_MAP_DATA_TYPE_BFLOAT16, 3, const_cast<void*>(p), dims, strides, box, es, CU_TENSOR_MAP_INTERLEAVE_NONE,
        atom == 32 ? CU_TENSOR_MAP_SWIZZLE_64B : CU_TENSOR_MAP_SWIZZLE_128B, CU_TENSOR_MAP_L2_PROMOTION_L2_128B, CU_TENSOR_MAP_FLOAT_OOB_FILL_NONE);
}

extern "C" void kernel_launch(void* const* d_in, const int* in_sizes, int n_in, void* d_out, int out_size) {
    const bf16* q = (const bf16*)d_in[0];
    const bf16* k = (const bf16*)d_in[1];
    const bf16* v = (const bf16*)d_in[2];
    const bf16* shift_k = (const bf16*)d_in[3];
    const bf16* ssm_k = (const bf16*)d_in[4];
    const bf16* ssm_D = (const bf16*)d_in[5];
    const bf16* wg = (const bf16*)d_in[7];
    const bf16* wu = (const bf16*)d_in[8];
    const bf16* wd = (const bf16*)d_in[9];
    bf16* out = (bf16*)d_out;

    static EncodeFn enc = nullptr;
    static void *p_hT = nullptr, *p_hh = nullptr;
    if (!enc) {
        void* fn = nullptr; cudaDriverEntryPointQueryResult qr;
        cudaGetDriverEntryPoint("cuTensorMapEncodeTiled", &fn, cudaEnableDefault, &qr);
        enc = (EncodeFn)fn;
        cudaGetSymbolAddress(&p_hT, g_hT);
        cudaGetSymbolAddress(&p_hh, g_hh);
        cudaFuncSetAttribute(conv_kernel, cudaFuncAttributeMaxDynamicSharedMemorySize, (int)sizeof(K1Smem));
        cudaFuncSetAttribute(gemm1_kernel, cudaFuncAttributeMaxDynamicSharedMemorySize, G1_SMEM);
        cudaFuncSetAttribute(gemm2_kernel, cudaFuncAttributeMaxDynamicSharedMemorySize, G2_SMEM);
    }
    CUtensorMap mA, mG64, mU64, mG32, mU32, mHH, mWd, mH, mWgp, mWup;
    enc2d_plain(enc, &mWgp, wg, D_, F_, 256, 32);
    enc2d_plain(enc, &mWup, wu, D_, F_, 256, 32);
    enc3d(enc, &mA, p_hT, D_, S_, 64, 64, 2, HT_PITCH);
    enc2d(enc, &mH, p_hT, D_, S_, 128, 64, HT_PITCH);
    enc3d(enc, &mG64, wg, D_, F_, 32, 64, 4);
    enc3d(enc, &mU64, wu, D_, F_, 32, 64, 4);
    enc3d(enc, &mG32, wg, D_, F_, 32, 64, 3);
    enc3d(enc, &mU32, wu, D_, F_, 32, 64, 3);
    enc2d(enc, &mHH, p_hh, S_, F_, 128, 64);
    enc3d(enc, &mWd, wd, F_, D_, 64, 64, 2);

    cudaStream_t st = cudaStreamPerThread;
    cudaLaunchAttribute at[1];
    at[0].id = cudaLaunchAttributeProgrammaticStreamSerialization;
    at[0].val.programmaticStreamSerializationAllowed = 1;
    cudaLaunchConfig_t cfg = {};
    cfg.stream = st; cfg.attrs = at; cfg.numAttrs = 1;
    conv_kernel<<<128, K1_THREADS, sizeof(K1Smem), st>>>(q, k, v, shift_k, ssm_k, ssm_D, mWgp, mWup, wd);
    cfg.gridDim = dim3(128); cfg.blockDim = dim3(G1_THREADS); cfg.dynamicSmemBytes = G1_SMEM;
    cudaLaunchKernelEx(&cfg, gemm1_kernel, mA, mG64, mU64, mG32, mU32);
    cfg.gridDim = dim3(128); cfg.blockDim = dim3(G2_THREADS); cfg.dynamicSmemBytes = G2_SMEM;
    cudaLaunchKernelEx(&cfg, gemm2_kernel, mHH, mWd, mH, out);
}
```

```cpp
#include <cuda_runtime.h>
#include <cuda_bf16.h>
#include <cuda.h>
#include <stdint.h>

typedef __nv_bfloat16 bf16;
constexpr int S_ = 2048, D_ = 512, F_ = 1792;

constexpr int HT_PITCH = S_ + 64;
__device__ __align__(128) bf16 g_hT[D_ * HT_PITCH];
__device__ bf16 g_hh[S_ * F_];
__device__ __align__(128) float g_st1[S_ + S_ / 2];
__device__ float g_colsum[2 * F_];
__device__ unsigned int g_cnt;

#define TM(k, i)
#define TR(k, i)
__device__ __forceinline__ uint32_t smem_u32(const void* p) { return (uint32_t)__cvta_generic_to_shared(p); }
__device__ __forceinline__ float bf16r(float x) { return __bfloat162float(__float2bfloat16_rn(x)); }
__device__ __forceinline__ float bf_lo(uint32_t w) { return __uint_as_float(w << 16); }
__device__ __forceinline__ float bf_hi(uint32_t w) { return __uint_as_float(w & 0xffff0000u); }
__device__ __forceinline__ uint32_t pack_bf16(float lo, float hi) {
    __nv_bfloat162 v = __floats2bfloat162_rn(lo, hi);
    return *reinterpret_cast<uint32_t*>(&v);
}
__device__ __forceinline__ uint32_t hmul2(uint32_t a, uint32_t b) {
    __nv_bfloat162 r = __hmul2_rn(*reinterpret_cast<__nv_bfloat162*>(&a), *reinterpret_cast<__nv_bfloat162*>(&b));
    return *reinterpret_cast<uint32_t*>(&r);
}
__device__ __forceinline__ uint32_t hadd2(uint32_t a, uint32_t b) {
    __nv_bfloat162 r = __hadd2_rn(*reinterpret_cast<__nv_bfloat162*>(&a), *reinterpret_cast<__nv_bfloat162*>(&b));
    return *reinterpret_cast<uint32_t*>(&r);
}
__device__ __forceinline__ uint4 ldg128(const void* p) {
    uint4 r; asm volatile("ld.global.nc.v4.u32 {%0,%1,%2,%3}, [%4];" : "=r"(r.x), "=r"(r.y), "=r"(r.z), "=r"(r.w) : "l"(p)); return r;
}
__device__ __forceinline__ uint4 ldcg128(const void* p) {
    uint4 r; asm volatile("ld.global.cg.v4.u32 {%0,%1,%2,%3}, [%4];" : "=r"(r.x), "=r"(r.y), "=r"(r.z), "=r"(r.w) : "l"(p)); return r;
}
__device__ __forceinline__ uint32_t ldg16(const void* p) {
    unsigned short r; asm volatile("ld.global.nc.u16 %0, [%1];" : "=h"(r) : "l"(p)); return (uint32_t)r;
}
__device__ __forceinline__ void mbar_init(uint32_t bar, int cnt) { asm volatile("mbarrier.init.shared::cta.b64 [%0], %1;" :: "r"(bar), "r"(cnt)); }
__device__ __forceinline__ void mbar_expect_tx(uint32_t bar, uint32_t bytes) { asm volatile("mbarrier.arrive.expect_tx.shared::cta.b64 _, [%0], %1;" :: "r"(bar), "r"(bytes) : "memory"); }
__device__ __forceinline__ void mbar_arrive(uint32_t bar) { asm volatile("mbarrier.arrive.shared::cta.b64 _, [%0];" :: "r"(bar) : "memory"); }
__device__ __forceinline__ void mbar_arrive_cluster(uint32_t bar, uint32_t cta) {
    asm volatile("{\n.reg .b32 ra;\nmapa.shared::cluster.u32 ra, %0, %1;\nmbarrier.arrive.shared::cluster.b64 _, [ra];\n}" :: "r"(bar), "r"(cta) : "memory");
}
__device__ __forceinline__ void mbar_wait(uint32_t bar, uint32_t parity) {
    asm volatile("{\n.reg .pred P1;\nLAB_WAIT:\nmbarrier.try_wait.parity.shared::cta.b64 P1, [%0], %1;\n@P1 bra DONE;\nbra LAB_WAIT;\nDONE:\n}" :: "r"(bar), "r"(parity) : "memory");
}
__device__ __forceinline__ void mbar_wait_cluster(uint32_t bar, uint32_t parity) {
    asm volatile("{\n.reg .pred P1;\nLAB_WAIT:\nmbarrier.try_wait.parity.acquire.cluster.shared::cta.b64 P1, [%0], %1;\n@P1 bra DONE;\nbra LAB_WAIT;\nDONE:\n}" :: "r"(bar), "r"(parity) : "memory");
}
__device__ __forceinline__ void tma_load_2d(uint32_t dst, const CUtensorMap* map, uint32_t bar, int c0, int c1) {
    asm volatile("cp.async.bulk.tensor.2d.shared::cluster.global.mbarrier::complete_tx::bytes [%0], [%1, {%3, %4}], [%2];"
        :: "r"(dst), "l"(map), "r"(bar), "r"(c0), "r"(c1) : "memory");
}
__device__ __forceinline__ void tma_load_2d_mc(uint32_t dst, const CUtensorMap* map, uint32_t bar, int c0, int c1, uint16_t mask) {
    asm volatile("cp.async.bulk.tensor.2d.shared::cluster.global.mbarrier::complete_tx::bytes.multicast::cluster [%0], [%1, {%3, %4}], [%2], %5;"
        :: "r"(dst), "l"(map), "r"(bar), "r"(c0), "r"(c1), "h"(mask) : "memory");
}
__device__ __forceinline__ void tma_load_3d_mc(uint32_t dst, const CUtensorMap* map, uint32_t bar, int c0, int c1, int c2, uint16_t mask) {
    asm volatile("cp.async.bulk.tensor.3d.shared::cluster.global.mbarrier::complete_tx::bytes.multicast::cluster [%0], [%1, {%3, %4, %5}], [%2], %6;"
        :: "r"(dst), "l"(map), "r"(bar), "r"(c0), "r"(c1), "r"(c2), "h"(mask) : "memory");
}
__device__ __forceinline__ void tma_load_3d(uint32_t dst, const CUtensorMap* map, uint32_t bar, int c0, int c1, int c2) {
    asm volatile("cp.async.bulk.tensor.3d.shared::cluster.global.mbarrier::complete_tx::bytes [%0], [%1, {%3, %4, %5}], [%2];"
        :: "r"(dst), "l"(map), "r"(bar), "r"(c0), "r"(c1), "r"(c2) : "memory");
}
__device__ __forceinline__ void cluster_arrive() { asm volatile("barrier.cluster.arrive.aligned;" ::: "memory"); }
__device__ __forceinline__ void cluster_arrive_relaxed() { asm volatile("barrier.cluster.arrive.relaxed.aligned;" ::: "memory"); }
__device__ __forceinline__ void cluster_wait() { asm volatile("barrier.cluster.wait.aligned;" ::: "memory"); }
__device__ __forceinline__ uint32_t mapa(uint32_t addr, uint32_t cta) {
    uint32_t r; asm volatile("mapa.shared::cluster.u32 %0, %1, %2;" : "=r"(r) : "r"(addr), "r"(cta)); return r;
}
__device__ __forceinline__ void st_async_v2(uint32_t addr, uint32_t a, uint32_t b, uint32_t rbar) {
    asm volatile("st.async.weak.shared::cluster.mbarrier::complete_tx::bytes.v2.b32 [%0], {%1, %2}, [%3];" :: "r"(addr), "r"(a), "r"(b), "r"(rbar) : "memory");
}
__device__ __forceinline__ void st_async_v4f(uint32_t addr, float a, float b, float c, float d, uint32_t rbar) {
    asm volatile("st.async.weak.shared::cluster.mbarrier::complete_tx::bytes.v4.f32 [%0], {%1, %2, %3, %4}, [%5];" :: "r"(addr), "f"(a), "f"(b), "f"(c), "f"(d), "r"(rbar) : "memory");
}
__device__ __forceinline__ void wgmma_fence() { asm volatile("wgmma.fence.sync.aligned;" ::: "memory"); }
__device__ __forceinline__ void wgmma_commit() { asm volatile("wgmma.commit_group.sync.aligned;" ::: "memory"); }
template <int N> __device__ __forceinline__ void wgmma_wait() { asm volatile("wgmma.wait_group.sync.aligned %0;" :: "n"(N) : "memory"); }
__device__ __forceinline__ uint64_t make_desc(uint32_t addr, uint32_t lbo_bytes, uint32_t sbo_bytes, uint32_t layout) {
    return (uint64_t)((addr & 0x3FFFF) >> 4) | ((uint64_t)(lbo_bytes >> 4) << 16) | ((uint64_t)(sbo_bytes >> 4) << 32) | ((uint64_t)layout << 62);
}
template <int R> __device__ __forceinline__ void reg_alloc() { asm volatile("setmaxnreg.inc.sync.aligned.u32 %0;" :: "n"(R)); }
template <int R> __device__ __forceinline__ void reg_dealloc() { asm volatile("setmaxnreg.dec.sync.aligned.u32 %0;" :: "n"(R)); }
__device__ __forceinline__ void pdl_launch() { asm volatile("griddepcontrol.launch_dependents;" ::: "memory"); }
__device__ __forceinline__ void pdl_wait() { asm volatile("griddepcontrol.wait;" ::: "memory"); }
__device__ __forceinline__ void prefetch_map(const CUtensorMap* m) { asm volatile("prefetch.tensormap [%0];" :: "l"(m) : "memory"); }
__device__ __forceinline__ void named_bar(int id, int n) { asm volatile("bar.sync %0, %1;" :: "r"(id), "r"(n) : "memory"); }

__device__ __forceinline__ void wgmma_m64n256k16_ss(float (&d)[128], uint64_t descA, uint64_t descB, int scaleD) {
    asm volatile("{\n.reg .pred p;\nsetp.ne.b32 p, %130, 0;\n"
        "wgmma.mma_async.sync.aligned.m64n256k16.f32.bf16.bf16 {%0, %1, %2, %3, %4, %5, %6, %7, %8, %9, %10, %11, %12, %13, %14, %15, %16, %17, %18, %19, %20, %21, %22, %23, %24, %25, %26, %27, %28, %29, %30, %31, %32, %33, %34, %35, %36, %37, %38, %39, %40, %41, %42, %43, %44, %45, %46, %47, %48, %49, %50, %51, %52, %53, %54, %55, %56, %57, %58, %59, %60, %61, %62, %63, %64, %65, %66, %67, %68, %69, %70, %71, %72, %73, %74, %75, %76, %77, %78, %79, %80, %81, %82, %83, %84, %85, %86, %87, %88, %89, %90, %91, %92, %93, %94, %95, %96, %97, %98, %99, %100, %101, %102, %103, %104, %105, %106, %107, %108, %109, %110, %111, %112, %113, %114, %115, %116, %117, %118, %119, %120, %121, %122, %123, %124, %125, %126, %127}, %128, %129, p, 1, 1, 1, 1;\n}\n"
        : "+f"(d[0]), "+f"(d[1]), "+f"(d[2]), "+f"(d[3]), "+f"(d[4]), "+f"(d[5]), "+f"(d[6]), "+f"(d[7]), "+f"(d[8]), "+f"(d[9]), "+f"(d[10]), "+f"(d[11]), "+f"(d[12]), "+f"(d[13]), "+f"(d[14]), "+f"(d[15]), "+f"(d[16]), "+f"(d[17]), "+f"(d[18]), "+f"(d[19]), "+f"(d[20]), "+f"(d[21]), "+f"(d[22]), "+f"(d[23]), "+f"(d[24]), "+f"(d[25]), "+f"(d[26]), "+f"(d[27]), "+f"(d[28]), "+f"(d[29]), "+f"(d[30]), "+f"(d[31]), "+f"(d[32]), "+f"(d[33]), "+f"(d[34]), "+f"(d[35]), "+f"(d[36]), "+f"(d[37]), "+f"(d[38]), "+f"(d[39]), "+f"(d[40]), "+f"(d[41]), "+f"(d[42]), "+f"(d[43]), "+f"(d[44]), "+f"(d[45]), "+f"(d[46]), "+f"(d[47]), "+f"(d[48]), "+f"(d[49]), "+f"(d[50]), "+f"(d[51]), "+f"(d[52]), "+f"(d[53]), "+f"(d[54]), "+f"(d[55]), "+f"(d[56]), "+f"(d[57]), "+f"(d[58]), "+f"(d[59]), "+f"(d[60]), "+f"(d[61]), "+f"(d[62]), "+f"(d[63]), "+f"(d[64]), "+f"(d[65]), "+f"(d[66]), "+f"(d[67]), "+f"(d[68]), "+f"(d[69]), "+f"(d[70]), "+f"(d[71]), "+f"(d[72]), "+f"(d[73]), "+f"(d[74]), "+f"(d[75]), "+f"(d[76]), "+f"(d[77]), "+f"(d[78]), "+f"(d[79]), "+f"(d[80]), "+f"(d[81]), "+f"(d[82]), "+f"(d[83]), "+f"(d[84]), "+f"(d[85]), "+f"(d[86]), "+f"(d[87]), "+f"(d[88]), "+f"(d[89]), "+f"(d[90]), "+f"(d[91]), "+f"(d[92]), "+f"(d[93]), "+f"(d[94]), "+f"(d[95]), "+f"(d[96]), "+f"(d[97]), "+f"(d[98]), "+f"(d[99]), "+f"(d[100]), "+f"(d[101]), "+f"(d[102]), "+f"(d[103]), "+f"(d[104]), "+f"(d[105]), "+f"(d[106]), "+f"(d[107]), "+f"(d[108]), "+f"(d[109]), "+f"(d[110]), "+f"(d[111]), "+f"(d[112]), "+f"(d[113]), "+f"(d[114]), "+f"(d[115]), "+f"(d[116]), "+f"(d[117]), "+f"(d[118]), "+f"(d[119]), "+f"(d[120]), "+f"(d[121]), "+f"(d[122]), "+f"(d[123]), "+f"(d[124]), "+f"(d[125]), "+f"(d[126]), "+f"(d[127])
        : "l"(descA), "l"(descB), "r"(scaleD));
}

__device__ __forceinline__ void wgmma_m64n192k16_ss(float (&d)[96], uint64_t descA, uint64_t descB, int scaleD) {
    asm volatile("{\n.reg .pred p;\nsetp.ne.b32 p, %98, 0;\n"
        "wgmma.mma_async.sync.aligned.m64n192k16.f32.bf16.bf16 {%0, %1, %2, %3, %4, %5, %6, %7, %8, %9, %10, %11, %12, %13, %14, %15, %16, %17, %18, %19, %20, %21, %22, %23, %24, %25, %26, %27, %28, %29, %30, %31, %32, %33, %34, %35, %36, %37, %38, %39, %40, %41, %42, %43, %44, %45, %46, %47, %48, %49, %50, %51, %52, %53, %54, %55, %56, %57, %58, %59, %60, %61, %62, %63, %64, %65, %66, %67, %68, %69, %70, %71, %72, %73, %74, %75, %76, %77, %78, %79, %80, %81, %82, %83, %84, %85, %86, %87, %88, %89, %90, %91, %92, %93, %94, %95}, %96, %97, p, 1, 1, 1, 1;\n}\n"
        : "+f"(d[0]), "+f"(d[1]), "+f"(d[2]), "+f"(d[3]), "+f"(d[4]), "+f"(d[5]), "+f"(d[6]), "+f"(d[7]), "+f"(d[8]), "+f"(d[9]), "+f"(d[10]), "+f"(d[11]), "+f"(d[12]), "+f"(d[13]), "+f"(d[14]), "+f"(d[15]), "+f"(d[16]), "+f"(d[17]), "+f"(d[18]), "+f"(d[19]), "+f"(d[20]), "+f"(d[21]), "+f"(d[22]), "+f"(d[23]), "+f"(d[24]), "+f"(d[25]), "+f"(d[26]), "+f"(d[27]), "+f"(d[28]), "+f"(d[29]), "+f"(d[30]), "+f"(d[31]), "+f"(d[32]), "+f"(d[33]), "+f"(d[34]), "+f"(d[35]), "+f"(d[36]), "+f"(d[37]), "+f"(d[38]), "+f"(d[39]), "+f"(d[40]), "+f"(d[41]), "+f"(d[42]), "+f"(d[43]), "+f"(d[44]), "+f"(d[45]), "+f"(d[46]), "+f"(d[47]), "+f"(d[48]), "+f"(d[49]), "+f"(d[50]), "+f"(d[51]), "+f"(d[52]), "+f"(d[53]), "+f"(d[54]), "+f"(d[55]), "+f"(d[56]), "+f"(d[57]), "+f"(d[58]), "+f"(d[59]), "+f"(d[60]), "+f"(d[61]), "+f"(d[62]), "+f"(d[63]), "+f"(d[64]), "+f"(d[65]), "+f"(d[66]), "+f"(d[67]), "+f"(d[68]), "+f"(d[69]), "+f"(d[70]), "+f"(d[71]), "+f"(d[72]), "+f"(d[73]), "+f"(d[74]), "+f"(d[75]), "+f"(d[76]), "+f"(d[77]), "+f"(d[78]), "+f"(d[79]), "+f"(d[80]), "+f"(d[81]), "+f"(d[82]), "+f"(d[83]), "+f"(d[84]), "+f"(d[85]), "+f"(d[86]), "+f"(d[87]), "+f"(d[88]), "+f"(d[89]), "+f"(d[90]), "+f"(d[91]), "+f"(d[92]), "+f"(d[93]), "+f"(d[94]), "+f"(d[95])
        : "l"(descA), "l"(descB), "r"(scaleD));
}

__device__ __forceinline__ void wgmma_m64n128k16_ss(float (&d)[64], uint64_t descA, uint64_t descB, int scaleD) {
    asm volatile("{\n.reg .pred p;\nsetp.ne.b32 p, %66, 0;\n"
        "wgmma.mma_async.sync.aligned.m64n128k16.f32.bf16.bf16 {%0, %1, %2, %3, %4, %5, %6, %7, %8, %9, %10, %11, %12, %13, %14, %15, %16, %17, %18, %19, %20, %21, %22, %23, %24, %25, %26, %27, %28, %29, %30, %31, %32, %33, %34, %35, %36, %37, %38, %39, %40, %41, %42, %43, %44, %45, %46, %47, %48, %49, %50, %51, %52, %53, %54, %55, %56, %57, %58, %59, %60, %61, %62, %63}, %64, %65, p, 1, 1, 0, 1;\n}\n"
        : "+f"(d[0]), "+f"(d[1]), "+f"(d[2]), "+f"(d[3]), "+f"(d[4]), "+f"(d[5]), "+f"(d[6]), "+f"(d[7]), "+f"(d[8]), "+f"(d[9]), "+f"(d[10]), "+f"(d[11]), "+f"(d[12]), "+f"(d[13]), "+f"(d[14]), "+f"(d[15]), "+f"(d[16]), "+f"(d[17]), "+f"(d[18]), "+f"(d[19]), "+f"(d[20]), "+f"(d[21]), "+f"(d[22]), "+f"(d[23]), "+f"(d[24]), "+f"(d[25]), "+f"(d[26]), "+f"(d[27]), "+f"(d[28]), "+f"(d[29]), "+f"(d[30]), "+f"(d[31]), "+f"(d[32]), "+f"(d[33]), "+f"(d[34]), "+f"(d[35]), "+f"(d[36]), "+f"(d[37]), "+f"(d[38]), "+f"(d[39]), "+f"(d[40]), "+f"(d[41]), "+f"(d[42]), "+f"(d[43]), "+f"(d[44]), "+f"(d[45]), "+f"(d[46]), "+f"(d[47]), "+f"(d[48]), "+f"(d[49]), "+f"(d[50]), "+f"(d[51]), "+f"(d[52]), "+f"(d[53]), "+f"(d[54]), "+f"(d[55]), "+f"(d[56]), "+f"(d[57]), "+f"(d[58]), "+f"(d[59]), "+f"(d[60]), "+f"(d[61]), "+f"(d[62]), "+f"(d[63])
        : "l"(descA), "l"(descB), "r"(scaleD));
}

__device__ __forceinline__ void quad_transpose(uint32_t& r0, uint32_t& r1, uint32_t& r2, uint32_t& r3, int t) {
    const bool o1 = t & 1, o2 = t & 2;
    uint32_t x, y;
    x = o1 ? r0 : r1; y = __shfl_xor_sync(0xffffffffu, x, 1); if (o1) r0 = y; else r1 = y;
    x = o1 ? r2 : r3; y = __shfl_xor_sync(0xffffffffu, x, 1); if (o1) r2 = y; else r3 = y;
    x = o2 ? r0 : r2; y = __shfl_xor_sync(0xffffffffu, x, 2); if (o2) r0 = y; else r2 = y;
    x = o2 ? r1 : r3; y = __shfl_xor_sync(0xffffffffu, x, 2); if (o2) r1 = y; else r3 = y;
}

__device__ __forceinline__ float warp_sum(float s) {
#pragma unroll
    for (int o = 16; o > 0; o >>= 1) s += __shfl_xor_sync(0xffffffffu, s, o);
    return s;
}
__device__ __forceinline__ uint32_t hsub2(uint32_t a, uint32_t b) {
    __nv_bfloat162 r = __hsub2_rn(*reinterpret_cast<__nv_bfloat162*>(&a), *reinterpret_cast<__nv_bfloat162*>(&b));
    return *reinterpret_cast<uint32_t*>(&r);
}
__device__ __forceinline__ void ln_stats2(const uint32_t (&x)[2][8], float2 (&st)[2]) {
    float piv[2], s[2], ss[2];
#pragma unroll
    for (int r = 0; r < 2; r++) piv[r] = __shfl_sync(0xffffffffu, bf_lo(x[r][0]), 0);
#pragma unroll
    for (int r = 0; r < 2; r++) {
        float s0 = 0.f, s1 = 0.f, q0 = 0.f, q1 = 0.f;
#pragma unroll
        for (int i = 0; i < 8; i++) {
            const float d0 = bf_lo(x[r][i]) - piv[r], d1 = bf_hi(x[r][i]) - piv[r];
            s0 += d0; s1 += d1; q0 = fmaf(d0, d0, q0); q1 = fmaf(d1, d1, q1);
        }
        s[r] = s0 + s1; ss[r] = q0 + q1;
    }
#pragma unroll
    for (int o = 16; o > 0; o >>= 1) {
#pragma unroll
        for (int r = 0; r < 2; r++) { s[r] += __shfl_xor_sync(0xffffffffu, s[r], o); ss[r] += __shfl_xor_sync(0xffffffffu, ss[r], o); }
    }
#pragma unroll
    for (int r = 0; r < 2; r++) {
        const float md = s[r] * (1.0f / D_);
        const float var = bf16r(fmaxf(fmaf(-md, md, ss[r] * (1.0f / D_)), 0.f));
        st[r] = make_float2(bf16r(piv[r] + md), 1.0f / bf16r(sqrtf(bf16r(var + 1e-5f))));
    }
}
__device__ __forceinline__ void ln_apply(const uint32_t (&x)[8], float2 st, uint32_t (&o)[8]) {
    const uint32_t m2 = pack_bf16(st.x, st.x);
#pragma unroll
    for (int i = 0; i < 8; i++) {
        const uint32_t d = hsub2(x[i], m2);
        o[i] = pack_bf16(bf_lo(d) * st.y, bf_hi(d) * st.y);
    }
}

constexpr int K1_THREADS = 352;
constexpr int UT_PAD = 128;
constexpr int UT_LEN = UT_PAD + S_;
constexpr int KR_LEN = 2080;
constexpr int YP_LEN = S_ + (S_ / 32) * 8;

struct __align__(128) K1Smem {
    bf16 uT[4][UT_LEN];
    bf16 xT[4][S_];
    bf16 kr[4][2][KR_LEN];
    float yP[4][YP_LEN];
    alignas(128) float st[S_ + S_ / 2];
    alignas(128) uint4 wS[512][4];
    alignas(128) uint4 kS[1056];
    alignas(128) uint4 vS[1024];
    alignas(128) uint4 qS[1024];
    alignas(128) bf16 sS[4][S_];
    uint64_t bar, bar2, bar3, bar4, bar5, bar6;
};

__device__ __forceinline__ void mma16816(float (&c)[4], uint32_t a0, uint32_t a1, uint32_t a2, uint32_t a3, uint32_t b0, uint32_t b1) {
    asm volatile("mma.sync.aligned.m16n8k16.row.col.f32.bf16.bf16.f32 {%0,%1,%2,%3}, {%4,%5,%6,%7}, {%8,%9}, {%0,%1,%2,%3};"
        : "+f"(c[0]), "+f"(c[1]), "+f"(c[2]), "+f"(c[3])
        : "r"(a0), "r"(a1), "r"(a2), "r"(a3), "r"(b0), "r"(b1));
}
__device__ __forceinline__ void ldsm_x4(uint32_t& r0, uint32_t& r1, uint32_t& r2, uint32_t& r3, uint32_t addr) {
    asm volatile("ldmatrix.sync.aligned.m8n8.x4.shared.b16 {%0,%1,%2,%3}, [%4];" : "=r"(r0), "=r"(r1), "=r"(r2), "=r"(r3) : "r"(addr) : "memory");
}

__device__ __forceinline__ void conv_mma(const bf16* uTc, const bf16* krlane, float (&acc)[16][4], int lane, int half) {
    const int lrow = lane & 7, lk = (lane >> 3) & 1, lt = lane >> 4;
    const uint32_t ubase = smem_u32(uTc) + (UT_PAD + 16 * (8 * lt + lrow) + 8 * lk) * 2;
#pragma unroll 1
    for (int pp = 0; pp < 4; pp++) {
        const int p = half * 4 + pp;
        uint32_t U[16][2];
#pragma unroll
        for (int j = 0; j < 16; j += 2) ldsm_x4(U[j][0], U[j][1], U[j + 1][0], U[j + 1][1], ubase + (j * 128 - p * 16) * 2);
        const uint32_t* kp = reinterpret_cast<const uint32_t*>(krlane - 16 * p);
        const volatile uint32_t* kpv = kp;
        uint32_t a0 = kp[0], a1 = kp[-4], a2 = kp[4], a3 = kpv[0];
#pragma unroll
        for (int q = 0; q < 16; q++) {
            uint32_t b0 = 0, b1 = 0, b2 = 0, b3 = 0;
            if (q < 15) { b0 = kp[-64 * (q + 1)]; b1 = kp[-64 * (q + 1) - 4]; b2 = kp[-64 * (q + 1) + 4]; b3 = kpv[-64 * (q + 1)]; }
#pragma unroll
            for (int n = 15; n >= q; n--) mma16816(acc[n], a0, a1, a2, a3, U[n - q][0], U[n - q][1]);
            a0 = b0; a1 = b1; a2 = b2; a3 = b3;
        }
    }
}

__device__ __forceinline__ void cp_async16(uint32_t dst, const void* src) {
    asm volatile("cp.async.cg.shared.global [%0], [%1], 16;" :: "r"(dst), "l"(src) : "memory");
}

__global__ void __cluster_dims__(2, 1, 1) __launch_bounds__(K1_THREADS, 1)
conv_kernel(const bf16* __restrict__ q, const __grid_constant__ CUtensorMap mapK, const __grid_constant__ CUtensorMap mapV,
            const __grid_constant__ CUtensorMap mapQ, const bf16* __restrict__ shift_k, const bf16* __restrict__ ssm_k, const bf16* __restrict__ ssm_D,
            const __grid_constant__ CUtensorMap mapWg, const __grid_constant__ CUtensorMap mapWu, const bf16* __restrict__ wd) {
    extern __shared__ __align__(1024) uint8_t smem_raw[];
    pdl_launch();
    K1Smem& sm = *reinterpret_cast<K1Smem*>(smem_raw);
    const int tid = threadIdx.x, lane = tid & 31, warp = tid >> 5;
    const int bid = blockIdx.x;
    const int rank = bid & 1;
    const int c0 = 8 * (bid >> 1);
    const int cown = c0 + 4 * rank;
#define TMT 0
    TM(0, 0);
    const uint32_t bar = smem_u32(&sm.bar);
    if (tid == 0) {
        mbar_init(bar, 1);
        mbar_init(bar + 8, 1);
        mbar_init(bar + 16, 1);
        mbar_init(bar + 24, 1);
        mbar_init(bar + 32, 1);
        mbar_init(bar + 40, 1);
        asm volatile("fence.mbarrier_init.release.cluster;" ::: "memory");
        mbar_expect_tx(bar + 32, 1056 * 16 + 1024 * 16 + 4 * S_ * 2);
        for (int i = 0; i < 6; i++) tma_load_2d(smem_u32(&sm.kS[176 * i]), &mapK, bar + 32, c0, 1024 * rank - 8 + 176 * i);
        for (int i = 0; i < 4; i++) tma_load_2d(smem_u32(&sm.vS[256 * i]), &mapV, bar + 32, c0, 1024 * rank + 256 * i);
        asm volatile("cp.async.bulk.shared::cluster.global.mbarrier::complete_tx::bytes [%0], [%1], %2, [%3];"
            :: "r"(smem_u32(&sm.sS[0][0])), "l"(ssm_k + (size_t)cown * S_), "r"(4 * S_ * 2), "r"(bar + 32) : "memory");
        mbar_expect_tx(bar, 1024 * 4 * 2);
        mbar_expect_tx(bar + 8, 1024 * 4 * 2);
    }
    cluster_arrive_relaxed();

    if (warp < 8) {
        const int s0 = 1024 * rank + 4 * tid;
        uint4 kk[7], vv[4], qq[4], sw[4];
#pragma unroll
        for (int i = 0; i < 4; i++) sw[i] = ldg128(shift_k + (size_t)c0 * 4 + 8 * i);
        const uint32_t dval = ldg16(ssm_D + cown + (warp >> 1));
        if (tid < 64) *reinterpret_cast<uint4*>(&sm.uT[tid >> 4][(tid & 15) * 8]) = make_uint4(0, 0, 0, 0);
        named_bar(8, 352);
        mbar_wait(bar + 32, 0);
#pragma unroll
        for (int i = 0; i < 7; i++) kk[i] = sm.kS[4 * tid + 5 + i];
#pragma unroll
        for (int i = 0; i < 4; i++) vv[i] = sm.vS[4 * tid + i];
        uint4 kq[4]; uint32_t nx[4];
#pragma unroll
        for (int c = 0; c < 4; c++) {
            kq[c] = *reinterpret_cast<const uint4*>(&sm.sS[c][8 * tid]);
            nx[c] = (tid < 255) ? (uint32_t)*reinterpret_cast<const unsigned short*>(&sm.sS[c][8 * tid + 8]) : 0u;
        }
        uint32_t kvw[4][4];
        const uint32_t* kkw = reinterpret_cast<const uint32_t*>(kk);
        const uint32_t* vvw = reinterpret_cast<const uint32_t*>(vv);
        const uint32_t* qqw = reinterpret_cast<const uint32_t*>(qq);
#pragma unroll
        for (int i2 = 0; i2 < 4; i2++) {
            const uint32_t t0 = __byte_perm(sw[i2].x, sw[i2].z, 0x5410), t1 = __byte_perm(sw[i2].x, sw[i2].z, 0x7632);
            const uint32_t t2 = __byte_perm(sw[i2].y, sw[i2].w, 0x5410), t3 = __byte_perm(sw[i2].y, sw[i2].w, 0x7632);
#pragma unroll
            for (int r = 0; r < 4; r++) {
                uint32_t a = hmul2(kkw[(r + 0) * 4 + i2], t3);
                a = hadd2(a, hmul2(kkw[(r + 1) * 4 + i2], t2));
                a = hadd2(a, hmul2(kkw[(r + 2) * 4 + i2], t1));
                a = hadd2(a, hmul2(kkw[(r + 3) * 4 + i2], t0));
                kvw[r][i2] = hmul2(a, vvw[r * 4 + i2]);
            }
        }
        TM(0, 1);
        cluster_wait();
        const uint32_t rbar = mapa(bar, (uint32_t)(rank ^ 1));
#pragma unroll
        for (int i2 = 0; i2 < 4; i2++) {
#pragma unroll
            for (int e = 0; e < 2; e++) {
                const uint32_t sel = e ? 0x7632 : 0x5410;
                const uint32_t w0 = __byte_perm(kvw[0][i2], kvw[1][i2], sel), w1 = __byte_perm(kvw[2][i2], kvw[3][i2], sel);
                const int cc = 2 * i2 + e;
                if ((cc >> 2) == rank) *reinterpret_cast<uint2*>(&sm.uT[cc & 3][UT_PAD + s0]) = make_uint2(w0, w1);
                else st_async_v2(mapa(smem_u32(&sm.uT[cc & 3][UT_PAD + s0]), (uint32_t)(rank ^ 1)), w0, w1, rbar);
            }
        }
#pragma unroll
        for (int c = 0; c < 4; c++) {
            uint4 a, b;
            a.x = __byte_perm(kq[c].w, 0, 0x1032); a.y = __byte_perm(kq[c].z, 0, 0x1032);
            a.z = __byte_perm(kq[c].y, 0, 0x1032); a.w = __byte_perm(kq[c].x, 0, 0x1032);
            b.x = __byte_perm(nx[c], kq[c].w, 0x7610); b.y = __byte_perm(kq[c].w, kq[c].z, 0x7610);
            b.z = __byte_perm(kq[c].z, kq[c].y, 0x7610); b.w = __byte_perm(kq[c].y, kq[c].x, 0x7610);
            *reinterpret_cast<uint4*>(&sm.kr[c][0][2040 - 8 * tid]) = a;
            *reinterpret_cast<uint4*>(&sm.kr[c][1][2040 - 8 * tid]) = b;
            if (tid == 0) {
                *reinterpret_cast<uint4*>(&sm.kr[c][1][2048]) = make_uint4(kq[c].x & 0xffffu, 0, 0, 0);
            } else if (tid < 8) {
                if (tid < 4) *reinterpret_cast<uint4*>(&sm.kr[c][1][2048 + 8 * tid]) = make_uint4(0, 0, 0, 0);
                else *reinterpret_cast<uint4*>(&sm.kr[c][0][2048 + 8 * (tid - 4)]) = make_uint4(0, 0, 0, 0);
            }
        }
        if (tid == 0) {
            mbar_expect_tx(bar + 40, 1024 * 16);
            for (int i = 0; i < 4; i++) tma_load_2d(smem_u32(&sm.qS[256 * i]), &mapQ, bar + 40, c0, 1024 * rank + 256 * i);
        }
        TM(0, 3);
        named_bar(6, 352);
        mbar_wait_cluster(bar, 0);
        TM(0, 4);

        const int ch = warp >> 1, half = warp & 1;
        const int g = lane >> 2, t = lane & 3;
        float acc[16][4];
#pragma unroll
        for (int i = 0; i < 16; i++) { acc[i][0] = acc[i][1] = acc[i][2] = acc[i][3] = 0.f; }
        const bf16* krlane = (g & 1) ? &sm.kr[ch][0][2047 - g + 2 * t] : &sm.kr[ch][1][2048 - g + 2 * t];
        conv_mma(sm.uT[ch], krlane, acc, lane, half);
        TM(0, 5);
        mbar_wait(bar + 40, 0);
#pragma unroll
        for (int i = 0; i < 4; i++) qq[i] = sm.qS[4 * tid + i];
#pragma unroll
        for (int i2 = 0; i2 < 4; i2++) {
#pragma unroll
            for (int e = 0; e < 2; e++) {
                const uint32_t sel = e ? 0x7632 : 0x5410;
                const uint32_t w0 = __byte_perm(qqw[i2], qqw[4 + i2], sel), w1 = __byte_perm(qqw[8 + i2], qqw[12 + i2], sel);
                const int cc = 2 * i2 + e;
                if ((cc >> 2) == rank) *reinterpret_cast<uint2*>(&sm.xT[cc & 3][s0]) = make_uint2(w0, w1);
                else st_async_v2(mapa(smem_u32(&sm.xT[cc & 3][s0]), (uint32_t)(rank ^ 1)), w0, w1, rbar + 8);
            }
        }
        float* yp = &sm.yP[ch][40 * t + g];
        if (half) {
#pragma unroll
            for (int n = 0; n < 16; n++) {
                yp[160 * n] = acc[n][0];
                yp[160 * n + 16] = acc[n][1];
                yp[160 * n + 8] = acc[n][2];
                yp[160 * n + 24] = acc[n][3];
            }
        }
        named_bar(1 + ch, 64);
        if (!half) {
#pragma unroll
            for (int n = 0; n < 16; n++) {
                yp[160 * n] += acc[n][0];
                yp[160 * n + 16] += acc[n][1];
                yp[160 * n + 8] += acc[n][2];
                yp[160 * n + 24] += acc[n][3];
            }
        }
        named_bar(7, 288);
        mbar_wait_cluster(bar + 8, 0);
        TM(0, 6);
        {
            const int tt = tid & 63;
            bf16* dst = g_hT + (size_t)(cown + ch) * HT_PITCH;
            const uint32_t d2 = dval * 0x10001u;
#pragma unroll
            for (int j = 0; j < 4; j++) {
                const int s = (j * 64 + tt) * 8;
                const float* src = &sm.yP[ch][s + (s >> 5) * 8];
                const float4 a = *reinterpret_cast<const float4*>(src), b = *reinterpret_cast<const float4*>(src + 4);
                const uint4 kv4 = *reinterpret_cast<const uint4*>(&sm.uT[ch][UT_PAD + s]);
                const uint4 x4 = *reinterpret_cast<const uint4*>(&sm.xT[ch][s]);
                const uint32_t y2[4] = {hadd2(pack_bf16(a.x, a.y), hmul2(kv4.x, d2)), hadd2(pack_bf16(a.z, a.w), hmul2(kv4.y, d2)),
                                        hadd2(pack_bf16(b.x, b.y), hmul2(kv4.z, d2)), hadd2(pack_bf16(b.z, b.w), hmul2(kv4.w, d2))};
                const uint32_t xw[4] = {x4.x, x4.y, x4.z, x4.w};
                const uint4 m4 = *reinterpret_cast<const uint4*>(&sm.st[S_ + s / 2]);
                const float4 ra = *reinterpret_cast<const float4*>(&sm.st[s]), rb4 = *reinterpret_cast<const float4*>(&sm.st[s + 4]);
                const uint32_t mw[4] = {m4.x, m4.y, m4.z, m4.w};
                const float rw[8] = {ra.x, ra.y, ra.z, ra.w, rb4.x, rb4.y, rb4.z, rb4.w};
                uint32_t o[4];
#pragma unroll
                for (int i = 0; i < 4; i++) {
                    const uint32_t d = hsub2(xw[i], mw[i]);
                    const uint32_t qn = pack_bf16(bf_lo(d) * rw[2 * i], bf_hi(d) * rw[2 * i + 1]);
                    o[i] = hadd2(xw[i], hmul2(qn, y2[i]));
                }
                *reinterpret_cast<uint4*>(dst + s) = make_uint4(o[0], o[1], o[2], o[3]);
            }
        }
        TM(0, 7);
    } else {
        named_bar(8, 352);
        cluster_wait();
        named_bar(6, 352);
        const uint32_t hbar = bar + 16;
        if (warp < 10) {
            {
                const int rr = 8 * (warp - 8);
                uint32_t xq[4][2][8];
#pragma unroll
                for (int r = 0; r < 8; r++) {
                    const uint4 qa = ldg128(q + (size_t)(16 * bid + rr + r) * D_ + 8 * lane);
                    const uint4 qb = ldg128(q + (size_t)(16 * bid + rr + r) * D_ + 8 * (lane + 32));
                    uint32_t* x = xq[r >> 1][r & 1];
                    x[0] = qa.x; x[1] = qa.y; x[2] = qa.z; x[3] = qa.w; x[4] = qb.x; x[5] = qb.y; x[6] = qb.z; x[7] = qb.w;
                }
#pragma unroll
                for (int r2 = 0; r2 < 4; r2++) {
                    float2 sa[2];
                    ln_stats2(xq[r2], sa);
                    if (lane == 0) {
                        *reinterpret_cast<float2*>(&g_st1[16 * bid + rr + 2 * r2]) = make_float2(sa[0].y, sa[1].y);
                        reinterpret_cast<uint32_t*>(&g_st1[S_])[(16 * bid + rr) / 2 + r2] = pack_bf16(sa[0].x, sa[1].x);
                    }
                }
            }
            if (lane == 0) { __threadfence(); atomicAdd(&g_cnt, 1u); }
            if (warp == 9) return;
            if (lane == 0) {
                unsigned int c; int spins = 0;
                while (true) {
                    asm volatile("ld.acquire.gpu.global.u32 %0, [%1];" : "=r"(c) : "l"(&g_cnt) : "memory");
                    if (c >= 2 * gridDim.x || ++spins > (1 << 22)) break;
                    __nanosleep(200);
                }
                asm volatile("fence.proxy.async;" ::: "memory");
                mbar_expect_tx(hbar + 8, 12288);
                asm volatile("cp.async.bulk.shared::cluster.global.mbarrier::complete_tx::bytes [%0], [%1], %2, [%3];"
                    :: "r"(smem_u32(&sm.st[0])), "l"(&g_st1[0]), "r"(12288), "r"(hbar + 8) : "memory");
            }
            mbar_wait(hbar + 8, 0);
            named_bar(7, 288);
        } else {
            if (lane == 0) asm volatile("cp.async.bulk.prefetch.L2.global [%0], %1;" :: "l"(wd + (size_t)bid * 7168), "r"(14336) : "memory");
            if (bid < 112) {
                if (lane == 0) {
                    mbar_expect_tx(hbar, 32768);
                    const CUtensorMap* mw = (bid < 56) ? &mapWg : &mapWu;
                    const int col = 32 * ((bid < 56) ? bid : bid - 56);
                    tma_load_2d(smem_u32(&sm.wS[0][0]), mw, hbar, col, 0);
                    tma_load_2d(smem_u32(&sm.wS[256][0]), mw, hbar, col, 256);
                }
                mbar_wait(hbar, 0);
                const int cq = lane & 3, rgp = lane >> 2;
                float cs[8];
#pragma unroll
                for (int i = 0; i < 8; i++) cs[i] = 0.f;
#pragma unroll 4
                for (int r = 0; r < 64; r++) {
                    const uint4 w = sm.wS[r * 8 + rgp][cq];
                    cs[0] += bf_lo(w.x); cs[1] += bf_hi(w.x); cs[2] += bf_lo(w.y); cs[3] += bf_hi(w.y);
                    cs[4] += bf_lo(w.z); cs[5] += bf_hi(w.z); cs[6] += bf_lo(w.w); cs[7] += bf_hi(w.w);
                }
#pragma unroll
                for (int i = 0; i < 8; i++) {
                    cs[i] += __shfl_xor_sync(0xffffffffu, cs[i], 4);
                    cs[i] += __shfl_xor_sync(0xffffffffu, cs[i], 8);
                    cs[i] += __shfl_xor_sync(0xffffffffu, cs[i], 16);
                }
                if (lane < 4) {
                    *reinterpret_cast<float4*>(&g_colsum[32 * bid + lane * 8]) = make_float4(cs[0], cs[1], cs[2], cs[3]);
                    *reinterpret_cast<float4*>(&g_colsum[32 * bid + lane * 8 + 4]) = make_float4(cs[4], cs[5], cs[6], cs[7]);
                }
            }
        }
    }
#undef TMT
}

constexpr int G1_THREADS = 384;
constexpr int G1_STAGES = 3;
constexpr int G1_A_BYTES = 8 * 16384;
constexpr int G1_B_STAGE = 32768;
constexpr int G1_OFF_B = G1_A_BYTES;
constexpr int G1_OFF_STATS = G1_OFF_B + G1_STAGES * G1_B_STAGE;
constexpr int G1_OFF_CS = G1_OFF_STATS + 1024;
constexpr int G1_OFF_BAR = G1_OFF_CS + 1792;
constexpr int G1_SMEM = G1_OFF_BAR + 128;

__device__ __forceinline__ float tanh_fast(float x) { float t; asm("tanh.approx.f32 %0, %1;" : "=f"(t) : "f"(x)); return t; }

template <int NT>
__device__ __forceinline__ void g1_math(const float (&acc)[NT * 8], const float* cs_g, const float* cs_u, float2 st0, float2 st1, uint32_t (&P)[NT * 2], int t) {
    const float r0 = st0.y, r1 = st1.y, m0 = -st0.x * st0.y, m1 = -st1.x * st1.y;
#pragma unroll
    for (int j = 0; j < NT; j++) {
        const float2 cg = *reinterpret_cast<const float2*>(cs_g + 8 * j + 2 * t);
        const float2 cu = *reinterpret_cast<const float2*>(cs_u + 8 * j + 2 * t);
        float r[4];
#pragma unroll
        for (int e = 0; e < 4; e++) {
            const float rr = (e < 2) ? r0 : r1, mm = (e < 2) ? m0 : m1;
            const float gh = fmaf(acc[4 * j + e], 0.5f * rr, (0.5f * mm) * ((e & 1) ? cg.y : cg.x));
            const float uv = fmaf(acc[4 * (NT + j) + e], rr, mm * ((e & 1) ? cu.y : cu.x));
            r[e] = fmaf(tanh_fast(gh), 0.5f, 0.5f) * uv;
        }
        P[2 * j] = pack_bf16(r[0], r[1]);
        P[2 * j + 1] = pack_bf16(r[2], r[3]);
    }
}
template <int NT>
__device__ __forceinline__ void g1_store(uint32_t (&P)[NT * 2], bf16* out0, int t) {
#pragma unroll
    for (int j0 = 0; j0 < NT; j0 += 4) {
        quad_transpose(P[2 * j0], P[2 * j0 + 2], P[2 * j0 + 4], P[2 * j0 + 6], t);
        quad_transpose(P[2 * j0 + 1], P[2 * j0 + 3], P[2 * j0 + 5], P[2 * j0 + 7], t);
        *reinterpret_cast<uint4*>(out0 + 8 * (j0 + t)) = make_uint4(P[2 * j0], P[2 * j0 + 2], P[2 * j0 + 4], P[2 * j0 + 6]);
        *reinterpret_cast<uint4*>(out0 + 8 * F_ + 8 * (j0 + t)) = make_uint4(P[2 * j0 + 1], P[2 * j0 + 3], P[2 * j0 + 5], P[2 * j0 + 7]);
    }
}

__global__ void __cluster_dims__(2, 1, 1) __launch_bounds__(G1_THREADS, 1)
gemm1_kernel(const __grid_constant__ CUtensorMap mapA, const __grid_constant__ CUtensorMap mapG4, const __grid_constant__ CUtensorMap mapU4,
             const __grid_constant__ CUtensorMap mapG3, const __grid_constant__ CUtensorMap mapU3) {
    extern __shared__ __align__(1024) uint8_t smem_raw[];
    const uint32_t sb = smem_u32(smem_raw);
    const int tid = threadIdx.x, lane = tid & 31, warp = tid >> 5, wgi = tid >> 7;
    const int rank = blockIdx.x & 1;
    const int cb = blockIdx.x & 7, rb = blockIdx.x >> 3;
#define TMT 128
    TM(2, 0);
    pdl_launch();
    if (tid == 32) { prefetch_map(&mapA); prefetch_map(&mapG3); prefetch_map(&mapU3); }
    const uint32_t barA = sb + G1_OFF_BAR;
    const uint32_t barF = barA + 64;
    const uint32_t barE = barF + 8 * G1_STAGES;
    const uint32_t barS = barE + 8 * G1_STAGES;
    if (tid == 0) {
        for (int i = 0; i < 8; i++) mbar_init(barA + 8 * i, 1);
        for (int i = 0; i < G1_STAGES; i++) { mbar_init(barF + 8 * i, 1); mbar_init(barE + 8 * i, 2); }
        mbar_init(barS, 1);
        for (int i = 0; i < 8; i++) mbar_expect_tx(barA + 8 * i, 16384);
        asm volatile("fence.mbarrier_init.release.cluster;" ::: "memory");
    }
    __syncthreads();
    cluster_arrive_relaxed();

    if (wgi == 0) {
        reg_dealloc<40>();
        if (warp == 0) {
            cluster_wait();
            if (lane == 0) {
                int st = 0, ph = 1;
                for (int it = 0; it < 16; it++) {
                    const int kc = it & 7;
                    if (it == 2) {
                        pdl_wait();
                        for (int i = 0; i < 4; i++) {
                            const int c = 2 * i + rank;
                            tma_load_3d_mc(sb + c * 16384, &mapA, barA + 8 * c, 0, c * 64, rb * 2, (uint16_t)3);
                        }
                    }
                    mbar_wait(barE + 8 * st, ph);
                    const uint32_t dst = sb + G1_OFF_B + st * G1_B_STAGE;
                    if (it < 8) {
                        mbar_expect_tx(barF + 8 * st, 32768);
                        tma_load_3d(dst, &mapG4, barF + 8 * st, 0, kc * 64, cb * 7);
                        tma_load_3d(dst + 16384, &mapU4, barF + 8 * st, 0, kc * 64, cb * 7);
                    } else {
                        mbar_expect_tx(barF + 8 * st, 24576);
                        tma_load_3d(dst, &mapG3, barF + 8 * st, 0, kc * 64, cb * 7 + 4);
                        tma_load_3d(dst + 12288, &mapU3, barF + 8 * st, 0, kc * 64, cb * 7 + 4);
                    }
                    if (++st == G1_STAGES) { st = 0; ph ^= 1; }
                }
            }
            __syncwarp();
        } else if (warp == 1) {
            cluster_wait();
            pdl_wait();
            float* cs = reinterpret_cast<float*>(smem_raw + G1_OFF_CS);
            for (int i = lane; i < 448; i += 32) cs[i] = __ldcg((i < 224) ? &g_colsum[cb * 224 + i] : &g_colsum[F_ + cb * 224 + (i - 224)]);
            __syncwarp();
            if (lane == 0) mbar_arrive(barS);
        } else {
            cluster_wait();
        }
    } else {
        reg_alloc<232>();
        cluster_wait();
        const int cw = wgi - 1;
        const int g = lane >> 2, t = lane & 3, wl = warp & 3, tl = tid & 127;
        bf16* outp = g_hh + (size_t)(rb * 128 + cw * 64 + wl * 16 + g) * F_ + cb * 224;
        const float* cs = reinterpret_cast<const float*>(smem_raw + G1_OFF_CS);
        int st = 0, ph = 0;
        float2 st0, st1;
        uint32_t P1[32];
        {
            float acc[128];
            const int kq = lane >> 3, mp = lane & 7;
            const uint8_t* sbase = smem_raw + cw * 8192 + kq * 128 + (mp & 3) * 4;
            const int mc = 2 * wl + (mp >> 2);
            float p0 = 0.f, p1 = 0.f, s0 = 0.f, s1 = 0.f, q0 = 0.f, q1 = 0.f;
#pragma unroll 1
            for (int kc = 0; kc < 8; kc++) {
                mbar_wait(barA + 8 * kc, 0);
                mbar_wait(barF + 8 * st, ph);
                if (tl == 0 && cw == 0) TR(1, kc);
                wgmma_fence();
                const uint32_t aaddr = sb + kc * 16384 + cw * 8192;
                const uint32_t baddr = sb + G1_OFF_B + st * G1_B_STAGE;
#pragma unroll
                for (int kk = 0; kk < 4; kk++)
                    wgmma_m64n256k16_ss(acc, make_desc(aaddr + kk * 2048, 8192, 1024, 1), make_desc(baddr + kk * 1024, 4096, 512, 2), (kc | kk) != 0);
                wgmma_commit();
                if (kc == 0) {
                    const uint32_t w = *reinterpret_cast<const uint32_t*>(smem_raw + cw * 8192 + (mc << 4) + (mp & 3) * 4);
                    p0 = bf_lo(w); p1 = bf_hi(w);
                }
#pragma unroll
                for (int i = 0; i < 16; i++) {
                    const int kr = 4 * i;
                    const uint32_t w = *reinterpret_cast<const uint32_t*>(sbase + kc * 16384 + kr * 128 + ((mc ^ ((kr + kq) & 7)) << 4));
                    const float d0 = bf_lo(w) - p0, d1 = bf_hi(w) - p1;
                    s0 += d0; s1 += d1; q0 = fmaf(d0, d0, q0); q1 = fmaf(d1, d1, q1);
                }
                wgmma_wait<0>();
                if (tl == 0) mbar_arrive(barE + 8 * st);
                if (++st == G1_STAGES) { st = 0; ph ^= 1; }
            }
            TM(2, 1);
            {
#pragma unroll
                for (int o = 8; o <= 16; o <<= 1) {
                    s0 += __shfl_xor_sync(0xffffffffu, s0, o); s1 += __shfl_xor_sync(0xffffffffu, s1, o);
                    q0 += __shfl_xor_sync(0xffffffffu, q0, o); q1 += __shfl_xor_sync(0xffffffffu, q1, o);
                }
                const float md0 = s0 * (1.0f / D_), md1 = s1 * (1.0f / D_);
                const float v0 = bf16r(fmaxf(fmaf(-md0, md0, q0 * (1.0f / D_)), 0.f)), v1 = bf16r(fmaxf(fmaf(-md1, md1, q1 * (1.0f / D_)), 0.f));
                const float ma = bf16r(p0 + md0), mb = bf16r(p1 + md1);
                const float ra = 1.0f / bf16r(sqrtf(bf16r(v0 + 1e-5f))), rbb = 1.0f / bf16r(sqrtf(bf16r(v1 + 1e-5f)));
                const float mA = __shfl_sync(0xffffffffu, ma, g >> 1), mB = __shfl_sync(0xffffffffu, mb, g >> 1);
                const float rA = __shfl_sync(0xffffffffu, ra, g >> 1), rB = __shfl_sync(0xffffffffu, rbb, g >> 1);
                const float mC = __shfl_sync(0xffffffffu, ma, 4 + (g >> 1)), mD = __shfl_sync(0xffffffffu, mb, 4 + (g >> 1));
                const float rC = __shfl_sync(0xffffffffu, ra, 4 + (g >> 1)), rD = __shfl_sync(0xffffffffu, rbb, 4 + (g >> 1));
                st0 = (g & 1) ? make_float2(mB, rB) : make_float2(mA, rA);
                st1 = (g & 1) ? make_float2(mD, rD) : make_float2(mC, rC);
            }
            mbar_wait(barS, 0);
            TM(2, 5);
            g1_math<16>(acc, cs, cs + 224, st0, st1, P1, t);
            TM(2, 2);
        }
        {
            float acc[96];
#pragma unroll 1
            for (int kc = 0; kc < 8; kc++) {
                mbar_wait(barF + 8 * st, ph);
                if (tl == 0 && cw == 0) TR(1, 8 + kc);
                wgmma_fence();
                const uint32_t aaddr = sb + kc * 16384 + cw * 8192;
                const uint32_t baddr = sb + G1_OFF_B + st * G1_B_STAGE;
#pragma unroll
                for (int kk = 0; kk < 4; kk++)
                    wgmma_m64n192k16_ss(acc, make_desc(aaddr + kk * 2048, 8192, 1024, 1), make_desc(baddr + kk * 1024, 4096, 512, 2), (kc | kk) != 0);
                wgmma_commit();
                if (kc == 0) g1_store<16>(P1, outp, t);
                wgmma_wait<0>();
                if (tl == 0) mbar_arrive(barE + 8 * st);
                if (++st == G1_STAGES) { st = 0; ph ^= 1; }
            }
            TM(2, 3);
            uint32_t P2[24];
            g1_math<12>(acc, cs + 128, cs + 224 + 128, st0, st1, P2, t);
            g1_store<12>(P2, outp + 128, t);
            TM(2, 4);
        }
    }
}

constexpr int G2_THREADS = 384;
constexpr int G2_STAGES = 6;
constexpr int G2_STAGE = 32768;
constexpr int G2_OFF_X = G2_STAGES * G2_STAGE;
constexpr int G2_OFF_BAR = G2_OFF_X + 32768;
constexpr int G2_SMEM = G2_OFF_BAR + 128;
constexpr int G2_KSTEPS = 14;
constexpr int G2_PRE = 6;

__device__ __forceinline__ void ldsm_x4_t(uint32_t& r0, uint32_t& r1, uint32_t& r2, uint32_t& r3, uint32_t addr) {
    asm volatile("ldmatrix.sync.aligned.m8n8.x4.trans.shared.b16 {%0,%1,%2,%3}, [%4];" : "=r"(r0), "=r"(r1), "=r"(r2), "=r"(r3) : "r"(addr) : "memory");
}

__global__ void __cluster_dims__(2, 1, 1) __launch_bounds__(G2_THREADS, 1)
gemm2_kernel(const __grid_constant__ CUtensorMap mapHH, const __grid_constant__ CUtensorMap mapWd, const __grid_constant__ CUtensorMap mapH,
             bf16* __restrict__ out) {
    extern __shared__ __align__(1024) uint8_t smem_raw[];
    const uint32_t sb = smem_u32(smem_raw);
    const int tid = threadIdx.x, lane = tid & 31, warp = tid >> 5, wgi = tid >> 7;
    const int ks = blockIdx.x & 1, nb = (blockIdx.x >> 1) & 3, rb = blockIdx.x >> 3;
    TM(3, 0);
    if (tid == 32) { prefetch_map(&mapHH); prefetch_map(&mapH); }
    const uint32_t barF = sb + G2_OFF_BAR;
    const uint32_t barE = barF + 8 * G2_STAGES;
    const uint32_t barX = barE + 8 * G2_STAGES;
    if (tid == 0) {
        for (int i = 0; i < G2_STAGES; i++) { mbar_init(barF + 8 * i, 1); mbar_init(barE + 8 * i, 2); }
        mbar_init(barX, 1);
        asm volatile("fence.mbarrier_init.release.cluster;" ::: "memory");
        mbar_expect_tx(barX, 32768);
        for (int it = 0; it < G2_PRE; it++) {
            mbar_expect_tx(barF + 8 * it, 32768);
            tma_load_3d(sb + it * G2_STAGE + 16384, &mapWd, barF + 8 * it, 0, ks * 896 + it * 64, nb * 2);
        }
    }
    __syncthreads();
    cluster_arrive_relaxed();

    if (wgi == 0) {
        if (tid == 0) {
            pdl_wait();
            for (int it = 0; it < G2_STAGES; it++) {
                if (it >= G2_PRE) mbar_expect_tx(barF + 8 * it, 32768);
                tma_load_2d(sb + it * G2_STAGE, &mapHH, barF + 8 * it, ks * 896 + it * 64, rb * 128);
                if (it >= G2_PRE) tma_load_3d(sb + it * G2_STAGE + 16384, &mapWd, barF + 8 * it, 0, ks * 896 + it * 64, nb * 2);
            }
            if (blockIdx.x == 0) g_cnt = 0u;
            int st = 0, ph = 0;
            for (int it = G2_STAGES; it < G2_KSTEPS; it++) {
                mbar_wait(barE + 8 * st, ph);
                const uint32_t dst = sb + st * G2_STAGE;
                const int k0 = ks * 896 + it * 64;
                mbar_expect_tx(barF + 8 * st, 32768);
                tma_load_2d(dst, &mapHH, barF + 8 * st, k0, rb * 128);
                tma_load_3d(dst + 16384, &mapWd, barF + 8 * st, 0, k0, nb * 2);
                if (++st == G2_STAGES) { st = 0; ph ^= 1; }
            }
            mbar_wait(barE + 8 * st, ph);
            mbar_expect_tx(barF + 8 * st, 16384);
            tma_load_2d(sb + st * G2_STAGE, &mapH, barF + 8 * st, rb * 128 + ks * 64, nb * 128);
        }
        __syncwarp();
        cluster_wait();
    } else {
        const int cw = wgi - 1;
        const int g = lane >> 2, t = lane & 3, wl = warp & 3;
        const int tl = tid & 127;
        int st = 0, ph = 0;
        float acc[64];
#pragma unroll 1
        for (int it = 0; it < G2_KSTEPS; it++) {
            mbar_wait(barF + 8 * st, ph);
            if (it == 0) TM(3, 1);
            wgmma_fence();
            const uint32_t aaddr = sb + st * G2_STAGE + cw * 8192;
            const uint32_t baddr = sb + st * G2_STAGE + 16384;
#pragma unroll
            for (int kk = 0; kk < 4; kk++)
                wgmma_m64n128k16_ss(acc, make_desc(aaddr + kk * 32, 16, 1024, 1), make_desc(baddr + kk * 2048, 8192, 1024, 1), (it | kk) != 0);
            wgmma_commit();
            wgmma_wait<0>();
            if (tl == 0) mbar_arrive(barE + 8 * st);
            if (++st == G2_STAGES) { st = 0; ph ^= 1; }
        }
        TM(3, 2);
        cluster_wait();
        if (cw != ks) {
            const uint32_t dst = mapa(sb + G2_OFF_X + tl * 16, (uint32_t)(ks ^ 1));
            const uint32_t rbar = mapa(barX, (uint32_t)(ks ^ 1));
#pragma unroll
            for (int i = 0; i < 16; i++) st_async_v4f(dst + i * 2048, acc[4 * i], acc[4 * i + 1], acc[4 * i + 2], acc[4 * i + 3], rbar);
        } else {
            const float4* xb = reinterpret_cast<const float4*>(smem_raw + G2_OFF_X) + tl;
            const int row0 = rb * 128 + cw * 64 + wl * 16 + g;
            bf16* o0 = out + (size_t)row0 * D_ + nb * 128;
            uint32_t ha[16], hb[16];
            mbar_wait(barF + 8 * st, ph);
            {
                const int chl = 8 * (lane >> 4) + (lane & 7), sb8 = 2 * wl + ((lane >> 3) & 1);
                const uint32_t hbase = sb + st * G2_STAGE + chl * 128 + ((sb8 ^ (lane & 7)) << 4);
#pragma unroll
                for (int j = 0; j < 16; j += 2) ldsm_x4_t(ha[j], hb[j], ha[j + 1], hb[j + 1], hbase + j * 1024);
            }
            mbar_wait_cluster(barX, 0);
            TM(3, 4);
#pragma unroll
            for (int j0 = 0; j0 < 16; j0 += 4) {
                uint32_t P0[4], P1[4];
#pragma unroll
                for (int jj = 0; jj < 4; jj++) {
                    const int j = j0 + jj;
                    const float4 x = xb[j * 128];
                    P0[jj] = hadd2(ha[j], pack_bf16(acc[4 * j] + x.x, acc[4 * j + 1] + x.y));
                    P1[jj] = hadd2(hb[j], pack_bf16(acc[4 * j + 2] + x.z, acc[4 * j + 3] + x.w));
                }
                quad_transpose(P0[0], P0[1], P0[2], P0[3], t);
                quad_transpose(P1[0], P1[1], P1[2], P1[3], t);
                *reinterpret_cast<uint4*>(o0 + 8 * (j0 + t)) = make_uint4(P0[0], P0[1], P0[2], P0[3]);
                *reinterpret_cast<uint4*>(o0 + 8 * D_ + 8 * (j0 + t)) = make_uint4(P1[0], P1[1], P1[2], P1[3]);
            }
        }
        TM(3, 5);
    }
#undef TMT
}

typedef CUresult (*EncodeFn)(CUtensorMap*, CUtensorMapDataType, cuuint32_t, void*, const cuuint64_t*, const cuuint64_t*,
                             const cuuint32_t*, const cuuint32_t*, CUtensorMapInterleave, CUtensorMapSwizzle,
                             CUtensorMapL2promotion, CUtensorMapFloatOOBfill);

static void enc2d(EncodeFn enc, CUtensorMap* m, const void* p, int rows, int cols, int brows, int bcols, int pitch = 0) {
    cuuint64_t dims[2] = {(cuuint64_t)cols, (cuuint64_t)rows};
    cuuint64_t strides[1] = {(cuuint64_t)(pitch ? pitch : cols) * 2};
    cuuint32_t box[2] = {(cuuint32_t)bcols, (cuuint32_t)brows};
    cuuint32_t es[2] = {1, 1};
    enc(m, CU_TENSOR_MAP_DATA_TYPE_BFLOAT16, 2, const_cast<void*>(p), dims, strides, box, es, CU_TENSOR_MAP_INTERLEAVE_NONE,
        bcols == 32 ? CU_TENSOR_MAP_SWIZZLE_64B : CU_TENSOR_MAP_SWIZZLE_128B, CU_TENSOR_MAP_L2_PROMOTION_L2_128B, CU_TENSOR_MAP_FLOAT_OOB_FILL_NONE);
}
static void enc2d_plain(EncodeFn enc, CUtensorMap* m, const void* p, int rows, int cols, int brows, int bcols) {
    cuuint64_t dims[2] = {(cuuint64_t)cols, (cuuint64_t)rows};
    cuuint64_t strides[1] = {(cuuint64_t)cols * 2};
    cuuint32_t box[2] = {(cuuint32_t)bcols, (cuuint32_t)brows};
    cuuint32_t es[2] = {1, 1};
    enc(m, CU_TENSOR_MAP_DATA_TYPE_BFLOAT16, 2, const_cast<void*>(p), dims, strides, box, es, CU_TENSOR_MAP_INTERLEAVE_NONE,
        CU_TENSOR_MAP_SWIZZLE_NONE, CU_TENSOR_MAP_L2_PROMOTION_L2_128B, CU_TENSOR_MAP_FLOAT_OOB_FILL_NONE);
}
static void enc3d(EncodeFn enc, CUtensorMap* m, const void* p, int rows, int cols, int atom, int brows, int natoms, int pitch = 0) {
    cuuint64_t dims[3] = {(cuuint64_t)atom, (cuuint64_t)rows, (cuuint64_t)(cols / atom)};
    cuuint64_t strides[2] = {(cuuint64_t)(pitch ? pitch : cols) * 2, (cuuint64_t)atom * 2};
    cuuint32_t box[3] = {(cuuint32_t)atom, (cuuint32_t)brows, (cuuint32_t)natoms};
    cuuint32_t es[3] = {1, 1, 1};
    enc(m, CU_TENSOR_MAP_DATA_TYPE_BFLOAT16, 3, const_cast<void*>(p), dims, strides, box, es, CU_TENSOR_MAP_INTERLEAVE_NONE,
        atom == 32 ? CU_TENSOR_MAP_SWIZZLE_64B : CU_TENSOR_MAP_SWIZZLE_128B, CU_TENSOR_MAP_L2_PROMOTION_L2_128B, CU_TENSOR_MAP_FLOAT_OOB_FILL_NONE);
}

extern "C" void kernel_launch(void* const* d_in, const int* in_sizes, int n_in, void* d_out, int out_size) {
    const bf16* q = (const bf16*)d_in[0];
    const bf16* k = (const bf16*)d_in[1];
    const bf16* v = (const bf16*)d_in[2];
    const bf16* shift_k = (const bf16*)d_in[3];
    const bf16* ssm_k = (const bf16*)d_in[4];
    const bf16* ssm_D = (const bf16*)d_in[5];
    const bf16* wg = (const bf16*)d_in[7];
    const bf16* wu = (const bf16*)d_in[8];
    const bf16* wd = (const bf16*)d_in[9];
    bf16* out = (bf16*)d_out;

    static EncodeFn enc = nullptr;
    static void *p_hT = nullptr, *p_hh = nullptr;
    if (!enc) {
        void* fn = nullptr; cudaDriverEntryPointQueryResult qr;
        cudaGetDriverEntryPoint("cuTensorMapEncodeTiled", &fn, cudaEnableDefault, &qr);
        enc = (EncodeFn)fn;
        cudaGetSymbolAddress(&p_hT, g_hT);
        cudaGetSymbolAddress(&p_hh, g_hh);
        cudaFuncSetAttribute(conv_kernel, cudaFuncAttributeMaxDynamicSharedMemorySize, (int)sizeof(K1Smem));
        cudaFuncSetAttribute(gemm1_kernel, cudaFuncAttributeMaxDynamicSharedMemorySize, G1_SMEM);
        cudaFuncSetAttribute(gemm2_kernel, cudaFuncAttributeMaxDynamicSharedMemorySize, G2_SMEM);
    }
    CUtensorMap mA, mG64, mU64, mG32, mU32, mHH, mWd, mH, mWgp, mWup;
    CUtensorMap mK, mV, mQ;
    enc2d_plain(enc, &mK, k, S_, D_, 176, 8);
    enc2d_plain(enc, &mV, v, S_, D_, 256, 8);
    enc2d_plain(enc, &mQ, q, S_, D_, 256, 8);
    enc2d_plain(enc, &mWgp, wg, D_, F_, 256, 32);
    enc2d_plain(enc, &mWup, wu, D_, F_, 256, 32);
    enc3d(enc, &mA, p_hT, D_, S_, 64, 64, 2, HT_PITCH);
    enc2d(enc, &mH, p_hT, D_, S_, 128, 64, HT_PITCH);
    enc3d(enc, &mG64, wg, D_, F_, 32, 64, 4);
    enc3d(enc, &mU64, wu, D_, F_, 32, 64, 4);
    enc3d(enc, &mG32, wg, D_, F_, 32, 64, 3);
    enc3d(enc, &mU32, wu, D_, F_, 32, 64, 3);
    enc2d(enc, &mHH, p_hh, S_, F_, 128, 64);
    enc3d(enc, &mWd, wd, F_, D_, 64, 64, 2);

    cudaStream_t st = cudaStreamPerThread;
    cudaLaunchAttribute at[1];
    at[0].id = cudaLaunchAttributeProgrammaticStreamSerialization;
    at[0].val.programmaticStreamSerializationAllowed = 1;
    cudaLaunchConfig_t cfg = {};
    cfg.stream = st; cfg.attrs = at; cfg.numAttrs = 1;
    conv_kernel<<<128, K1_THREADS, sizeof(K1Smem), st>>>(q, mK, mV, mQ, shift_k, ssm_k, ssm_D, mWgp, mWup, wd);
    cfg.gridDim = dim3(128); cfg.blockDim = dim3(G1_THREADS); cfg.dynamicSmemBytes = G1_SMEM;
    cudaLaunchKernelEx(&cfg, gemm1_kernel, mA, mG64, mU64, mG32, mU32);
    cfg.gridDim = dim3(128); cfg.blockDim = dim3(G2_THREADS); cfg.dynamicSmemBytes = G2_SMEM;
    cudaLaunchKernelEx(&cfg, gemm2_kernel, mHH, mWd, mH, out);
}
```

```cpp
#include <cuda_runtime.h>
#include <cuda_bf16.h>
#include <cuda.h>
#include <stdint.h>

typedef __nv_bfloat16 bf16;
constexpr int S_ = 2048, D_ = 512, F_ = 1792;

constexpr int HT_PITCH = S_ + 64;
__device__ __align__(128) bf16 g_hT[D_ * HT_PITCH];
__device__ bf16 g_hh[S_ * F_];
__device__ __align__(128) float g_st1[S_ + S_ / 2];
__device__ float g_colsum[2 * F_];
__device__ unsigned int g_cnt;

#define TM(k, i)
#define TR(k, i)
__device__ __forceinline__ uint32_t smem_u32(const void* p) { return (uint32_t)__cvta_generic_to_shared(p); }
__device__ __forceinline__ float bf16r(float x) { return __bfloat162float(__float2bfloat16_rn(x)); }
__device__ __forceinline__ float bf_lo(uint32_t w) { return __uint_as_float(w << 16); }
__device__ __forceinline__ float bf_hi(uint32_t w) { return __uint_as_float(w & 0xffff0000u); }
__device__ __forceinline__ uint32_t pack_bf16(float lo, float hi) {
    __nv_bfloat162 v = __floats2bfloat162_rn(lo, hi);
    return *reinterpret_cast<uint32_t*>(&v);
}
__device__ __forceinline__ uint32_t hmul2(uint32_t a, uint32_t b) {
    __nv_bfloat162 r = __hmul2_rn(*reinterpret_cast<__nv_bfloat162*>(&a), *reinterpret_cast<__nv_bfloat162*>(&b));
    return *reinterpret_cast<uint32_t*>(&r);
}
__device__ __forceinline__ uint32_t hadd2(uint32_t a, uint32_t b) {
    __nv_bfloat162 r = __hadd2_rn(*reinterpret_cast<__nv_bfloat162*>(&a), *reinterpret_cast<__nv_bfloat162*>(&b));
    return *reinterpret_cast<uint32_t*>(&r);
}
__device__ __forceinline__ uint4 ldg128(const void* p) {
    uint4 r; asm volatile("ld.global.nc.v4.u32 {%0,%1,%2,%3}, [%4];" : "=r"(r.x), "=r"(r.y), "=r"(r.z), "=r"(r.w) : "l"(p)); return r;
}
__device__ __forceinline__ uint4 ldg128_l2(const void* p) {
    uint4 r; asm volatile("ld.global.nc.L2::128B.v4.u32 {%0,%1,%2,%3}, [%4];" : "=r"(r.x), "=r"(r.y), "=r"(r.z), "=r"(r.w) : "l"(p)); return r;
}
__device__ __forceinline__ uint4 ldcg128(const void* p) {
    uint4 r; asm volatile("ld.global.cg.v4.u32 {%0,%1,%2,%3}, [%4];" : "=r"(r.x), "=r"(r.y), "=r"(r.z), "=r"(r.w) : "l"(p)); return r;
}
__device__ __forceinline__ uint32_t ldg16(const void* p) {
    unsigned short r; asm volatile("ld.global.nc.u16 %0, [%1];" : "=h"(r) : "l"(p)); return (uint32_t)r;
}
__device__ __forceinline__ void mbar_init(uint32_t bar, int cnt) { asm volatile("mbarrier.init.shared::cta.b64 [%0], %1;" :: "r"(bar), "r"(cnt)); }
__device__ __forceinline__ void mbar_expect_tx(uint32_t bar, uint32_t bytes) { asm volatile("mbarrier.arrive.expect_tx.shared::cta.b64 _, [%0], %1;" :: "r"(bar), "r"(bytes) : "memory"); }
__device__ __forceinline__ void mbar_arrive(uint32_t bar) { asm volatile("mbarrier.arrive.shared::cta.b64 _, [%0];" :: "r"(bar) : "memory"); }
__device__ __forceinline__ void mbar_arrive_cluster(uint32_t bar, uint32_t cta) {
    asm volatile("{\n.reg .b32 ra;\nmapa.shared::cluster.u32 ra, %0, %1;\nmbarrier.arrive.shared::cluster.b64 _, [ra];\n}" :: "r"(bar), "r"(cta) : "memory");
}
__device__ __forceinline__ void mbar_wait(uint32_t bar, uint32_t parity) {
    asm volatile("{\n.reg .pred P1;\nLAB_WAIT:\nmbarrier.try_wait.parity.shared::cta.b64 P1, [%0], %1;\n@P1 bra DONE;\nbra LAB_WAIT;\nDONE:\n}" :: "r"(bar), "r"(parity) : "memory");
}
__device__ __forceinline__ void mbar_wait_cluster(uint32_t bar, uint32_t parity) {
    asm volatile("{\n.reg .pred P1;\nLAB_WAIT:\nmbarrier.try_wait.parity.acquire.cluster.shared::cta.b64 P1, [%0], %1;\n@P1 bra DONE;\nbra LAB_WAIT;\nDONE:\n}" :: "r"(bar), "r"(parity) : "memory");
}
__device__ __forceinline__ void tma_load_2d(uint32_t dst, const CUtensorMap* map, uint32_t bar, int c0, int c1) {
    asm volatile("cp.async.bulk.tensor.2d.shared::cluster.global.mbarrier::complete_tx::bytes [%0], [%1, {%3, %4}], [%2];"
        :: "r"(dst), "l"(map), "r"(bar), "r"(c0), "r"(c1) : "memory");
}
__device__ __forceinline__ void tma_load_2d_mc(uint32_t dst, const CUtensorMap* map, uint32_t bar, int c0, int c1, uint16_t mask) {
    asm volatile("cp.async.bulk.tensor.2d.shared::cluster.global.mbarrier::complete_tx::bytes.multicast::cluster [%0], [%1, {%3, %4}], [%2], %5;"
        :: "r"(dst), "l"(map), "r"(bar), "r"(c0), "r"(c1), "h"(mask) : "memory");
}
__device__ __forceinline__ void tma_load_3d_mc(uint32_t dst, const CUtensorMap* map, uint32_t bar, int c0, int c1, int c2, uint16_t mask) {
    asm volatile("cp.async.bulk.tensor.3d.shared::cluster.global.mbarrier::complete_tx::bytes.multicast::cluster [%0], [%1, {%3, %4, %5}], [%2], %6;"
        :: "r"(dst), "l"(map), "r"(bar), "r"(c0), "r"(c1), "r"(c2), "h"(mask) : "memory");
}
__device__ __forceinline__ void tma_load_3d(uint32_t dst, const CUtensorMap* map, uint32_t bar, int c0, int c1, int c2) {
    asm volatile("cp.async.bulk.tensor.3d.shared::cluster.global.mbarrier::complete_tx::bytes [%0], [%1, {%3, %4, %5}], [%2];"
        :: "r"(dst), "l"(map), "r"(bar), "r"(c0), "r"(c1), "r"(c2) : "memory");
}
__device__ __forceinline__ void cluster_arrive() { asm volatile("barrier.cluster.arrive.aligned;" ::: "memory"); }
__device__ __forceinline__ void cluster_arrive_relaxed() { asm volatile("barrier.cluster.arrive.relaxed.aligned;" ::: "memory"); }
__device__ __forceinline__ void cluster_wait() { asm volatile("barrier.cluster.wait.aligned;" ::: "memory"); }
__device__ __forceinline__ uint32_t mapa(uint32_t addr, uint32_t cta) {
    uint32_t r; asm volatile("mapa.shared::cluster.u32 %0, %1, %2;" : "=r"(r) : "r"(addr), "r"(cta)); return r;
}
__device__ __forceinline__ void st_async_v2(uint32_t addr, uint32_t a, uint32_t b, uint32_t rbar) {
    asm volatile("st.async.weak.shared::cluster.mbarrier::complete_tx::bytes.v2.b32 [%0], {%1, %2}, [%3];" :: "r"(addr), "r"(a), "r"(b), "r"(rbar) : "memory");
}
__device__ __forceinline__ void st_async_v4f(uint32_t addr, float a, float b, float c, float d, uint32_t rbar) {
    asm volatile("st.async.weak.shared::cluster.mbarrier::complete_tx::bytes.v4.f32 [%0], {%1, %2, %3, %4}, [%5];" :: "r"(addr), "f"(a), "f"(b), "f"(c), "f"(d), "r"(rbar) : "memory");
}
__device__ __forceinline__ void wgmma_fence() { asm volatile("wgmma.fence.sync.aligned;" ::: "memory"); }
__device__ __forceinline__ void wgmma_commit() { asm volatile("wgmma.commit_group.sync.aligned;" ::: "memory"); }
template <int N> __device__ __forceinline__ void wgmma_wait() { asm volatile("wgmma.wait_group.sync.aligned %0;" :: "n"(N) : "memory"); }
__device__ __forceinline__ uint64_t make_desc(uint32_t addr, uint32_t lbo_bytes, uint32_t sbo_bytes, uint32_t layout) {
    return (uint64_t)((addr & 0x3FFFF) >> 4) | ((uint64_t)(lbo_bytes >> 4) << 16) | ((uint64_t)(sbo_bytes >> 4) << 32) | ((uint64_t)layout << 62);
}
template <int R> __device__ __forceinline__ void reg_alloc() { asm volatile("setmaxnreg.inc.sync.aligned.u32 %0;" :: "n"(R)); }
template <int R> __device__ __forceinline__ void reg_dealloc() { asm volatile("setmaxnreg.dec.sync.aligned.u32 %0;" :: "n"(R)); }
__device__ __forceinline__ void pdl_launch() { asm volatile("griddepcontrol.launch_dependents;" ::: "memory"); }
__device__ __forceinline__ void pdl_wait() { asm volatile("griddepcontrol.wait;" ::: "memory"); }
__device__ __forceinline__ void prefetch_map(const CUtensorMap* m) { asm volatile("prefetch.tensormap [%0];" :: "l"(m) : "memory"); }
__device__ __forceinline__ void named_bar(int id, int n) { asm volatile("bar.sync %0, %1;" :: "r"(id), "r"(n) : "memory"); }

__device__ __forceinline__ void wgmma_m64n256k16_ss(float (&d)[128], uint64_t descA, uint64_t descB, int scaleD) {
    asm volatile("{\n.reg .pred p;\nsetp.ne.b32 p, %130, 0;\n"
        "wgmma.mma_async.sync.aligned.m64n256k16.f32.bf16.bf16 {%0, %1, %2, %3, %4, %5, %6, %7, %8, %9, %10, %11, %12, %13, %14, %15, %16, %17, %18, %19, %20, %21, %22, %23, %24, %25, %26, %27, %28, %29, %30, %31, %32, %33, %34, %35, %36, %37, %38, %39, %40, %41, %42, %43, %44, %45, %46, %47, %48, %49, %50, %51, %52, %53, %54, %55, %56, %57, %58, %59, %60, %61, %62, %63, %64, %65, %66, %67, %68, %69, %70, %71, %72, %73, %74, %75, %76, %77, %78, %79, %80, %81, %82, %83, %84, %85, %86, %87, %88, %89, %90, %91, %92, %93, %94, %95, %96, %97, %98, %99, %100, %101, %102, %103, %104, %105, %106, %107, %108, %109, %110, %111, %112, %113, %114, %115, %116, %117, %118, %119, %120, %121, %122, %123, %124, %125, %126, %127}, %128, %129, p, 1, 1, 1, 1;\n}\n"
        : "+f"(d[0]), "+f"(d[1]), "+f"(d[2]), "+f"(d[3]), "+f"(d[4]), "+f"(d[5]), "+f"(d[6]), "+f"(d[7]), "+f"(d[8]), "+f"(d[9]), "+f"(d[10]), "+f"(d[11]), "+f"(d[12]), "+f"(d[13]), "+f"(d[14]), "+f"(d[15]), "+f"(d[16]), "+f"(d[17]), "+f"(d[18]), "+f"(d[19]), "+f"(d[20]), "+f"(d[21]), "+f"(d[22]), "+f"(d[23]), "+f"(d[24]), "+f"(d[25]), "+f"(d[26]), "+f"(d[27]), "+f"(d[28]), "+f"(d[29]), "+f"(d[30]), "+f"(d[31]), "+f"(d[32]), "+f"(d[33]), "+f"(d[34]), "+f"(d[35]), "+f"(d[36]), "+f"(d[37]), "+f"(d[38]), "+f"(d[39]), "+f"(d[40]), "+f"(d[41]), "+f"(d[42]), "+f"(d[43]), "+f"(d[44]), "+f"(d[45]), "+f"(d[46]), "+f"(d[47]), "+f"(d[48]), "+f"(d[49]), "+f"(d[50]), "+f"(d[51]), "+f"(d[52]), "+f"(d[53]), "+f"(d[54]), "+f"(d[55]), "+f"(d[56]), "+f"(d[57]), "+f"(d[58]), "+f"(d[59]), "+f"(d[60]), "+f"(d[61]), "+f"(d[62]), "+f"(d[63]), "+f"(d[64]), "+f"(d[65]), "+f"(d[66]), "+f"(d[67]), "+f"(d[68]), "+f"(d[69]), "+f"(d[70]), "+f"(d[71]), "+f"(d[72]), "+f"(d[73]), "+f"(d[74]), "+f"(d[75]), "+f"(d[76]), "+f"(d[77]), "+f"(d[78]), "+f"(d[79]), "+f"(d[80]), "+f"(d[81]), "+f"(d[82]), "+f"(d[83]), "+f"(d[84]), "+f"(d[85]), "+f"(d[86]), "+f"(d[87]), "+f"(d[88]), "+f"(d[89]), "+f"(d[90]), "+f"(d[91]), "+f"(d[92]), "+f"(d[93]), "+f"(d[94]), "+f"(d[95]), "+f"(d[96]), "+f"(d[97]), "+f"(d[98]), "+f"(d[99]), "+f"(d[100]), "+f"(d[101]), "+f"(d[102]), "+f"(d[103]), "+f"(d[104]), "+f"(d[105]), "+f"(d[106]), "+f"(d[107]), "+f"(d[108]), "+f"(d[109]), "+f"(d[110]), "+f"(d[111]), "+f"(d[112]), "+f"(d[113]), "+f"(d[114]), "+f"(d[115]), "+f"(d[116]), "+f"(d[117]), "+f"(d[118]), "+f"(d[119]), "+f"(d[120]), "+f"(d[121]), "+f"(d[122]), "+f"(d[123]), "+f"(d[124]), "+f"(d[125]), "+f"(d[126]), "+f"(d[127])
        : "l"(descA), "l"(descB), "r"(scaleD));
}

__device__ __forceinline__ void wgmma_m64n192k16_ss(float (&d)[96], uint64_t descA, uint64_t descB, int scaleD) {
    asm volatile("{\n.reg .pred p;\nsetp.ne.b32 p, %98, 0;\n"
        "wgmma.mma_async.sync.aligned.m64n192k16.f32.bf16.bf16 {%0, %1, %2, %3, %4, %5, %6, %7, %8, %9, %10, %11, %12, %13, %14, %15, %16, %17, %18, %19, %20, %21, %22, %23, %24, %25, %26, %27, %28, %29, %30, %31, %32, %33, %34, %35, %36, %37, %38, %39, %40, %41, %42, %43, %44, %45, %46, %47, %48, %49, %50, %51, %52, %53, %54, %55, %56, %57, %58, %59, %60, %61, %62, %63, %64, %65, %66, %67, %68, %69, %70, %71, %72, %73, %74, %75, %76, %77, %78, %79, %80, %81, %82, %83, %84, %85, %86, %87, %88, %89, %90, %91, %92, %93, %94, %95}, %96, %97, p, 1, 1, 1, 1;\n}\n"
        : "+f"(d[0]), "+f"(d[1]), "+f"(d[2]), "+f"(d[3]), "+f"(d[4]), "+f"(d[5]), "+f"(d[6]), "+f"(d[7]), "+f"(d[8]), "+f"(d[9]), "+f"(d[10]), "+f"(d[11]), "+f"(d[12]), "+f"(d[13]), "+f"(d[14]), "+f"(d[15]), "+f"(d[16]), "+f"(d[17]), "+f"(d[18]), "+f"(d[19]), "+f"(d[20]), "+f"(d[21]), "+f"(d[22]), "+f"(d[23]), "+f"(d[24]), "+f"(d[25]), "+f"(d[26]), "+f"(d[27]), "+f"(d[28]), "+f"(d[29]), "+f"(d[30]), "+f"(d[31]), "+f"(d[32]), "+f"(d[33]), "+f"(d[34]), "+f"(d[35]), "+f"(d[36]), "+f"(d[37]), "+f"(d[38]), "+f"(d[39]), "+f"(d[40]), "+f"(d[41]), "+f"(d[42]), "+f"(d[43]), "+f"(d[44]), "+f"(d[45]), "+f"(d[46]), "+f"(d[47]), "+f"(d[48]), "+f"(d[49]), "+f"(d[50]), "+f"(d[51]), "+f"(d[52]), "+f"(d[53]), "+f"(d[54]), "+f"(d[55]), "+f"(d[56]), "+f"(d[57]), "+f"(d[58]), "+f"(d[59]), "+f"(d[60]), "+f"(d[61]), "+f"(d[62]), "+f"(d[63]), "+f"(d[64]), "+f"(d[65]), "+f"(d[66]), "+f"(d[67]), "+f"(d[68]), "+f"(d[69]), "+f"(d[70]), "+f"(d[71]), "+f"(d[72]), "+f"(d[73]), "+f"(d[74]), "+f"(d[75]), "+f"(d[76]), "+f"(d[77]), "+f"(d[78]), "+f"(d[79]), "+f"(d[80]), "+f"(d[81]), "+f"(d[82]), "+f"(d[83]), "+f"(d[84]), "+f"(d[85]), "+f"(d[86]), "+f"(d[87]), "+f"(d[88]), "+f"(d[89]), "+f"(d[90]), "+f"(d[91]), "+f"(d[92]), "+f"(d[93]), "+f"(d[94]), "+f"(d[95])
        : "l"(descA), "l"(descB), "r"(scaleD));
}

__device__ __forceinline__ void wgmma_m64n128k16_ss(float (&d)[64], uint64_t descA, uint64_t descB, int scaleD) {
    asm volatile("{\n.reg .pred p;\nsetp.ne.b32 p, %66, 0;\n"
        "wgmma.mma_async.sync.aligned.m64n128k16.f32.bf16.bf16 {%0, %1, %2, %3, %4, %5, %6, %7, %8, %9, %10, %11, %12, %13, %14, %15, %16, %17, %18, %19, %20, %21, %22, %23, %24, %25, %26, %27, %28, %29, %30, %31, %32, %33, %34, %35, %36, %37, %38, %39, %40, %41, %42, %43, %44, %45, %46, %47, %48, %49, %50, %51, %52, %53, %54, %55, %56, %57, %58, %59, %60, %61, %62, %63}, %64, %65, p, 1, 1, 0, 1;\n}\n"
        : "+f"(d[0]), "+f"(d[1]), "+f"(d[2]), "+f"(d[3]), "+f"(d[4]), "+f"(d[5]), "+f"(d[6]), "+f"(d[7]), "+f"(d[8]), "+f"(d[9]), "+f"(d[10]), "+f"(d[11]), "+f"(d[12]), "+f"(d[13]), "+f"(d[14]), "+f"(d[15]), "+f"(d[16]), "+f"(d[17]), "+f"(d[18]), "+f"(d[19]), "+f"(d[20]), "+f"(d[21]), "+f"(d[22]), "+f"(d[23]), "+f"(d[24]), "+f"(d[25]), "+f"(d[26]), "+f"(d[27]), "+f"(d[28]), "+f"(d[29]), "+f"(d[30]), "+f"(d[31]), "+f"(d[32]), "+f"(d[33]), "+f"(d[34]), "+f"(d[35]), "+f"(d[36]), "+f"(d[37]), "+f"(d[38]), "+f"(d[39]), "+f"(d[40]), "+f"(d[41]), "+f"(d[42]), "+f"(d[43]), "+f"(d[44]), "+f"(d[45]), "+f"(d[46]), "+f"(d[47]), "+f"(d[48]), "+f"(d[49]), "+f"(d[50]), "+f"(d[51]), "+f"(d[52]), "+f"(d[53]), "+f"(d[54]), "+f"(d[55]), "+f"(d[56]), "+f"(d[57]), "+f"(d[58]), "+f"(d[59]), "+f"(d[60]), "+f"(d[61]), "+f"(d[62]), "+f"(d[63])
        : "l"(descA), "l"(descB), "r"(scaleD));
}

__device__ __forceinline__ void quad_transpose(uint32_t& r0, uint32_t& r1, uint32_t& r2, uint32_t& r3, int t) {
    const bool o1 = t & 1, o2 = t & 2;
    uint32_t x, y;
    x = o1 ? r0 : r1; y = __shfl_xor_sync(0xffffffffu, x, 1); if (o1) r0 = y; else r1 = y;
    x = o1 ? r2 : r3; y = __shfl_xor_sync(0xffffffffu, x, 1); if (o1) r2 = y; else r3 = y;
    x = o2 ? r0 : r2; y = __shfl_xor_sync(0xffffffffu, x, 2); if (o2) r0 = y; else r2 = y;
    x = o2 ? r1 : r3; y = __shfl_xor_sync(0xffffffffu, x, 2); if (o2) r1 = y; else r3 = y;
}

__device__ __forceinline__ float warp_sum(float s) {
#pragma unroll
    for (int o = 16; o > 0; o >>= 1) s += __shfl_xor_sync(0xffffffffu, s, o);
    return s;
}
__device__ __forceinline__ uint32_t hsub2(uint32_t a, uint32_t b) {
    __nv_bfloat162 r = __hsub2_rn(*reinterpret_cast<__nv_bfloat162*>(&a), *reinterpret_cast<__nv_bfloat162*>(&b));
    return *reinterpret_cast<uint32_t*>(&r);
}
__device__ __forceinline__ void ln_stats2(const uint32_t (&x)[2][8], float2 (&st)[2]) {
    float piv[2], s[2], ss[2];
#pragma unroll
    for (int r = 0; r < 2; r++) piv[r] = __shfl_sync(0xffffffffu, bf_lo(x[r][0]), 0);
#pragma unroll
    for (int r = 0; r < 2; r++) {
        float s0 = 0.f, s1 = 0.f, q0 = 0.f, q1 = 0.f;
#pragma unroll
        for (int i = 0; i < 8; i++) {
            const float d0 = bf_lo(x[r][i]) - piv[r], d1 = bf_hi(x[r][i]) - piv[r];
            s0 += d0; s1 += d1; q0 = fmaf(d0, d0, q0); q1 = fmaf(d1, d1, q1);
        }
        s[r] = s0 + s1; ss[r] = q0 + q1;
    }
#pragma unroll
    for (int o = 16; o > 0; o >>= 1) {
#pragma unroll
        for (int r = 0; r < 2; r++) { s[r] += __shfl_xor_sync(0xffffffffu, s[r], o); ss[r] += __shfl_xor_sync(0xffffffffu, ss[r], o); }
    }
#pragma unroll
    for (int r = 0; r < 2; r++) {
        const float md = s[r] * (1.0f / D_);
        const float var = bf16r(fmaxf(fmaf(-md, md, ss[r] * (1.0f / D_)), 0.f));
        st[r] = make_float2(bf16r(piv[r] + md), 1.0f / bf16r(sqrtf(bf16r(var + 1e-5f))));
    }
}
__device__ __forceinline__ void ln_apply(const uint32_t (&x)[8], float2 st, uint32_t (&o)[8]) {
    const uint32_t m2 = pack_bf16(st.x, st.x);
#pragma unroll
    for (int i = 0; i < 8; i++) {
        const uint32_t d = hsub2(x[i], m2);
        o[i] = pack_bf16(bf_lo(d) * st.y, bf_hi(d) * st.y);
    }
}

constexpr int K1_THREADS = 352;
constexpr int UT_PAD = 128;
constexpr int UT_LEN = UT_PAD + S_;
constexpr int KR_LEN = 2080;
constexpr int YP_LEN = S_ + (S_ / 32) * 8;

struct __align__(128) K1Smem {
    bf16 uT[4][UT_LEN];
    bf16 xT[4][S_];
    bf16 kr[4][2][KR_LEN];
    float yP[4][YP_LEN];
    alignas(128) float st[S_ + S_ / 2];
    alignas(128) uint4 wS[512][4];
    float red[8][32];
    uint64_t bar, bar2, bar3, bar4;
};

__device__ __forceinline__ void mma16816(float (&c)[4], uint32_t a0, uint32_t a1, uint32_t a2, uint32_t a3, uint32_t b0, uint32_t b1) {
    asm volatile("mma.sync.aligned.m16n8k16.row.col.f32.bf16.bf16.f32 {%0,%1,%2,%3}, {%4,%5,%6,%7}, {%8,%9}, {%0,%1,%2,%3};"
        : "+f"(c[0]), "+f"(c[1]), "+f"(c[2]), "+f"(c[3])
        : "r"(a0), "r"(a1), "r"(a2), "r"(a3), "r"(b0), "r"(b1));
}
__device__ __forceinline__ void ldsm_x4(uint32_t& r0, uint32_t& r1, uint32_t& r2, uint32_t& r3, uint32_t addr) {
    asm volatile("ldmatrix.sync.aligned.m8n8.x4.shared.b16 {%0,%1,%2,%3}, [%4];" : "=r"(r0), "=r"(r1), "=r"(r2), "=r"(r3) : "r"(addr) : "memory");
}

__device__ __forceinline__ void conv_mma(const bf16* uTc, const bf16* krlane, float (&acc)[16][4], int lane, int half) {
    const int lrow = lane & 7, lk = (lane >> 3) & 1, lt = lane >> 4;
    const uint32_t ubase = smem_u32(uTc) + (UT_PAD + 16 * (8 * lt + lrow) + 8 * lk) * 2;
#pragma unroll 1
    for (int pp = 0; pp < 4; pp++) {
        const int p = half * 4 + pp;
        uint32_t U[16][2];
#pragma unroll
        for (int j = 0; j < 16; j += 2) ldsm_x4(U[j][0], U[j][1], U[j + 1][0], U[j + 1][1], ubase + (j * 128 - p * 16) * 2);
        const uint32_t* kp = reinterpret_cast<const uint32_t*>(krlane - 16 * p);
        const volatile uint32_t* kpv = kp;
        uint32_t a0 = kp[0], a1 = kp[-4], a2 = kp[4], a3 = kpv[0];
#pragma unroll
        for (int q = 0; q < 16; q++) {
            uint32_t b0 = 0, b1 = 0, b2 = 0, b3 = 0;
            if (q < 15) { b0 = kp[-64 * (q + 1)]; b1 = kp[-64 * (q + 1) - 4]; b2 = kp[-64 * (q + 1) + 4]; b3 = kpv[-64 * (q + 1)]; }
#pragma unroll
            for (int n = 15; n >= q; n--) mma16816(acc[n], a0, a1, a2, a3, U[n - q][0], U[n - q][1]);
            a0 = b0; a1 = b1; a2 = b2; a3 = b3;
        }
    }
}

__device__ __forceinline__ void cp_async16(uint32_t dst, const void* src) {
    asm volatile("cp.async.cg.shared.global [%0], [%1], 16;" :: "r"(dst), "l"(src) : "memory");
}

__global__ void __cluster_dims__(2, 1, 1) __launch_bounds__(K1_THREADS, 1)
conv_kernel(const bf16* __restrict__ q, const bf16* __restrict__ k, const bf16* __restrict__ v,
            const bf16* __restrict__ shift_k, const bf16* __restrict__ ssm_k, const bf16* __restrict__ ssm_D,
            const __grid_constant__ CUtensorMap mapWg, const __grid_constant__ CUtensorMap mapWu, const bf16* __restrict__ wd) {
    extern __shared__ __align__(1024) uint8_t smem_raw[];
    pdl_launch();
    K1Smem& sm = *reinterpret_cast<K1Smem*>(smem_raw);
    const int tid = threadIdx.x, lane = tid & 31, warp = tid >> 5;
    const int bid = blockIdx.x;
    const int rank = bid & 1;
    const int c0 = 8 * (bid >> 1);
    const int cown = c0 + 4 * rank;
#define TMT 0
    TM(0, 0);
    const uint32_t bar = smem_u32(&sm.bar);
    if (tid == 0) {
        mbar_init(bar, 1);
        mbar_init(bar + 8, 1);
        mbar_init(bar + 16, 1);
        mbar_init(bar + 24, 1);
        asm volatile("fence.mbarrier_init.release.cluster;" ::: "memory");
        mbar_expect_tx(bar, 1024 * 4 * 2);
        mbar_expect_tx(bar + 8, 1024 * 4 * 2);
    }
    cluster_arrive_relaxed();

    if (warp < 8) {
        const int s0 = 1024 * rank + 4 * tid;
        uint4 kk[7], vv[4], qq[4], sw[4];
#pragma unroll
        for (int i = 0; i < 4; i++) kk[3 + i] = ldg128_l2(k + (size_t)(s0 + i) * D_ + c0);
#pragma unroll
        for (int i = 0; i < 4; i++) vv[i] = ldg128_l2(v + (size_t)(s0 + i) * D_ + c0);
        if (lane == 0) {
#pragma unroll
            for (int i = 0; i < 3; i++) {
                const int s = s0 - 3 + i;
                kk[i] = make_uint4(0, 0, 0, 0);
                if (s >= 0) kk[i] = ldg128(k + (size_t)s * D_ + c0);
            }
        }
#pragma unroll
        for (int i = 0; i < 4; i++) sw[i] = ldg128(shift_k + (size_t)c0 * 4 + 8 * i);
        uint4 kq[4]; uint32_t nx[4];
#pragma unroll
        for (int c = 0; c < 4; c++) {
            const bf16* kr = ssm_k + (size_t)(cown + c) * S_;
            kq[c] = ldg128(kr + 8 * tid);
            nx[c] = 0u;
            if (tid < 255) nx[c] = ldg16(kr + 8 * tid + 8);
        }
        const uint32_t dval = ldg16(ssm_D + cown + (warp >> 1));
        if (tid < 64) *reinterpret_cast<uint4*>(&sm.uT[tid >> 4][(tid & 15) * 8]) = make_uint4(0, 0, 0, 0);
#pragma unroll
        for (int i = 0; i < 3; i++) {
            uint4 t;
            t.x = __shfl_up_sync(0xffffffffu, kk[4 + i].x, 1); t.y = __shfl_up_sync(0xffffffffu, kk[4 + i].y, 1);
            t.z = __shfl_up_sync(0xffffffffu, kk[4 + i].z, 1); t.w = __shfl_up_sync(0xffffffffu, kk[4 + i].w, 1);
            if (lane != 0) kk[i] = t;
        }
        uint32_t kvw[4][4];
        const uint32_t* kkw = reinterpret_cast<const uint32_t*>(kk);
        const uint32_t* vvw = reinterpret_cast<const uint32_t*>(vv);
        const uint32_t* qqw = reinterpret_cast<const uint32_t*>(qq);
#pragma unroll
        for (int i2 = 0; i2 < 4; i2++) {
            const uint32_t t0 = __byte_perm(sw[i2].x, sw[i2].z, 0x5410), t1 = __byte_perm(sw[i2].x, sw[i2].z, 0x7632);
            const uint32_t t2 = __byte_perm(sw[i2].y, sw[i2].w, 0x5410), t3 = __byte_perm(sw[i2].y, sw[i2].w, 0x7632);
#pragma unroll
            for (int r = 0; r < 4; r++) {
                uint32_t a = hmul2(kkw[(r + 0) * 4 + i2], t3);
                a = hadd2(a, hmul2(kkw[(r + 1) * 4 + i2], t2));
                a = hadd2(a, hmul2(kkw[(r + 2) * 4 + i2], t1));
                a = hadd2(a, hmul2(kkw[(r + 3) * 4 + i2], t0));
                kvw[r][i2] = hmul2(a, vvw[r * 4 + i2]);
            }
        }
        TM(0, 1);
        cluster_wait();
        const uint32_t rbar = mapa(bar, (uint32_t)(rank ^ 1));
#pragma unroll
        for (int i2 = 0; i2 < 4; i2++) {
#pragma unroll
            for (int e = 0; e < 2; e++) {
                const uint32_t sel = e ? 0x7632 : 0x5410;
                const uint32_t w0 = __byte_perm(kvw[0][i2], kvw[1][i2], sel), w1 = __byte_perm(kvw[2][i2], kvw[3][i2], sel);
                const int cc = 2 * i2 + e;
                if ((cc >> 2) == rank) *reinterpret_cast<uint2*>(&sm.uT[cc & 3][UT_PAD + s0]) = make_uint2(w0, w1);
                else st_async_v2(mapa(smem_u32(&sm.uT[cc & 3][UT_PAD + s0]), (uint32_t)(rank ^ 1)), w0, w1, rbar);
            }
        }
#pragma unroll
        for (int c = 0; c < 4; c++) {
            uint4 a, b;
            a.x = __byte_perm(kq[c].w, 0, 0x1032); a.y = __byte_perm(kq[c].z, 0, 0x1032);
            a.z = __byte_perm(kq[c].y, 0, 0x1032); a.w = __byte_perm(kq[c].x, 0, 0x1032);
            b.x = __byte_perm(nx[c], kq[c].w, 0x7610); b.y = __byte_perm(kq[c].w, kq[c].z, 0x7610);
            b.z = __byte_perm(kq[c].z, kq[c].y, 0x7610); b.w = __byte_perm(kq[c].y, kq[c].x, 0x7610);
            *reinterpret_cast<uint4*>(&sm.kr[c][0][2040 - 8 * tid]) = a;
            *reinterpret_cast<uint4*>(&sm.kr[c][1][2040 - 8 * tid]) = b;
            if (tid == 0) {
                *reinterpret_cast<uint4*>(&sm.kr[c][1][2048]) = make_uint4(kq[c].x & 0xffffu, 0, 0, 0);
            } else if (tid < 8) {
                if (tid < 4) *reinterpret_cast<uint4*>(&sm.kr[c][1][2048 + 8 * tid]) = make_uint4(0, 0, 0, 0);
                else *reinterpret_cast<uint4*>(&sm.kr[c][0][2048 + 8 * (tid - 4)]) = make_uint4(0, 0, 0, 0);
            }
        }
#pragma unroll
        for (int i = 0; i < 4; i++) qq[i] = ldg128(q + (size_t)(s0 + i) * D_ + c0);
        TM(0, 3);
        named_bar(6, 352);
        mbar_wait_cluster(bar, 0);
        TM(0, 4);

        const int ch = warp >> 1, half = warp & 1;
        const int g = lane >> 2, t = lane & 3;
        float acc[16][4];
#pragma unroll
        for (int i = 0; i < 16; i++) { acc[i][0] = acc[i][1] = acc[i][2] = acc[i][3] = 0.f; }
        const bf16* krlane = (g & 1) ? &sm.kr[ch][0][2047 - g + 2 * t] : &sm.kr[ch][1][2048 - g + 2 * t];
        conv_mma(sm.uT[ch], krlane, acc, lane, half);
        TM(0, 5);
#pragma unroll
        for (int i2 = 0; i2 < 4; i2++) {
#pragma unroll
            for (int e = 0; e < 2; e++) {
                const uint32_t sel = e ? 0x7632 : 0x5410;
                const uint32_t w0 = __byte_perm(qqw[i2], qqw[4 + i2], sel), w1 = __byte_perm(qqw[8 + i2], qqw[12 + i2], sel);
                const int cc = 2 * i2 + e;
                if ((cc >> 2) == rank) *reinterpret_cast<uint2*>(&sm.xT[cc & 3][s0]) = make_uint2(w0, w1);
                else st_async_v2(mapa(smem_u32(&sm.xT[cc & 3][s0]), (uint32_t)(rank ^ 1)), w0, w1, rbar + 8);
            }
        }
        float* yp = &sm.yP[ch][40 * t + g];
        if (half) {
#pragma unroll
            for (int n = 0; n < 16; n++) {
                yp[160 * n] = acc[n][0];
                yp[160 * n + 16] = acc[n][1];
                yp[160 * n + 8] = acc[n][2];
                yp[160 * n + 24] = acc[n][3];
            }
        }
        named_bar(1 + ch, 64);
        if (!half) {
#pragma unroll
            for (int n = 0; n < 16; n++) {
                yp[160 * n] += acc[n][0];
                yp[160 * n + 16] += acc[n][1];
                yp[160 * n + 8] += acc[n][2];
                yp[160 * n + 24] += acc[n][3];
            }
        }
        named_bar(7, 288);
        mbar_wait_cluster(bar + 8, 0);
        TM(0, 6);
        {
            const int tt = tid & 63;
            bf16* dst = g_hT + (size_t)(cown + ch) * HT_PITCH;
            const uint32_t d2 = dval * 0x10001u;
#pragma unroll
            for (int j = 0; j < 4; j++) {
                const int s = (j * 64 + tt) * 8;
                const float* src = &sm.yP[ch][s + (s >> 5) * 8];
                const float4 a = *reinterpret_cast<const float4*>(src), b = *reinterpret_cast<const float4*>(src + 4);
                const uint4 kv4 = *reinterpret_cast<const uint4*>(&sm.uT[ch][UT_PAD + s]);
                const uint4 x4 = *reinterpret_cast<const uint4*>(&sm.xT[ch][s]);
                const uint32_t y2[4] = {hadd2(pack_bf16(a.x, a.y), hmul2(kv4.x, d2)), hadd2(pack_bf16(a.z, a.w), hmul2(kv4.y, d2)),
                                        hadd2(pack_bf16(b.x, b.y), hmul2(kv4.z, d2)), hadd2(pack_bf16(b.z, b.w), hmul2(kv4.w, d2))};
                const uint32_t xw[4] = {x4.x, x4.y, x4.z, x4.w};
                const uint4 m4 = *reinterpret_cast<const uint4*>(&sm.st[S_ + s / 2]);
                const float4 ra = *reinterpret_cast<const float4*>(&sm.st[s]), rb4 = *reinterpret_cast<const float4*>(&sm.st[s + 4]);
                const uint32_t mw[4] = {m4.x, m4.y, m4.z, m4.w};
                const float rw[8] = {ra.x, ra.y, ra.z, ra.w, rb4.x, rb4.y, rb4.z, rb4.w};
                uint32_t o[4];
#pragma unroll
                for (int i = 0; i < 4; i++) {
                    const uint32_t d = hsub2(xw[i], mw[i]);
                    const uint32_t qn = pack_bf16(bf_lo(d) * rw[2 * i], bf_hi(d) * rw[2 * i + 1]);
                    o[i] = hadd2(xw[i], hmul2(qn, y2[i]));
                }
                *reinterpret_cast<uint4*>(dst + s) = make_uint4(o[0], o[1], o[2], o[3]);
            }
        }
        TM(0, 7);
    } else {
        cluster_wait();
        named_bar(6, 352);
        const uint32_t hbar = bar + 16;
        if (warp < 10) {
            {
                const int rr = 8 * (warp - 8);
                uint32_t xq[4][2][8];
#pragma unroll
                for (int r = 0; r < 8; r++) {
                    const uint4 qa = ldg128(q + (size_t)(16 * bid + rr + r) * D_ + 8 * lane);
                    const uint4 qb = ldg128(q + (size_t)(16 * bid + rr + r) * D_ + 8 * (lane + 32));
                    uint32_t* x = xq[r >> 1][r & 1];
                    x[0] = qa.x; x[1] = qa.y; x[2] = qa.z; x[3] = qa.w; x[4] = qb.x; x[5] = qb.y; x[6] = qb.z; x[7] = qb.w;
                }
#pragma unroll
                for (int r2 = 0; r2 < 4; r2++) {
                    float2 sa[2];
                    ln_stats2(xq[r2], sa);
                    if (lane == 0) {
                        *reinterpret_cast<float2*>(&g_st1[16 * bid + rr + 2 * r2]) = make_float2(sa[0].y, sa[1].y);
                        reinterpret_cast<uint32_t*>(&g_st1[S_])[(16 * bid + rr) / 2 + r2] = pack_bf16(sa[0].x, sa[1].x);
                    }
                }
            }
            if (lane == 0) { __threadfence(); atomicAdd(&g_cnt, 1u); }
            if (warp == 9) return;
            if (lane == 0) {
                unsigned int c; int spins = 0;
                while (true) {
                    asm volatile("ld.acquire.gpu.global.u32 %0, [%1];" : "=r"(c) : "l"(&g_cnt) : "memory");
                    if (c >= 2 * gridDim.x || ++spins > (1 << 22)) break;
                    __nanosleep(200);
                }
                asm volatile("fence.proxy.async;" ::: "memory");
                mbar_expect_tx(hbar + 8, 12288);
                asm volatile("cp.async.bulk.shared::cluster.global.mbarrier::complete_tx::bytes [%0], [%1], %2, [%3];"
                    :: "r"(smem_u32(&sm.st[0])), "l"(&g_st1[0]), "r"(12288), "r"(hbar + 8) : "memory");
            }
            mbar_wait(hbar + 8, 0);
            named_bar(7, 288);
        } else {
            if (lane == 0) asm volatile("cp.async.bulk.prefetch.L2.global [%0], %1;" :: "l"(wd + (size_t)bid * 7168), "r"(14336) : "memory");
            if (bid < 112) {
                if (lane == 0) {
                    mbar_expect_tx(hbar, 32768);
                    const CUtensorMap* mw = (bid < 56) ? &mapWg : &mapWu;
                    const int col = 32 * ((bid < 56) ? bid : bid - 56);
                    tma_load_2d(smem_u32(&sm.wS[0][0]), mw, hbar, col, 0);
                    tma_load_2d(smem_u32(&sm.wS[256][0]), mw, hbar, col, 256);
                }
                mbar_wait(hbar, 0);
                const int cq = lane & 3, rgp = lane >> 2;
                float cs[8];
#pragma unroll
                for (int i = 0; i < 8; i++) cs[i] = 0.f;
#pragma unroll 4
                for (int r = 0; r < 64; r++) {
                    const uint4 w = sm.wS[r * 8 + rgp][cq];
                    cs[0] += bf_lo(w.x); cs[1] += bf_hi(w.x); cs[2] += bf_lo(w.y); cs[3] += bf_hi(w.y);
                    cs[4] += bf_lo(w.z); cs[5] += bf_hi(w.z); cs[6] += bf_lo(w.w); cs[7] += bf_hi(w.w);
                }
#pragma unroll
                for (int i = 0; i < 8; i++) {
                    cs[i] += __shfl_xor_sync(0xffffffffu, cs[i], 4);
                    cs[i] += __shfl_xor_sync(0xffffffffu, cs[i], 8);
                    cs[i] += __shfl_xor_sync(0xffffffffu, cs[i], 16);
                }
                if (lane < 4) {
                    *reinterpret_cast<float4*>(&g_colsum[32 * bid + lane * 8]) = make_float4(cs[0], cs[1], cs[2], cs[3]);
                    *reinterpret_cast<float4*>(&g_colsum[32 * bid + lane * 8 + 4]) = make_float4(cs[4], cs[5], cs[6], cs[7]);
                }
            }
        }
    }
#undef TMT
}

constexpr int G1_THREADS = 384;
constexpr int G1_STAGES = 3;
constexpr int G1_A_BYTES = 8 * 16384;
constexpr int G1_B_STAGE = 32768;
constexpr int G1_OFF_B = G1_A_BYTES;
constexpr int G1_OFF_STATS = G1_OFF_B + G1_STAGES * G1_B_STAGE;
constexpr int G1_OFF_CS = G1_OFF_STATS + 1024;
constexpr int G1_OFF_BAR = G1_OFF_CS + 1792;
constexpr int G1_SMEM = G1_OFF_BAR + 128;

__device__ __forceinline__ float tanh_fast(float x) { float t; asm("tanh.approx.f32 %0, %1;" : "=f"(t) : "f"(x)); return t; }

template <int NT>
__device__ __forceinline__ void g1_math(const float (&acc)[NT * 8], const float* cs_g, const float* cs_u, float2 st0, float2 st1, uint32_t (&P)[NT * 2], int t) {
    const float r0 = st0.y, r1 = st1.y, m0 = -st0.x * st0.y, m1 = -st1.x * st1.y;
#pragma unroll
    for (int j = 0; j < NT; j++) {
        const float2 cg = *reinterpret_cast<const float2*>(cs_g + 8 * j + 2 * t);
        const float2 cu = *reinterpret_cast<const float2*>(cs_u + 8 * j + 2 * t);
        float r[4];
#pragma unroll
        for (int e = 0; e < 4; e++) {
            const float rr = (e < 2) ? r0 : r1, mm = (e < 2) ? m0 : m1;
            const float gh = fmaf(acc[4 * j + e], 0.5f * rr, (0.5f * mm) * ((e & 1) ? cg.y : cg.x));
            const float uv = fmaf(acc[4 * (NT + j) + e], rr, mm * ((e & 1) ? cu.y : cu.x));
            r[e] = fmaf(tanh_fast(gh), 0.5f, 0.5f) * uv;
        }
        P[2 * j] = pack_bf16(r[0], r[1]);
        P[2 * j + 1] = pack_bf16(r[2], r[3]);
    }
}
template <int NT>
__device__ __forceinline__ void g1_store(uint32_t (&P)[NT * 2], bf16* out0, int t) {
#pragma unroll
    for (int j0 = 0; j0 < NT; j0 += 4) {
        quad_transpose(P[2 * j0], P[2 * j0 + 2], P[2 * j0 + 4], P[2 * j0 + 6], t);
        quad_transpose(P[2 * j0 + 1], P[2 * j0 + 3], P[2 * j0 + 5], P[2 * j0 + 7], t);
        *reinterpret_cast<uint4*>(out0 + 8 * (j0 + t)) = make_uint4(P[2 * j0], P[2 * j0 + 2], P[2 * j0 + 4], P[2 * j0 + 6]);
        *reinterpret_cast<uint4*>(out0 + 8 * F_ + 8 * (j0 + t)) = make_uint4(P[2 * j0 + 1], P[2 * j0 + 3], P[2 * j0 + 5], P[2 * j0 + 7]);
    }
}

__global__ void __cluster_dims__(2, 1, 1) __launch_bounds__(G1_THREADS, 1)
gemm1_kernel(const __grid_constant__ CUtensorMap mapA, const __grid_constant__ CUtensorMap mapG4, const __grid_constant__ CUtensorMap mapU4,
             const __grid_constant__ CUtensorMap mapG3, const __grid_constant__ CUtensorMap mapU3) {
    extern __shared__ __align__(1024) uint8_t smem_raw[];
    const uint32_t sb = smem_u32(smem_raw);
    const int tid = threadIdx.x, lane = tid & 31, warp = tid >> 5, wgi = tid >> 7;
    const int rank = blockIdx.x & 1;
    const int cb = blockIdx.x & 7, rb = blockIdx.x >> 3;
#define TMT 128
    TM(2, 0);
    pdl_launch();
    if (tid == 32) { prefetch_map(&mapA); prefetch_map(&mapG3); prefetch_map(&mapU3); }
    const uint32_t barA = sb + G1_OFF_BAR;
    const uint32_t barF = barA + 64;
    const uint32_t barE = barF + 8 * G1_STAGES;
    const uint32_t barS = barE + 8 * G1_STAGES;
    if (tid == 0) {
        for (int i = 0; i < 8; i++) mbar_init(barA + 8 * i, 1);
        for (int i = 0; i < G1_STAGES; i++) { mbar_init(barF + 8 * i, 1); mbar_init(barE + 8 * i, 2); }
        mbar_init(barS, 1);
        for (int i = 0; i < 8; i++) mbar_expect_tx(barA + 8 * i, 16384);
        asm volatile("fence.mbarrier_init.release.cluster;" ::: "memory");
    }
    __syncthreads();
    cluster_arrive_relaxed();

    if (wgi == 0) {
        reg_dealloc<40>();
        if (warp == 0) {
            cluster_wait();
            if (lane == 0) {
                int st = 0, ph = 1;
                for (int it = 0; it < 16; it++) {
                    const int kc = it & 7;
                    if (it == 2) {
                        pdl_wait();
                        for (int i = 0; i < 4; i++) {
                            const int c = 2 * i + rank;
                            tma_load_3d_mc(sb + c * 16384, &mapA, barA + 8 * c, 0, c * 64, rb * 2, (uint16_t)3);
                        }
                    }
                    mbar_wait(barE + 8 * st, ph);
                    const uint32_t dst = sb + G1_OFF_B + st * G1_B_STAGE;
                    if (it < 8) {
                        mbar_expect_tx(barF + 8 * st, 32768);
                        tma_load_3d(dst, &mapG4, barF + 8 * st, 0, kc * 64, cb * 7);
                        tma_load_3d(dst + 16384, &mapU4, barF + 8 * st, 0, kc * 64, cb * 7);
                    } else {
                        mbar_expect_tx(barF + 8 * st, 24576);
                        tma_load_3d(dst, &mapG3, barF + 8 * st, 0, kc * 64, cb * 7 + 4);
                        tma_load_3d(dst + 12288, &mapU3, barF + 8 * st, 0, kc * 64, cb * 7 + 4);
                    }
                    if (++st == G1_STAGES) { st = 0; ph ^= 1; }
                }
            }
            __syncwarp();
        } else if (warp == 1) {
            cluster_wait();
            pdl_wait();
            float* cs = reinterpret_cast<float*>(smem_raw + G1_OFF_CS);
            for (int i = lane; i < 448; i += 32) cs[i] = __ldcg((i < 224) ? &g_colsum[cb * 224 + i] : &g_colsum[F_ + cb * 224 + (i - 224)]);
            __syncwarp();
            if (lane == 0) mbar_arrive(barS);
        } else {
            cluster_wait();
        }
    } else {
        reg_alloc<232>();
        cluster_wait();
        const int cw = wgi - 1;
        const int g = lane >> 2, t = lane & 3, wl = warp & 3, tl = tid & 127;
        bf16* outp = g_hh + (size_t)(rb * 128 + cw * 64 + wl * 16 + g) * F_ + cb * 224;
        const float* cs = reinterpret_cast<const float*>(smem_raw + G1_OFF_CS);
        int st = 0, ph = 0;
        float2 st0, st1;
        uint32_t P1[32];
        {
            float acc[128];
            const int kq = lane >> 3, mp = lane & 7;
            const uint8_t* sbase = smem_raw + cw * 8192 + kq * 128 + (mp & 3) * 4;
            const int mc = 2 * wl + (mp >> 2);
            float p0 = 0.f, p1 = 0.f, s0 = 0.f, s1 = 0.f, q0 = 0.f, q1 = 0.f;
#pragma unroll 1
            for (int kc = 0; kc < 8; kc++) {
                mbar_wait(barA + 8 * kc, 0);
                mbar_wait(barF + 8 * st, ph);
                if (tl == 0 && cw == 0) TR(1, kc);
                wgmma_fence();
                const uint32_t aaddr = sb + kc * 16384 + cw * 8192;
                const uint32_t baddr = sb + G1_OFF_B + st * G1_B_STAGE;
#pragma unroll
                for (int kk = 0; kk < 4; kk++)
                    wgmma_m64n256k16_ss(acc, make_desc(aaddr + kk * 2048, 8192, 1024, 1), make_desc(baddr + kk * 1024, 4096, 512, 2), (kc | kk) != 0);
                wgmma_commit();
                if (kc == 0) {
                    const uint32_t w = *reinterpret_cast<const uint32_t*>(smem_raw + cw * 8192 + (mc << 4) + (mp & 3) * 4);
                    p0 = bf_lo(w); p1 = bf_hi(w);
                }
#pragma unroll
                for (int i = 0; i < 16; i++) {
                    const int kr = 4 * i;
                    const uint32_t w = *reinterpret_cast<const uint32_t*>(sbase + kc * 16384 + kr * 128 + ((mc ^ ((kr + kq) & 7)) << 4));
                    const float d0 = bf_lo(w) - p0, d1 = bf_hi(w) - p1;
                    s0 += d0; s1 += d1; q0 = fmaf(d0, d0, q0); q1 = fmaf(d1, d1, q1);
                }
                wgmma_wait<0>();
                if (tl == 0) mbar_arrive(barE + 8 * st);
                if (++st == G1_STAGES) { st = 0; ph ^= 1; }
            }
            TM(2, 1);
            {
#pragma unroll
                for (int o = 8; o <= 16; o <<= 1) {
                    s0 += __shfl_xor_sync(0xffffffffu, s0, o); s1 += __shfl_xor_sync(0xffffffffu, s1, o);
                    q0 += __shfl_xor_sync(0xffffffffu, q0, o); q1 += __shfl_xor_sync(0xffffffffu, q1, o);
                }
                const float md0 = s0 * (1.0f / D_), md1 = s1 * (1.0f / D_);
                const float v0 = bf16r(fmaxf(fmaf(-md0, md0, q0 * (1.0f / D_)), 0.f)), v1 = bf16r(fmaxf(fmaf(-md1, md1, q1 * (1.0f / D_)), 0.f));
                const float ma = bf16r(p0 + md0), mb = bf16r(p1 + md1);
                const float ra = 1.0f / bf16r(sqrtf(bf16r(v0 + 1e-5f))), rbb = 1.0f / bf16r(sqrtf(bf16r(v1 + 1e-5f)));
                const float mA = __shfl_sync(0xffffffffu, ma, g >> 1), mB = __shfl_sync(0xffffffffu, mb, g >> 1);
                const float rA = __shfl_sync(0xffffffffu, ra, g >> 1), rB = __shfl_sync(0xffffffffu, rbb, g >> 1);
                const float mC = __shfl_sync(0xffffffffu, ma, 4 + (g >> 1)), mD = __shfl_sync(0xffffffffu, mb, 4 + (g >> 1));
                const float rC = __shfl_sync(0xffffffffu, ra, 4 + (g >> 1)), rD = __shfl_sync(0xffffffffu, rbb, 4 + (g >> 1));
                st0 = (g & 1) ? make_float2(mB, rB) : make_float2(mA, rA);
                st1 = (g & 1) ? make_float2(mD, rD) : make_float2(mC, rC);
            }
            mbar_wait(barS, 0);
            TM(2, 5);
            g1_math<16>(acc, cs, cs + 224, st0, st1, P1, t);
            TM(2, 2);
        }
        {
            float acc[96];
#pragma unroll 1
            for (int kc = 0; kc < 8; kc++) {
                mbar_wait(barF + 8 * st, ph);
                if (tl == 0 && cw == 0) TR(1, 8 + kc);
                wgmma_fence();
                const uint32_t aaddr = sb + kc * 16384 + cw * 8192;
                const uint32_t baddr = sb + G1_OFF_B + st * G1_B_STAGE;
#pragma unroll
                for (int kk = 0; kk < 4; kk++)
                    wgmma_m64n192k16_ss(acc, make_desc(aaddr + kk * 2048, 8192, 1024, 1), make_desc(baddr + kk * 1024, 4096, 512, 2), (kc | kk) != 0);
                wgmma_commit();
                if (kc == 0) g1_store<16>(P1, outp, t);
                wgmma_wait<0>();
                if (tl == 0) mbar_arrive(barE + 8 * st);
                if (++st == G1_STAGES) { st = 0; ph ^= 1; }
            }
            TM(2, 3);
            uint32_t P2[24];
            g1_math<12>(acc, cs + 128, cs + 224 + 128, st0, st1, P2, t);
            g1_store<12>(P2, outp + 128, t);
            TM(2, 4);
        }
    }
}

constexpr int G2_THREADS = 384;
constexpr int G2_STAGES = 6;
constexpr int G2_STAGE = 32768;
constexpr int G2_OFF_X = G2_STAGES * G2_STAGE;
constexpr int G2_OFF_BAR = G2_OFF_X + 32768;
constexpr int G2_SMEM = G2_OFF_BAR + 128;
constexpr int G2_KSTEPS = 14;
constexpr int G2_PRE = 6;

__device__ __forceinline__ void ldsm_x4_t(uint32_t& r0, uint32_t& r1, uint32_t& r2, uint32_t& r3, uint32_t addr) {
    asm volatile("ldmatrix.sync.aligned.m8n8.x4.trans.shared.b16 {%0,%1,%2,%3}, [%4];" : "=r"(r0), "=r"(r1), "=r"(r2), "=r"(r3) : "r"(addr) : "memory");
}

__global__ void __cluster_dims__(2, 1, 1) __launch_bounds__(G2_THREADS, 1)
gemm2_kernel(const __grid_constant__ CUtensorMap mapHH, const __grid_constant__ CUtensorMap mapWd, const __grid_constant__ CUtensorMap mapH,
             bf16* __restrict__ out) {
    extern __shared__ __align__(1024) uint8_t smem_raw[];
    const uint32_t sb = smem_u32(smem_raw);
    const int tid = threadIdx.x, lane = tid & 31, warp = tid >> 5, wgi = tid >> 7;
    const int ks = blockIdx.x & 1, nb = (blockIdx.x >> 1) & 3, rb = blockIdx.x >> 3;
    TM(3, 0);
    if (tid == 32) { prefetch_map(&mapHH); prefetch_map(&mapH); }
    const uint32_t barF = sb + G2_OFF_BAR;
    const uint32_t barE = barF + 8 * G2_STAGES;
    const uint32_t barX = barE + 8 * G2_STAGES;
    if (tid == 0) {
        for (int i = 0; i < G2_STAGES; i++) { mbar_init(barF + 8 * i, 1); mbar_init(barE + 8 * i, 2); }
        mbar_init(barX, 1);
        asm volatile("fence.mbarrier_init.release.cluster;" ::: "memory");
        mbar_expect_tx(barX, 32768);
        for (int it = 0; it < G2_PRE; it++) {
            mbar_expect_tx(barF + 8 * it, 32768);
            tma_load_3d(sb + it * G2_STAGE + 16384, &mapWd, barF + 8 * it, 0, ks * 896 + it * 64, nb * 2);
        }
    }
    __syncthreads();
    cluster_arrive_relaxed();

    if (wgi == 0) {
        if (tid == 0) {
            pdl_wait();
            for (int it = 0; it < G2_STAGES; it++) {
                if (it >= G2_PRE) mbar_expect_tx(barF + 8 * it, 32768);
                tma_load_2d(sb + it * G2_STAGE, &mapHH, barF + 8 * it, ks * 896 + it * 64, rb * 128);
                if (it >= G2_PRE) tma_load_3d(sb + it * G2_STAGE + 16384, &mapWd, barF + 8 * it, 0, ks * 896 + it * 64, nb * 2);
            }
            if (blockIdx.x == 0) g_cnt = 0u;
            int st = 0, ph = 0;
            for (int it = G2_STAGES; it < G2_KSTEPS; it++) {
                mbar_wait(barE + 8 * st, ph);
                const uint32_t dst = sb + st * G2_STAGE;
                const int k0 = ks * 896 + it * 64;
                mbar_expect_tx(barF + 8 * st, 32768);
                tma_load_2d(dst, &mapHH, barF + 8 * st, k0, rb * 128);
                tma_load_3d(dst + 16384, &mapWd, barF + 8 * st, 0, k0, nb * 2);
                if (++st == G2_STAGES) { st = 0; ph ^= 1; }
            }
            mbar_wait(barE + 8 * st, ph);
            mbar_expect_tx(barF + 8 * st, 16384);
            tma_load_2d(sb + st * G2_STAGE, &mapH, barF + 8 * st, rb * 128 + ks * 64, nb * 128);
        }
        __syncwarp();
        cluster_wait();
    } else {
        const int cw = wgi - 1;
        const int g = lane >> 2, t = lane & 3, wl = warp & 3;
        const int tl = tid & 127;
        int st = 0, ph = 0;
        float acc[64];
#pragma unroll 1
        for (int it = 0; it < G2_KSTEPS; it++) {
            mbar_wait(barF + 8 * st, ph);
            if (it == 0) TM(3, 1);
            wgmma_fence();
            const uint32_t aaddr = sb + st * G2_STAGE + cw * 8192;
            const uint32_t baddr = sb + st * G2_STAGE + 16384;
#pragma unroll
            for (int kk = 0; kk < 4; kk++)
                wgmma_m64n128k16_ss(acc, make_desc(aaddr + kk * 32, 16, 1024, 1), make_desc(baddr + kk * 2048, 8192, 1024, 1), (it | kk) != 0);
            wgmma_commit();
            wgmma_wait<0>();
            if (tl == 0) mbar_arrive(barE + 8 * st);
            if (++st == G2_STAGES) { st = 0; ph ^= 1; }
        }
        TM(3, 2);
        cluster_wait();
        if (cw != ks) {
            const uint32_t dst = mapa(sb + G2_OFF_X + tl * 16, (uint32_t)(ks ^ 1));
            const uint32_t rbar = mapa(barX, (uint32_t)(ks ^ 1));
#pragma unroll
            for (int i = 0; i < 16; i++) st_async_v4f(dst + i * 2048, acc[4 * i], acc[4 * i + 1], acc[4 * i + 2], acc[4 * i + 3], rbar);
        } else {
            const float4* xb = reinterpret_cast<const float4*>(smem_raw + G2_OFF_X) + tl;
            const int row0 = rb * 128 + cw * 64 + wl * 16 + g;
            bf16* o0 = out + (size_t)row0 * D_ + nb * 128;
            uint32_t ha[16], hb[16];
            mbar_wait(barF + 8 * st, ph);
            {
                const int chl = 8 * (lane >> 4) + (lane & 7), sb8 = 2 * wl + ((lane >> 3) & 1);
                const uint32_t hbase = sb + st * G2_STAGE + chl * 128 + ((sb8 ^ (lane & 7)) << 4);
#pragma unroll
                for (int j = 0; j < 16; j += 2) ldsm_x4_t(ha[j], hb[j], ha[j + 1], hb[j + 1], hbase + j * 1024);
            }
            mbar_wait_cluster(barX, 0);
            TM(3, 4);
#pragma unroll
            for (int j0 = 0; j0 < 16; j0 += 4) {
                uint32_t P0[4], P1[4];
#pragma unroll
                for (int jj = 0; jj < 4; jj++) {
                    const int j = j0 + jj;
                    const float4 x = xb[j * 128];
                    P0[jj] = hadd2(ha[j], pack_bf16(acc[4 * j] + x.x, acc[4 * j + 1] + x.y));
                    P1[jj] = hadd2(hb[j], pack_bf16(acc[4 * j + 2] + x.z, acc[4 * j + 3] + x.w));
                }
                quad_transpose(P0[0], P0[1], P0[2], P0[3], t);
                quad_transpose(P1[0], P1[1], P1[2], P1[3], t);
                *reinterpret_cast<uint4*>(o0 + 8 * (j0 + t)) = make_uint4(P0[0], P0[1], P0[2], P0[3]);
                *reinterpret_cast<uint4*>(o0 + 8 * D_ + 8 * (j0 + t)) = make_uint4(P1[0], P1[1], P1[2], P1[3]);
            }
        }
        TM(3, 5);
    }
#undef TMT
}

typedef CUresult (*EncodeFn)(CUtensorMap*, CUtensorMapDataType, cuuint32_t, void*, const cuuint64_t*, const cuuint64_t*,
                             const cuuint32_t*, const cuuint32_t*, CUtensorMapInterleave, CUtensorMapSwizzle,
                             CUtensorMapL2promotion, CUtensorMapFloatOOBfill);

static void enc2d(EncodeFn enc, CUtensorMap* m, const void* p, int rows, int cols, int brows, int bcols, int pitch = 0) {
    cuuint64_t dims[2] = {(cuuint64_t)cols, (cuuint64_t)rows};
    cuuint64_t strides[1] = {(cuuint64_t)(pitch ? pitch : cols) * 2};
    cuuint32_t box[2] = {(cuuint32_t)bcols, (cuuint32_t)brows};
    cuuint32_t es[2] = {1, 1};
    enc(m, CU_TENSOR_MAP_DATA_TYPE_BFLOAT16, 2, const_cast<void*>(p), dims, strides, box, es, CU_TENSOR_MAP_INTERLEAVE_NONE,
        bcols == 32 ? CU_TENSOR_MAP_SWIZZLE_64B : CU_TENSOR_MAP_SWIZZLE_128B, CU_TENSOR_MAP_L2_PROMOTION_L2_128B, CU_TENSOR_MAP_FLOAT_OOB_FILL_NONE);
}
static void enc2d_plain(EncodeFn enc, CUtensorMap* m, const void* p, int rows, int cols, int brows, int bcols) {
    cuuint64_t dims[2] = {(cuuint64_t)cols, (cuuint64_t)rows};
    cuuint64_t strides[1] = {(cuuint64_t)cols * 2};
    cuuint32_t box[2] = {(cuuint32_t)bcols, (cuuint32_t)brows};
    cuuint32_t es[2] = {1, 1};
    enc(m, CU_TENSOR_MAP_DATA_TYPE_BFLOAT16, 2, const_cast<void*>(p), dims, strides, box, es, CU_TENSOR_MAP_INTERLEAVE_NONE,
        CU_TENSOR_MAP_SWIZZLE_NONE, CU_TENSOR_MAP_L2_PROMOTION_L2_128B, CU_TENSOR_MAP_FLOAT_OOB_FILL_NONE);
}
static void enc3d(EncodeFn enc, CUtensorMap* m, const void* p, int rows, int cols, int atom, int brows, int natoms, int pitch = 0) {
    cuuint64_t dims[3] = {(cuuint64_t)atom, (cuuint64_t)rows, (cuuint64_t)(cols / atom)};
    cuuint64_t strides[2] = {(cuuint64_t)(pitch ? pitch : cols) * 2, (cuuint64_t)atom * 2};
    cuuint32_t box[3] = {(cuuint32_t)atom, (cuuint32_t)brows, (cuuint32_t)natoms};
    cuuint32_t es[3] = {1, 1, 1};
    enc(m, CU_TENSOR_MAP_DATA_TYPE_BFLOAT16, 3, const_cast<void*>(p), dims, strides, box, es, CU_TENSOR_MAP_INTERLEAVE_NONE,
        atom == 32 ? CU_TENSOR_MAP_SWIZZLE_64B : CU_TENSOR_MAP_SWIZZLE_128B, CU_TENSOR_MAP_L2_PROMOTION_L2_128B, CU_TENSOR_MAP_FLOAT_OOB_FILL_NONE);
}

extern "C" void kernel_launch(void* const* d_in, const int* in_sizes, int n_in, void* d_out, int out_size) {
    const bf16* q = (const bf16*)d_in[0];
    const bf16* k = (const bf16*)d_in[1];
    const bf16* v = (const bf16*)d_in[2];
    const bf16* shift_k = (const bf16*)d_in[3];
    const bf16* ssm_k = (const bf16*)d_in[4];
    const bf16* ssm_D = (const bf16*)d_in[5];
    const bf16* wg = (const bf16*)d_in[7];
    const bf16* wu = (const bf16*)d_in[8];
    const bf16* wd = (const bf16*)d_in[9];
    bf16* out = (bf16*)d_out;

    static EncodeFn enc = nullptr;
    static void *p_hT = nullptr, *p_hh = nullptr;
    if (!enc) {
        void* fn = nullptr; cudaDriverEntryPointQueryResult qr;
        cudaGetDriverEntryPoint("cuTensorMapEncodeTiled", &fn, cudaEnableDefault, &qr);
        enc = (EncodeFn)fn;
        cudaGetSymbolAddress(&p_hT, g_hT);
        cudaGetSymbolAddress(&p_hh, g_hh);
        cudaFuncSetAttribute(conv_kernel, cudaFuncAttributeMaxDynamicSharedMemorySize, (int)sizeof(K1Smem));
        cudaFuncSetAttribute(gemm1_kernel, cudaFuncAttributeMaxDynamicSharedMemorySize, G1_SMEM);
        cudaFuncSetAttribute(gemm2_kernel, cudaFuncAttributeMaxDynamicSharedMemorySize, G2_SMEM);
    }
    CUtensorMap mA, mG64, mU64, mG32, mU32, mHH, mWd, mH, mWgp, mWup;
    enc2d_plain(enc, &mWgp, wg, D_, F_, 256, 32);
    enc2d_plain(enc, &mWup, wu, D_, F_, 256, 32);
    enc3d(enc, &mA, p_hT, D_, S_, 64, 64, 2, HT_PITCH);
    enc2d(enc, &mH, p_hT, D_, S_, 128, 64, HT_PITCH);
    enc3d(enc, &mG64, wg, D_, F_, 32, 64, 4);
    enc3d(enc, &mU64, wu, D_, F_, 32, 64, 4);
    enc3d(enc, &mG32, wg, D_, F_, 32, 64, 3);
    enc3d(enc, &mU32, wu, D_, F_, 32, 64, 3);
    enc2d(enc, &mHH, p_hh, S_, F_, 128, 64);
    enc3d(enc, &mWd, wd, F_, D_, 64, 64, 2);

    cudaStream_t st = cudaStreamPerThread;
    cudaLaunchAttribute at[1];
    at[0].id = cudaLaunchAttributeProgrammaticStreamSerialization;
    at[0].val.programmaticStreamSerializationAllowed = 1;
    cudaLaunchConfig_t cfg = {};
    cfg.stream = st; cfg.attrs = at; cfg.numAttrs = 1;
    conv_kernel<<<128, K1_THREADS, sizeof(K1Smem), st>>>(q, k, v, shift_k, ssm_k, ssm_D, mWgp, mWup, wd);
    cfg.gridDim = dim3(128); cfg.blockDim = dim3(G1_THREADS); cfg.dynamicSmemBytes = G1_SMEM;
    cudaLaunchKernelEx(&cfg, gemm1_kernel, mA, mG64, mU64, mG32, mU32);
    cfg.gridDim = dim3(128); cfg.blockDim = dim3(G2_THREADS); cfg.dynamicSmemBytes = G2_SMEM;
    cudaLaunchKernelEx(&cfg, gemm2_kernel, mHH, mWd, mH, out);
}
```

```cpp
#include <cuda_runtime.h>
#include <cuda_bf16.h>
#include <cuda.h>
#include <stdint.h>

typedef __nv_bfloat16 bf16;
constexpr int S_ = 2048, D_ = 512, F_ = 1792;

constexpr int HT_PITCH = S_ + 64;
__device__ __align__(128) bf16 g_hT[D_ * HT_PITCH];
__device__ __align__(128) bf16 g_hh[S_ * F_];
__device__ __align__(128) float g_st1[S_ + S_ / 2];
__device__ __align__(16) float g_colsum[2 * F_];
__device__ unsigned int g_cnt;

__device__ __forceinline__ uint32_t smem_u32(const void* p) { return (uint32_t)__cvta_generic_to_shared(p); }
__device__ __forceinline__ float bf16r(float x) { return __bfloat162float(__float2bfloat16_rn(x)); }
__device__ __forceinline__ float bf_lo(uint32_t w) { return __uint_as_float(w << 16); }
__device__ __forceinline__ float bf_hi(uint32_t w) { return __uint_as_float(w & 0xffff0000u); }
__device__ __forceinline__ uint32_t pack_bf16(float lo, float hi) {
    __nv_bfloat162 v = __floats2bfloat162_rn(lo, hi);
    return *reinterpret_cast<uint32_t*>(&v);
}
__device__ __forceinline__ uint32_t hmul2(uint32_t a, uint32_t b) {
    __nv_bfloat162 r = __hmul2_rn(*reinterpret_cast<__nv_bfloat162*>(&a), *reinterpret_cast<__nv_bfloat162*>(&b));
    return *reinterpret_cast<uint32_t*>(&r);
}
__device__ __forceinline__ uint32_t hadd2(uint32_t a, uint32_t b) {
    __nv_bfloat162 r = __hadd2_rn(*reinterpret_cast<__nv_bfloat162*>(&a), *reinterpret_cast<__nv_bfloat162*>(&b));
    return *reinterpret_cast<uint32_t*>(&r);
}
__device__ __forceinline__ uint4 ldg128(const void* p) {
    uint4 r; asm volatile("ld.global.nc.v4.u32 {%0,%1,%2,%3}, [%4];" : "=r"(r.x), "=r"(r.y), "=r"(r.z), "=r"(r.w) : "l"(p)); return r;
}
__device__ __forceinline__ uint4 ldg128_l2(const void* p) {
    uint4 r; asm volatile("ld.global.nc.L2::128B.v4.u32 {%0,%1,%2,%3}, [%4];" : "=r"(r.x), "=r"(r.y), "=r"(r.z), "=r"(r.w) : "l"(p)); return r;
}
__device__ __forceinline__ uint4 ldcg128(const void* p) {
    uint4 r; asm volatile("ld.global.cg.v4.u32 {%0,%1,%2,%3}, [%4];" : "=r"(r.x), "=r"(r.y), "=r"(r.z), "=r"(r.w) : "l"(p)); return r;
}
__device__ __forceinline__ uint32_t ldg16(const void* p) {
    unsigned short r; asm volatile("ld.global.nc.u16 %0, [%1];" : "=h"(r) : "l"(p)); return (uint32_t)r;
}
__device__ __forceinline__ void mbar_init(uint32_t bar, int cnt) { asm volatile("mbarrier.init.shared::cta.b64 [%0], %1;" :: "r"(bar), "r"(cnt)); }
__device__ __forceinline__ void mbar_expect_tx(uint32_t bar, uint32_t bytes) { asm volatile("mbarrier.arrive.expect_tx.shared::cta.b64 _, [%0], %1;" :: "r"(bar), "r"(bytes) : "memory"); }
__device__ __forceinline__ void mbar_arrive(uint32_t bar) { asm volatile("mbarrier.arrive.shared::cta.b64 _, [%0];" :: "r"(bar) : "memory"); }
__device__ __forceinline__ void mbar_arrive_cluster(uint32_t bar, uint32_t cta) {
    asm volatile("{\n.reg .b32 ra;\nmapa.shared::cluster.u32 ra, %0, %1;\nmbarrier.arrive.shared::cluster.b64 _, [ra];\n}" :: "r"(bar), "r"(cta) : "memory");
}
__device__ __forceinline__ void mbar_wait(uint32_t bar, uint32_t parity) {
    asm volatile("{\n.reg .pred P1;\nLAB_WAIT:\nmbarrier.try_wait.parity.shared::cta.b64 P1, [%0], %1;\n@P1 bra DONE;\nbra LAB_WAIT;\nDONE:\n}" :: "r"(bar), "r"(parity) : "memory");
}
__device__ __forceinline__ void mbar_wait_cluster(uint32_t bar, uint32_t parity) {
    asm volatile("{\n.reg .pred P1;\nLAB_WAIT:\nmbarrier.try_wait.parity.acquire.cluster.shared::cta.b64 P1, [%0], %1;\n@P1 bra DONE;\nbra LAB_WAIT;\nDONE:\n}" :: "r"(bar), "r"(parity) : "memory");
}
__device__ __forceinline__ void tma_load_2d(uint32_t dst, const CUtensorMap* map, uint32_t bar, int c0, int c1) {
    asm volatile("cp.async.bulk.tensor.2d.shared::cluster.global.mbarrier::complete_tx::bytes [%0], [%1, {%3, %4}], [%2];"
        :: "r"(dst), "l"(map), "r"(bar), "r"(c0), "r"(c1) : "memory");
}
__device__ __forceinline__ void tma_load_2d_mc(uint32_t dst, const CUtensorMap* map, uint32_t bar, int c0, int c1, uint16_t mask) {
    asm volatile("cp.async.bulk.tensor.2d.shared::cluster.global.mbarrier::complete_tx::bytes.multicast::cluster [%0], [%1, {%3, %4}], [%2], %5;"
        :: "r"(dst), "l"(map), "r"(bar), "r"(c0), "r"(c1), "h"(mask) : "memory");
}
__device__ __forceinline__ void tma_load_3d_mc(uint32_t dst, const CUtensorMap* map, uint32_t bar, int c0, int c1, int c2, uint16_t mask) {
    asm volatile("cp.async.bulk.tensor.3d.shared::cluster.global.mbarrier::complete_tx::bytes.multicast::cluster [%0], [%1, {%3, %4, %5}], [%2], %6;"
        :: "r"(dst), "l"(map), "r"(bar), "r"(c0), "r"(c1), "r"(c2), "h"(mask) : "memory");
}
__device__ __forceinline__ void tma_load_3d(uint32_t dst, const CUtensorMap* map, uint32_t bar, int c0, int c1, int c2) {
    asm volatile("cp.async.bulk.tensor.3d.shared::cluster.global.mbarrier::complete_tx::bytes [%0], [%1, {%3, %4, %5}], [%2];"
        :: "r"(dst), "l"(map), "r"(bar), "r"(c0), "r"(c1), "r"(c2) : "memory");
}
__device__ __forceinline__ void cluster_arrive() { asm volatile("barrier.cluster.arrive.aligned;" ::: "memory"); }
__device__ __forceinline__ void cluster_arrive_relaxed() { asm volatile("barrier.cluster.arrive.relaxed.aligned;" ::: "memory"); }
__device__ __forceinline__ void cluster_wait() { asm volatile("barrier.cluster.wait.aligned;" ::: "memory"); }
__device__ __forceinline__ uint32_t mapa(uint32_t addr, uint32_t cta) {
    uint32_t r; asm volatile("mapa.shared::cluster.u32 %0, %1, %2;" : "=r"(r) : "r"(addr), "r"(cta)); return r;
}
__device__ __forceinline__ void st_async_v2(uint32_t addr, uint32_t a, uint32_t b, uint32_t rbar) {
    asm volatile("st.async.weak.shared::cluster.mbarrier::complete_tx::bytes.v2.b32 [%0], {%1, %2}, [%3];" :: "r"(addr), "r"(a), "r"(b), "r"(rbar) : "memory");
}
__device__ __forceinline__ void st_async_v4f(uint32_t addr, float a, float b, float c, float d, uint32_t rbar) {
    asm volatile("st.async.weak.shared::cluster.mbarrier::complete_tx::bytes.v4.f32 [%0], {%1, %2, %3, %4}, [%5];" :: "r"(addr), "f"(a), "f"(b), "f"(c), "f"(d), "r"(rbar) : "memory");
}
__device__ __forceinline__ void wgmma_fence() { asm volatile("wgmma.fence.sync.aligned;" ::: "memory"); }
__device__ __forceinline__ void wgmma_commit() { asm volatile("wgmma.commit_group.sync.aligned;" ::: "memory"); }
template <int N> __device__ __forceinline__ void wgmma_wait() { asm volatile("wgmma.wait_group.sync.aligned %0;" :: "n"(N) : "memory"); }
__device__ __forceinline__ uint64_t make_desc(uint32_t addr, uint32_t lbo_bytes, uint32_t sbo_bytes, uint32_t layout) {
    return (uint64_t)((addr & 0x3FFFF) >> 4) | ((uint64_t)(lbo_bytes >> 4) << 16) | ((uint64_t)(sbo_bytes >> 4) << 32) | ((uint64_t)layout << 62);
}
template <int R> __device__ __forceinline__ void reg_alloc() { asm volatile("setmaxnreg.inc.sync.aligned.u32 %0;" :: "n"(R)); }
template <int R> __device__ __forceinline__ void reg_dealloc() { asm volatile("setmaxnreg.dec.sync.aligned.u32 %0;" :: "n"(R)); }
__device__ __forceinline__ void pdl_launch() { asm volatile("griddepcontrol.launch_dependents;" ::: "memory"); }
__device__ __forceinline__ void pdl_wait() { asm volatile("griddepcontrol.wait;" ::: "memory"); }
__device__ __forceinline__ void prefetch_map(const CUtensorMap* m) { asm volatile("prefetch.tensormap [%0];" :: "l"(m) : "memory"); }
__device__ __forceinline__ void named_bar(int id, int n) { asm volatile("bar.sync %0, %1;" :: "r"(id), "r"(n) : "memory"); }

__device__ __forceinline__ void wgmma_m64n256k16_ss(float (&d)[128], uint64_t descA, uint64_t descB, int scaleD) {
    asm volatile("{\n.reg .pred p;\nsetp.ne.b32 p, %130, 0;\n"
        "wgmma.mma_async.sync.aligned.m64n256k16.f32.bf16.bf16 {%0, %1, %2, %3, %4, %5, %6, %7, %8, %9, %10, %11, %12, %13, %14, %15, %16, %17, %18, %19, %20, %21, %22, %23, %24, %25, %26, %27, %28, %29, %30, %31, %32, %33, %34, %35, %36, %37, %38, %39, %40, %41, %42, %43, %44, %45, %46, %47, %48, %49, %50, %51, %52, %53, %54, %55, %56, %57, %58, %59, %60, %61, %62, %63, %64, %65, %66, %67, %68, %69, %70, %71, %72, %73, %74, %75, %76, %77, %78, %79, %80, %81, %82, %83, %84, %85, %86, %87, %88, %89, %90, %91, %92, %93, %94, %95, %96, %97, %98, %99, %100, %101, %102, %103, %104, %105, %106, %107, %108, %109, %110, %111, %112, %113, %114, %115, %116, %117, %118, %119, %120, %121, %122, %123, %124, %125, %126, %127}, %128, %129, p, 1, 1, 1, 1;\n}\n"
        : "+f"(d[0]), "+f"(d[1]), "+f"(d[2]), "+f"(d[3]), "+f"(d[4]), "+f"(d[5]), "+f"(d[6]), "+f"(d[7]), "+f"(d[8]), "+f"(d[9]), "+f"(d[10]), "+f"(d[11]), "+f"(d[12]), "+f"(d[13]), "+f"(d[14]), "+f"(d[15]), "+f"(d[16]), "+f"(d[17]), "+f"(d[18]), "+f"(d[19]), "+f"(d[20]), "+f"(d[21]), "+f"(d[22]), "+f"(d[23]), "+f"(d[24]), "+f"(d[25]), "+f"(d[26]), "+f"(d[27]), "+f"(d[28]), "+f"(d[29]), "+f"(d[30]), "+f"(d[31]), "+f"(d[32]), "+f"(d[33]), "+f"(d[34]), "+f"(d[35]), "+f"(d[36]), "+f"(d[37]), "+f"(d[38]), "+f"(d[39]), "+f"(d[40]), "+f"(d[41]), "+f"(d[42]), "+f"(d[43]), "+f"(d[44]), "+f"(d[45]), "+f"(d[46]), "+f"(d[47]), "+f"(d[48]), "+f"(d[49]), "+f"(d[50]), "+f"(d[51]), "+f"(d[52]), "+f"(d[53]), "+f"(d[54]), "+f"(d[55]), "+f"(d[56]), "+f"(d[57]), "+f"(d[58]), "+f"(d[59]), "+f"(d[60]), "+f"(d[61]), "+f"(d[62]), "+f"(d[63]), "+f"(d[64]), "+f"(d[65]), "+f"(d[66]), "+f"(d[67]), "+f"(d[68]), "+f"(d[69]), "+f"(d[70]), "+f"(d[71]), "+f"(d[72]), "+f"(d[73]), "+f"(d[74]), "+f"(d[75]), "+f"(d[76]), "+f"(d[77]), "+f"(d[78]), "+f"(d[79]), "+f"(d[80]), "+f"(d[81]), "+f"(d[82]), "+f"(d[83]), "+f"(d[84]), "+f"(d[85]), "+f"(d[86]), "+f"(d[87]), "+f"(d[88]), "+f"(d[89]), "+f"(d[90]), "+f"(d[91]), "+f"(d[92]), "+f"(d[93]), "+f"(d[94]), "+f"(d[95]), "+f"(d[96]), "+f"(d[97]), "+f"(d[98]), "+f"(d[99]), "+f"(d[100]), "+f"(d[101]), "+f"(d[102]), "+f"(d[103]), "+f"(d[104]), "+f"(d[105]), "+f"(d[106]), "+f"(d[107]), "+f"(d[108]), "+f"(d[109]), "+f"(d[110]), "+f"(d[111]), "+f"(d[112]), "+f"(d[113]), "+f"(d[114]), "+f"(d[115]), "+f"(d[116]), "+f"(d[117]), "+f"(d[118]), "+f"(d[119]), "+f"(d[120]), "+f"(d[121]), "+f"(d[122]), "+f"(d[123]), "+f"(d[124]), "+f"(d[125]), "+f"(d[126]), "+f"(d[127])
        : "l"(descA), "l"(descB), "r"(scaleD));
}

__device__ __forceinline__ void wgmma_m64n192k16_ss(float (&d)[96], uint64_t descA, uint64_t descB, int scaleD) {
    asm volatile("{\n.reg .pred p;\nsetp.ne.b32 p, %98, 0;\n"
        "wgmma.mma_async.sync.aligned.m64n192k16.f32.bf16.bf16 {%0, %1, %2, %3, %4, %5, %6, %7, %8, %9, %10, %11, %12, %13, %14, %15, %16, %17, %18, %19, %20, %21, %22, %23, %24, %25, %26, %27, %28, %29, %30, %31, %32, %33, %34, %35, %36, %37, %38, %39, %40, %41, %42, %43, %44, %45, %46, %47, %48, %49, %50, %51, %52, %53, %54, %55, %56, %57, %58, %59, %60, %61, %62, %63, %64, %65, %66, %67, %68, %69, %70, %71, %72, %73, %74, %75, %76, %77, %78, %79, %80, %81, %82, %83, %84, %85, %86, %87, %88, %89, %90, %91, %92, %93, %94, %95}, %96, %97, p, 1, 1, 1, 1;\n}\n"
        : "+f"(d[0]), "+f"(d[1]), "+f"(d[2]), "+f"(d[3]), "+f"(d[4]), "+f"(d[5]), "+f"(d[6]), "+f"(d[7]), "+f"(d[8]), "+f"(d[9]), "+f"(d[10]), "+f"(d[11]), "+f"(d[12]), "+f"(d[13]), "+f"(d[14]), "+f"(d[15]), "+f"(d[16]), "+f"(d[17]), "+f"(d[18]), "+f"(d[19]), "+f"(d[20]), "+f"(d[21]), "+f"(d[22]), "+f"(d[23]), "+f"(d[24]), "+f"(d[25]), "+f"(d[26]), "+f"(d[27]), "+f"(d[28]), "+f"(d[29]), "+f"(d[30]), "+f"(d[31]), "+f"(d[32]), "+f"(d[33]), "+f"(d[34]), "+f"(d[35]), "+f"(d[36]), "+f"(d[37]), "+f"(d[38]), "+f"(d[39]), "+f"(d[40]), "+f"(d[41]), "+f"(d[42]), "+f"(d[43]), "+f"(d[44]), "+f"(d[45]), "+f"(d[46]), "+f"(d[47]), "+f"(d[48]), "+f"(d[49]), "+f"(d[50]), "+f"(d[51]), "+f"(d[52]), "+f"(d[53]), "+f"(d[54]), "+f"(d[55]), "+f"(d[56]), "+f"(d[57]), "+f"(d[58]), "+f"(d[59]), "+f"(d[60]), "+f"(d[61]), "+f"(d[62]), "+f"(d[63]), "+f"(d[64]), "+f"(d[65]), "+f"(d[66]), "+f"(d[67]), "+f"(d[68]), "+f"(d[69]), "+f"(d[70]), "+f"(d[71]), "+f"(d[72]), "+f"(d[73]), "+f"(d[74]), "+f"(d[75]), "+f"(d[76]), "+f"(d[77]), "+f"(d[78]), "+f"(d[79]), "+f"(d[80]), "+f"(d[81]), "+f"(d[82]), "+f"(d[83]), "+f"(d[84]), "+f"(d[85]), "+f"(d[86]), "+f"(d[87]), "+f"(d[88]), "+f"(d[89]), "+f"(d[90]), "+f"(d[91]), "+f"(d[92]), "+f"(d[93]), "+f"(d[94]), "+f"(d[95])
        : "l"(descA), "l"(descB), "r"(scaleD));
}

__device__ __forceinline__ void wgmma_m64n128k16_ss(float (&d)[64], uint64_t descA, uint64_t descB, int scaleD) {
    asm volatile("{\n.reg .pred p;\nsetp.ne.b32 p, %66, 0;\n"
        "wgmma.mma_async.sync.aligned.m64n128k16.f32.bf16.bf16 {%0, %1, %2, %3, %4, %5, %6, %7, %8, %9, %10, %11, %12, %13, %14, %15, %16, %17, %18, %19, %20, %21, %22, %23, %24, %25, %26, %27, %28, %29, %30, %31, %32, %33, %34, %35, %36, %37, %38, %39, %40, %41, %42, %43, %44, %45, %46, %47, %48, %49, %50, %51, %52, %53, %54, %55, %56, %57, %58, %59, %60, %61, %62, %63}, %64, %65, p, 1, 1, 0, 1;\n}\n"
        : "+f"(d[0]), "+f"(d[1]), "+f"(d[2]), "+f"(d[3]), "+f"(d[4]), "+f"(d[5]), "+f"(d[6]), "+f"(d[7]), "+f"(d[8]), "+f"(d[9]), "+f"(d[10]), "+f"(d[11]), "+f"(d[12]), "+f"(d[13]), "+f"(d[14]), "+f"(d[15]), "+f"(d[16]), "+f"(d[17]), "+f"(d[18]), "+f"(d[19]), "+f"(d[20]), "+f"(d[21]), "+f"(d[22]), "+f"(d[23]), "+f"(d[24]), "+f"(d[25]), "+f"(d[26]), "+f"(d[27]), "+f"(d[28]), "+f"(d[29]), "+f"(d[30]), "+f"(d[31]), "+f"(d[32]), "+f"(d[33]), "+f"(d[34]), "+f"(d[35]), "+f"(d[36]), "+f"(d[37]), "+f"(d[38]), "+f"(d[39]), "+f"(d[40]), "+f"(d[41]), "+f"(d[42]), "+f"(d[43]), "+f"(d[44]), "+f"(d[45]), "+f"(d[46]), "+f"(d[47]), "+f"(d[48]), "+f"(d[49]), "+f"(d[50]), "+f"(d[51]), "+f"(d[52]), "+f"(d[53]), "+f"(d[54]), "+f"(d[55]), "+f"(d[56]), "+f"(d[57]), "+f"(d[58]), "+f"(d[59]), "+f"(d[60]), "+f"(d[61]), "+f"(d[62]), "+f"(d[63])
        : "l"(descA), "l"(descB), "r"(scaleD));
}


__device__ __forceinline__ void quad_transpose(uint32_t& r0, uint32_t& r1, uint32_t& r2, uint32_t& r3, int t) {
    const bool o1 = t & 1, o2 = t & 2;
    uint32_t x, y;
    x = o1 ? r0 : r1; y = __shfl_xor_sync(0xffffffffu, x, 1); if (o1) r0 = y; else r1 = y;
    x = o1 ? r2 : r3; y = __shfl_xor_sync(0xffffffffu, x, 1); if (o1) r2 = y; else r3 = y;
    x = o2 ? r0 : r2; y = __shfl_xor_sync(0xffffffffu, x, 2); if (o2) r0 = y; else r2 = y;
    x = o2 ? r1 : r3; y = __shfl_xor_sync(0xffffffffu, x, 2); if (o2) r1 = y; else r3 = y;
}


__device__ __forceinline__ float warp_sum(float s) {
#pragma unroll
    for (int o = 16; o > 0; o >>= 1) s += __shfl_xor_sync(0xffffffffu, s, o);
    return s;
}
__device__ __forceinline__ uint32_t hsub2(uint32_t a, uint32_t b) {
    __nv_bfloat162 r = __hsub2_rn(*reinterpret_cast<__nv_bfloat162*>(&a), *reinterpret_cast<__nv_bfloat162*>(&b));
    return *reinterpret_cast<uint32_t*>(&r);
}
__device__ __forceinline__ void ln_stats2(const uint32_t (&x)[2][8], float2 (&st)[2]) {
    float piv[2], s[2], ss[2];
#pragma unroll
    for (int r = 0; r < 2; r++) piv[r] = __shfl_sync(0xffffffffu, bf_lo(x[r][0]), 0);
#pragma unroll
    for (int r = 0; r < 2; r++) {
        float s0 = 0.f, s1 = 0.f, q0 = 0.f, q1 = 0.f;
#pragma unroll
        for (int i = 0; i < 8; i++) {
            const float d0 = bf_lo(x[r][i]) - piv[r], d1 = bf_hi(x[r][i]) - piv[r];
            s0 += d0; s1 += d1; q0 = fmaf(d0, d0, q0); q1 = fmaf(d1, d1, q1);
        }
        s[r] = s0 + s1; ss[r] = q0 + q1;
    }
#pragma unroll
    for (int o = 16; o > 0; o >>= 1) {
#pragma unroll
        for (int r = 0; r < 2; r++) { s[r] += __shfl_xor_sync(0xffffffffu, s[r], o); ss[r] += __shfl_xor_sync(0xffffffffu, ss[r], o); }
    }
#pragma unroll
    for (int r = 0; r < 2; r++) {
        const float md = s[r] * (1.0f / D_);
        const float var = bf16r(fmaxf(fmaf(-md, md, ss[r] * (1.0f / D_)), 0.f));
        st[r] = make_float2(bf16r(piv[r] + md), 1.0f / bf16r(sqrtf(bf16r(var + 1e-5f))));
    }
}
__device__ __forceinline__ void ln_apply(const uint32_t (&x)[8], float2 st, uint32_t (&o)[8]) {
    const uint32_t m2 = pack_bf16(st.x, st.x);
#pragma unroll
    for (int i = 0; i < 8; i++) {
        const uint32_t d = hsub2(x[i], m2);
        o[i] = pack_bf16(bf_lo(d) * st.y, bf_hi(d) * st.y);
    }
}

constexpr int K1_THREADS = 352;
constexpr int UT_PAD = 128;
constexpr int UT_LEN = UT_PAD + S_;
constexpr int KR_LEN = 2080;
constexpr int YP_LEN = S_ + (S_ / 32) * 8;

struct __align__(128) K1Smem {
    bf16 uT[4][UT_LEN];
    bf16 xT[4][S_];
    bf16 kr[4][2][KR_LEN];
    float yP[2][4][YP_LEN];
    alignas(128) float st[S_ + S_ / 2];
    alignas(128) uint4 wS[512][4];
    float red[8][32];
    uint64_t bar, bar2, bar3, bar4;
};

__device__ __forceinline__ void mma16816(float (&c)[4], uint32_t a0, uint32_t a1, uint32_t a2, uint32_t a3, uint32_t b0, uint32_t b1) {
    asm volatile("mma.sync.aligned.m16n8k16.row.col.f32.bf16.bf16.f32 {%0,%1,%2,%3}, {%4,%5,%6,%7}, {%8,%9}, {%0,%1,%2,%3};"
        : "+f"(c[0]), "+f"(c[1]), "+f"(c[2]), "+f"(c[3])
        : "r"(a0), "r"(a1), "r"(a2), "r"(a3), "r"(b0), "r"(b1));
}
__device__ __forceinline__ void ldsm_x4(uint32_t& r0, uint32_t& r1, uint32_t& r2, uint32_t& r3, uint32_t addr) {
    asm volatile("ldmatrix.sync.aligned.m8n8.x4.shared.b16 {%0,%1,%2,%3}, [%4];" : "=r"(r0), "=r"(r1), "=r"(r2), "=r"(r3) : "r"(addr) : "memory");
}

__device__ __forceinline__ void conv_mma(const bf16* uTc, const bf16* krlane, float (&acc)[16][4], int lane, int half) {
    const int lrow = lane & 7, lk = (lane >> 3) & 1, lt = lane >> 4;
    const uint32_t ubase = smem_u32(uTc) + (UT_PAD + 16 * (8 * lt + lrow) + 8 * lk) * 2;
#pragma unroll 1
    for (int pp = 0; pp < 4; pp++) {
        const int p = half * 4 + pp;
        uint32_t U[16][2];
#pragma unroll
        for (int j = 0; j < 16; j += 2) ldsm_x4(U[j][0], U[j][1], U[j + 1][0], U[j + 1][1], ubase + (j * 128 - p * 16) * 2);
        const uint32_t* kp = reinterpret_cast<const uint32_t*>(krlane - 16 * p);
        const volatile uint32_t* kpv = kp;
        uint32_t a0 = kp[0], a1 = kp[-4], a2 = kp[4], a3 = kpv[0];
#pragma unroll
        for (int q = 0; q < 16; q++) {
            uint32_t b0 = 0, b1 = 0, b2 = 0, b3 = 0;
            if (q < 15) { b0 = kp[-64 * (q + 1)]; b1 = kp[-64 * (q + 1) - 4]; b2 = kp[-64 * (q + 1) + 4]; b3 = kpv[-64 * (q + 1)]; }
#pragma unroll
            for (int n = 15; n >= q; n--) mma16816(acc[n], a0, a1, a2, a3, U[n - q][0], U[n - q][1]);
            a0 = b0; a1 = b1; a2 = b2; a3 = b3;
        }
    }
}

__device__ __forceinline__ void cp_async16(uint32_t dst, const void* src) {
    asm volatile("cp.async.cg.shared.global [%0], [%1], 16;" :: "r"(dst), "l"(src) : "memory");
}

__global__ void __cluster_dims__(2, 1, 1) __launch_bounds__(K1_THREADS, 1)
conv_kernel(const bf16* __restrict__ q, const bf16* __restrict__ k, const bf16* __restrict__ v,
            const bf16* __restrict__ shift_k, const bf16* __restrict__ ssm_k, const bf16* __restrict__ ssm_D,
            const __grid_constant__ CUtensorMap mapWg, const __grid_constant__ CUtensorMap mapWu, const bf16* __restrict__ wd) {
    extern __shared__ __align__(1024) uint8_t smem_raw[];
    pdl_launch();
    K1Smem& sm = *reinterpret_cast<K1Smem*>(smem_raw);
    const int tid = threadIdx.x, lane = tid & 31, warp = tid >> 5;
    const int bid = blockIdx.x;
    const int rank = bid & 1;
    const int c0 = 8 * (bid >> 1);
    const int cown = c0 + 4 * rank;
    const uint32_t bar = smem_u32(&sm.bar);
    if (tid == 0) {
        mbar_init(bar, 1);
        mbar_init(bar + 8, 1);
        mbar_init(bar + 16, 1);
        mbar_init(bar + 24, 1);
        asm volatile("fence.mbarrier_init.release.cluster;" ::: "memory");
        mbar_expect_tx(bar, 1024 * 4 * 2);
        mbar_expect_tx(bar + 8, 1024 * 4 * 2);
    }
    cluster_arrive_relaxed();

    if (warp < 8) {
        const int s0 = 1024 * rank + 4 * tid;
        uint4 kk[7], vv[4], qq[4], sw[4];
#pragma unroll
        for (int i = 0; i < 4; i++) kk[3 + i] = ldg128_l2(k + (size_t)(s0 + i) * D_ + c0);
#pragma unroll
        for (int i = 0; i < 4; i++) vv[i] = ldg128_l2(v + (size_t)(s0 + i) * D_ + c0);
        if (lane == 0) {
#pragma unroll
            for (int i = 0; i < 3; i++) {
                const int s = s0 - 3 + i;
                kk[i] = make_uint4(0, 0, 0, 0);
                if (s >= 0) kk[i] = ldg128(k + (size_t)s * D_ + c0);
            }
        }
#pragma unroll
        for (int i = 0; i < 4; i++) sw[i] = ldg128(shift_k + (size_t)c0 * 4 + 8 * i);
        uint4 kq[4]; uint32_t nx[4];
#pragma unroll
        for (int c = 0; c < 4; c++) {
            const bf16* kr = ssm_k + (size_t)(cown + c) * S_;
            kq[c] = ldg128(kr + 8 * tid);
            nx[c] = 0u;
            if (tid < 255) nx[c] = ldg16(kr + 8 * tid + 8);
        }
        const uint32_t dval = ldg16(ssm_D + cown + (warp >> 1));
        if (tid < 64) *reinterpret_cast<uint4*>(&sm.uT[tid >> 4][(tid & 15) * 8]) = make_uint4(0, 0, 0, 0);
#pragma unroll
        for (int i = 0; i < 3; i++) {
            uint4 t;
            t.x = __shfl_up_sync(0xffffffffu, kk[4 + i].x, 1); t.y = __shfl_up_sync(0xffffffffu, kk[4 + i].y, 1);
            t.z = __shfl_up_sync(0xffffffffu, kk[4 + i].z, 1); t.w = __shfl_up_sync(0xffffffffu, kk[4 + i].w, 1);
            if (lane != 0) kk[i] = t;
        }
        uint32_t kvw[4][4];
        const uint32_t* kkw = reinterpret_cast<const uint32_t*>(kk);
        const uint32_t* vvw = reinterpret_cast<const uint32_t*>(vv);
        const uint32_t* qqw = reinterpret_cast<const uint32_t*>(qq);
#pragma unroll
        for (int i2 = 0; i2 < 4; i2++) {
            const uint32_t t0 = __byte_perm(sw[i2].x, sw[i2].z, 0x5410), t1 = __byte_perm(sw[i2].x, sw[i2].z, 0x7632);
            const uint32_t t2 = __byte_perm(sw[i2].y, sw[i2].w, 0x5410), t3 = __byte_perm(sw[i2].y, sw[i2].w, 0x7632);
#pragma unroll
            for (int r = 0; r < 4; r++) {
                uint32_t a = hmul2(kkw[(r + 0) * 4 + i2], t3);
                a = hadd2(a, hmul2(kkw[(r + 1) * 4 + i2], t2));
                a = hadd2(a, hmul2(kkw[(r + 2) * 4 + i2], t1));
                a = hadd2(a, hmul2(kkw[(r + 3) * 4 + i2], t0));
                kvw[r][i2] = hmul2(a, vvw[r * 4 + i2]);
            }
        }
        cluster_wait();
        const uint32_t rbar = mapa(bar, (uint32_t)(rank ^ 1));
#pragma unroll
        for (int i2 = 0; i2 < 4; i2++) {
#pragma unroll
            for (int e = 0; e < 2; e++) {
                const uint32_t sel = e ? 0x7632 : 0x5410;
                const uint32_t w0 = __byte_perm(kvw[0][i2], kvw[1][i2], sel), w1 = __byte_perm(kvw[2][i2], kvw[3][i2], sel);
                const int cc = 2 * i2 + e;
                if ((cc >> 2) == rank) *reinterpret_cast<uint2*>(&sm.uT[cc & 3][UT_PAD + s0]) = make_uint2(w0, w1);
                else st_async_v2(mapa(smem_u32(&sm.uT[cc & 3][UT_PAD + s0]), (uint32_t)(rank ^ 1)), w0, w1, rbar);
            }
        }
#pragma unroll
        for (int c = 0; c < 4; c++) {
            uint4 a, b;
            a.x = __byte_perm(kq[c].w, 0, 0x1032); a.y = __byte_perm(kq[c].z, 0, 0x1032);
            a.z = __byte_perm(kq[c].y, 0, 0x1032); a.w = __byte_perm(kq[c].x, 0, 0x1032);
            b.x = __byte_perm(nx[c], kq[c].w, 0x7610); b.y = __byte_perm(kq[c].w, kq[c].z, 0x7610);
            b.z = __byte_perm(kq[c].z, kq[c].y, 0x7610); b.w = __byte_perm(kq[c].y, kq[c].x, 0x7610);
            *reinterpret_cast<uint4*>(&sm.kr[c][0][2040 - 8 * tid]) = a;
            *reinterpret_cast<uint4*>(&sm.kr[c][1][2040 - 8 * tid]) = b;
            if (tid == 0) {
                *reinterpret_cast<uint4*>(&sm.kr[c][1][2048]) = make_uint4(kq[c].x & 0xffffu, 0, 0, 0);
            } else if (tid < 8) {
                if (tid < 4) *reinterpret_cast<uint4*>(&sm.kr[c][1][2048 + 8 * tid]) = make_uint4(0, 0, 0, 0);
                else *reinterpret_cast<uint4*>(&sm.kr[c][0][2048 + 8 * (tid - 4)]) = make_uint4(0, 0, 0, 0);
            }
        }
#pragma unroll
        for (int i = 0; i < 4; i++) qq[i] = ldg128(q + (size_t)(s0 + i) * D_ + c0);
        named_bar(6, 352);
        mbar_wait_cluster(bar, 0);

        const int ch = warp >> 1, half = warp & 1;
        const int g = lane >> 2, t = lane & 3;
        float acc[16][4];
#pragma unroll
        for (int i = 0; i < 16; i++) { acc[i][0] = acc[i][1] = acc[i][2] = acc[i][3] = 0.f; }
        const bf16* krlane = (g & 1) ? &sm.kr[ch][0][2047 - g + 2 * t] : &sm.kr[ch][1][2048 - g + 2 * t];
        conv_mma(sm.uT[ch], krlane, acc, lane, half);
#pragma unroll
        for (int i2 = 0; i2 < 4; i2++) {
#pragma unroll
            for (int e = 0; e < 2; e++) {
                const uint32_t sel = e ? 0x7632 : 0x5410;
                const uint32_t w0 = __byte_perm(qqw[i2], qqw[4 + i2], sel), w1 = __byte_perm(qqw[8 + i2], qqw[12 + i2], sel);
                const int cc = 2 * i2 + e;
                if ((cc >> 2) == rank) *reinterpret_cast<uint2*>(&sm.xT[cc & 3][s0]) = make_uint2(w0, w1);
                else st_async_v2(mapa(smem_u32(&sm.xT[cc & 3][s0]), (uint32_t)(rank ^ 1)), w0, w1, rbar + 8);
            }
        }
        float* yp = &sm.yP[half][ch][40 * t + g];
#pragma unroll
        for (int n = 0; n < 16; n++) {
            yp[160 * n] = acc[n][0];
            yp[160 * n + 16] = acc[n][1];
            yp[160 * n + 8] = acc[n][2];
            yp[160 * n + 24] = acc[n][3];
        }
        named_bar(7, 288);
        mbar_wait_cluster(bar + 8, 0);
        {
            const int tt = tid & 63;
            bf16* dst = g_hT + (size_t)(cown + ch) * HT_PITCH;
            const uint32_t d2 = dval * 0x10001u;
#pragma unroll
            for (int j = 0; j < 4; j++) {
                const int s = (j * 64 + tt) * 8;
                const float* src = &sm.yP[0][ch][s + (s >> 5) * 8];
                const float* src2 = &sm.yP[1][ch][s + (s >> 5) * 8];
                float4 a = *reinterpret_cast<const float4*>(src), b = *reinterpret_cast<const float4*>(src + 4);
                const float4 a2 = *reinterpret_cast<const float4*>(src2), b2 = *reinterpret_cast<const float4*>(src2 + 4);
                a.x += a2.x; a.y += a2.y; a.z += a2.z; a.w += a2.w; b.x += b2.x; b.y += b2.y; b.z += b2.z; b.w += b2.w;
                const uint4 kv4 = *reinterpret_cast<const uint4*>(&sm.uT[ch][UT_PAD + s]);
                const uint4 x4 = *reinterpret_cast<const uint4*>(&sm.xT[ch][s]);
                const uint32_t y2[4] = {hadd2(pack_bf16(a.x, a.y), hmul2(kv4.x, d2)), hadd2(pack_bf16(a.z, a.w), hmul2(kv4.y, d2)),
                                        hadd2(pack_bf16(b.x, b.y), hmul2(kv4.z, d2)), hadd2(pack_bf16(b.z, b.w), hmul2(kv4.w, d2))};
                const uint32_t xw[4] = {x4.x, x4.y, x4.z, x4.w};
                const uint4 m4 = *reinterpret_cast<const uint4*>(&sm.st[S_ + s / 2]);
                const float4 ra = *reinterpret_cast<const float4*>(&sm.st[s]), rb4 = *reinterpret_cast<const float4*>(&sm.st[s + 4]);
                const uint32_t mw[4] = {m4.x, m4.y, m4.z, m4.w};
                const float rw[8] = {ra.x, ra.y, ra.z, ra.w, rb4.x, rb4.y, rb4.z, rb4.w};
                uint32_t o[4];
#pragma unroll
                for (int i = 0; i < 4; i++) {
                    const uint32_t d = hsub2(xw[i], mw[i]);
                    const uint32_t qn = pack_bf16(bf_lo(d) * rw[2 * i], bf_hi(d) * rw[2 * i + 1]);
                    o[i] = hadd2(xw[i], hmul2(qn, y2[i]));
                }
                *reinterpret_cast<uint4*>(dst + s) = make_uint4(o[0], o[1], o[2], o[3]);
            }
        }
    } else {
        cluster_wait();
        named_bar(6, 352);
        const uint32_t hbar = bar + 16;
        if (warp < 10) {
            {
                const int rr = 8 * (warp - 8);
                uint32_t xq[4][2][8];
#pragma unroll
                for (int r = 0; r < 8; r++) {
                    const uint4 qa = ldg128(q + (size_t)(16 * bid + rr + r) * D_ + 8 * lane);
                    const uint4 qb = ldg128(q + (size_t)(16 * bid + rr + r) * D_ + 8 * (lane + 32));
                    uint32_t* x = xq[r >> 1][r & 1];
                    x[0] = qa.x; x[1] = qa.y; x[2] = qa.z; x[3] = qa.w; x[4] = qb.x; x[5] = qb.y; x[6] = qb.z; x[7] = qb.w;
                }
#pragma unroll
                for (int r2 = 0; r2 < 4; r2++) {
                    float2 sa[2];
                    ln_stats2(xq[r2], sa);
                    if (lane == 0) {
                        *reinterpret_cast<float2*>(&g_st1[16 * bid + rr + 2 * r2]) = make_float2(sa[0].y, sa[1].y);
                        reinterpret_cast<uint32_t*>(&g_st1[S_])[(16 * bid + rr) / 2 + r2] = pack_bf16(sa[0].x, sa[1].x);
                    }
                }
            }
            if (lane == 0) { __threadfence(); atomicAdd(&g_cnt, 1u); }
            if (warp == 9) return;
            if (lane == 0) {
                unsigned int c; int spins = 0;
                while (true) {
                    asm volatile("ld.acquire.gpu.global.u32 %0, [%1];" : "=r"(c) : "l"(&g_cnt) : "memory");
                    if (c >= 2 * gridDim.x || ++spins > (1 << 22)) break;
                    __nanosleep(200);
                }
                asm volatile("fence.proxy.async;" ::: "memory");
                mbar_expect_tx(hbar + 8, 12288);
                asm volatile("cp.async.bulk.shared::cluster.global.mbarrier::complete_tx::bytes [%0], [%1], %2, [%3];"
                    :: "r"(smem_u32(&sm.st[0])), "l"(&g_st1[0]), "r"(12288), "r"(hbar + 8) : "memory");
            }
            mbar_wait(hbar + 8, 0);
            named_bar(7, 288);
        } else {
            if (lane == 0) asm volatile("cp.async.bulk.prefetch.L2.global [%0], %1;" :: "l"(wd + (size_t)bid * 7168), "r"(14336) : "memory");
            if (bid < 112) {
                if (lane == 0) {
                    mbar_expect_tx(hbar, 32768);
                    const CUtensorMap* mw = (bid < 56) ? &mapWg : &mapWu;
                    const int col = 32 * ((bid < 56) ? bid : bid - 56);
                    tma_load_2d(smem_u32(&sm.wS[0][0]), mw, hbar, col, 0);
                    tma_load_2d(smem_u32(&sm.wS[256][0]), mw, hbar, col, 256);
                }
                mbar_wait(hbar, 0);
                const int cq = lane & 3, rgp = lane >> 2;
                float cs[8];
#pragma unroll
                for (int i = 0; i < 8; i++) cs[i] = 0.f;
#pragma unroll 4
                for (int r = 0; r < 64; r++) {
                    const uint4 w = sm.wS[r * 8 + rgp][cq];
                    cs[0] += bf_lo(w.x); cs[1] += bf_hi(w.x); cs[2] += bf_lo(w.y); cs[3] += bf_hi(w.y);
                    cs[4] += bf_lo(w.z); cs[5] += bf_hi(w.z); cs[6] += bf_lo(w.w); cs[7] += bf_hi(w.w);
                }
#pragma unroll
                for (int i = 0; i < 8; i++) {
                    cs[i] += __shfl_xor_sync(0xffffffffu, cs[i], 4);
                    cs[i] += __shfl_xor_sync(0xffffffffu, cs[i], 8);
                    cs[i] += __shfl_xor_sync(0xffffffffu, cs[i], 16);
                }
                if (lane < 4) {
                    *reinterpret_cast<float4*>(&g_colsum[32 * bid + lane * 8]) = make_float4(cs[0], cs[1], cs[2], cs[3]);
                    *reinterpret_cast<float4*>(&g_colsum[32 * bid + lane * 8 + 4]) = make_float4(cs[4], cs[5], cs[6], cs[7]);
                }
            }
        }
    }
}

constexpr int G1_THREADS = 384;
constexpr int G1_STAGES = 3;
constexpr int G1_A_BYTES = 8 * 16384;
constexpr int G1_B_STAGE = 32768;
constexpr int G1_OFF_B = G1_A_BYTES;
constexpr int G1_OFF_STATS = G1_OFF_B + G1_STAGES * G1_B_STAGE;
constexpr int G1_OFF_CS = G1_OFF_STATS + 1024;
constexpr int G1_OFF_BAR = G1_OFF_CS + 1792;
constexpr int G1_SMEM = G1_OFF_BAR + 128;

__device__ __forceinline__ float tanh_fast(float x) { float t; asm("tanh.approx.f32 %0, %1;" : "=f"(t) : "f"(x)); return t; }

template <int NT>
__device__ __forceinline__ void g1_math(const float (&acc)[NT * 8], const float* cs_g, const float* cs_u, float2 st0, float2 st1, uint32_t (&P)[NT * 2], int t) {
    const float r0 = st0.y, r1 = st1.y, m0 = -st0.x * st0.y, m1 = -st1.x * st1.y;
#pragma unroll
    for (int j = 0; j < NT; j++) {
        const float2 cg = *reinterpret_cast<const float2*>(cs_g + 8 * j + 2 * t);
        const float2 cu = *reinterpret_cast<const float2*>(cs_u + 8 * j + 2 * t);
        float r[4];
#pragma unroll
        for (int e = 0; e < 4; e++) {
            const float rr = (e < 2) ? r0 : r1, mm = (e < 2) ? m0 : m1;
            const float gh = fmaf(acc[4 * j + e], 0.5f * rr, (0.5f * mm) * ((e & 1) ? cg.y : cg.x));
            const float uv = fmaf(acc[4 * (NT + j) + e], rr, mm * ((e & 1) ? cu.y : cu.x));
            r[e] = fmaf(tanh_fast(gh), 0.5f, 0.5f) * uv;
        }
        P[2 * j] = pack_bf16(r[0], r[1]);
        P[2 * j + 1] = pack_bf16(r[2], r[3]);
    }
}
template <int NT>
__device__ __forceinline__ void g1_store(uint32_t (&P)[NT * 2], bf16* out0, int t) {
#pragma unroll
    for (int j0 = 0; j0 < NT; j0 += 4) {
        quad_transpose(P[2 * j0], P[2 * j0 + 2], P[2 * j0 + 4], P[2 * j0 + 6], t);
        quad_transpose(P[2 * j0 + 1], P[2 * j0 + 3], P[2 * j0 + 5], P[2 * j0 + 7], t);
        *reinterpret_cast<uint4*>(out0 + 8 * (j0 + t)) = make_uint4(P[2 * j0], P[2 * j0 + 2], P[2 * j0 + 4], P[2 * j0 + 6]);
        *reinterpret_cast<uint4*>(out0 + 8 * F_ + 8 * (j0 + t)) = make_uint4(P[2 * j0 + 1], P[2 * j0 + 3], P[2 * j0 + 5], P[2 * j0 + 7]);
    }
}

__global__ void __cluster_dims__(2, 1, 1) __launch_bounds__(G1_THREADS, 1)
gemm1_kernel(const __grid_constant__ CUtensorMap mapA, const __grid_constant__ CUtensorMap mapG4, const __grid_constant__ CUtensorMap mapU4,
             const __grid_constant__ CUtensorMap mapG3, const __grid_constant__ CUtensorMap mapU3) {
    extern __shared__ __align__(1024) uint8_t smem_raw[];
    const uint32_t sb = smem_u32(smem_raw);
    const int tid = threadIdx.x, lane = tid & 31, warp = tid >> 5, wgi = tid >> 7;
    const int rank = blockIdx.x & 1;
    const int cb = blockIdx.x & 7, rb = blockIdx.x >> 3;
    pdl_launch();
    if (tid == 32) { prefetch_map(&mapA); prefetch_map(&mapG3); prefetch_map(&mapU3); }
    const uint32_t barA = sb + G1_OFF_BAR;
    const uint32_t barF = barA + 64;
    const uint32_t barE = barF + 8 * G1_STAGES;
    const uint32_t barS = barE + 8 * G1_STAGES;
    if (tid == 0) {
        for (int i = 0; i < 8; i++) mbar_init(barA + 8 * i, 1);
        for (int i = 0; i < G1_STAGES; i++) { mbar_init(barF + 8 * i, 1); mbar_init(barE + 8 * i, 2); }
        mbar_init(barS, 1);
        for (int i = 0; i < 8; i++) mbar_expect_tx(barA + 8 * i, 16384);
        asm volatile("fence.mbarrier_init.release.cluster;" ::: "memory");
    }
    __syncthreads();
    cluster_arrive_relaxed();

    if (wgi == 0) {
        reg_dealloc<40>();
        if (warp == 0) {
            cluster_wait();
            if (lane == 0) {
                int st = 0, ph = 1;
                for (int it = 0; it < 16; it++) {
                    const int kc = it & 7;
                    if (it == 2) {
                        pdl_wait();
                        for (int i = 0; i < 4; i++) {
                            const int c = 2 * i + rank;
                            tma_load_3d_mc(sb + c * 16384, &mapA, barA + 8 * c, 0, c * 64, rb * 2, (uint16_t)3);
                        }
                    }
                    mbar_wait(barE + 8 * st, ph);
                    const uint32_t dst = sb + G1_OFF_B + st * G1_B_STAGE;
                    if (it < 8) {
                        mbar_expect_tx(barF + 8 * st, 32768);
                        tma_load_2d(dst, &mapG4, barF + 8 * st, cb * 224, kc * 64);
                        tma_load_2d(dst + 8192, &mapG4, barF + 8 * st, cb * 224 + 64, kc * 64);
                        tma_load_2d(dst + 16384, &mapU4, barF + 8 * st, cb * 224, kc * 64);
                        tma_load_2d(dst + 24576, &mapU4, barF + 8 * st, cb * 224 + 64, kc * 64);
                    } else {
                        mbar_expect_tx(barF + 8 * st, 24576);
                        tma_load_3d(dst, &mapG3, barF + 8 * st, 0, kc * 64, cb * 7 + 4);
                        tma_load_3d(dst + 12288, &mapU3, barF + 8 * st, 0, kc * 64, cb * 7 + 4);
                    }
                    if (++st == G1_STAGES) { st = 0; ph ^= 1; }
                }
            }
            __syncwarp();
        } else if (warp == 1) {
            cluster_wait();
            pdl_wait();
            float* cs = reinterpret_cast<float*>(smem_raw + G1_OFF_CS);
            for (int i = lane; i < 448; i += 32) cs[i] = __ldcg((i < 224) ? &g_colsum[cb * 224 + i] : &g_colsum[F_ + cb * 224 + (i - 224)]);
            __syncwarp();
            if (lane == 0) mbar_arrive(barS);
        } else {
            cluster_wait();
        }
    } else {
        reg_alloc<232>();
        cluster_wait();
        const int cw = wgi - 1;
        const int g = lane >> 2, t = lane & 3, wl = warp & 3, tl = tid & 127;
        bf16* outp = g_hh + (size_t)(rb * 128 + cw * 64 + wl * 16 + g) * F_ + cb * 224;
        const float* cs = reinterpret_cast<const float*>(smem_raw + G1_OFF_CS);
        int st = 0, ph = 0;
        float2 st0, st1;
        uint32_t P1[32];
        {
            float acc[128];
            const int kq = lane >> 3, mp = lane & 7;
            const uint8_t* sbase = smem_raw + cw * 8192 + kq * 128 + (mp & 3) * 4;
            const int mc = 2 * wl + (mp >> 2);
            float p0 = 0.f, p1 = 0.f, s0 = 0.f, s1 = 0.f, q0 = 0.f, q1 = 0.f;
#pragma unroll 1
            for (int kc = 0; kc < 8; kc++) {
                mbar_wait(barA + 8 * kc, 0);
                mbar_wait(barF + 8 * st, ph);
                wgmma_fence();
                const uint32_t aaddr = sb + kc * 16384 + cw * 8192;
                const uint32_t baddr = sb + G1_OFF_B + st * G1_B_STAGE;
#pragma unroll
                for (int kk = 0; kk < 4; kk++)
                    wgmma_m64n256k16_ss(acc, make_desc(aaddr + kk * 2048, 8192, 1024, 1), make_desc(baddr + kk * 2048, 8192, 1024, 1), (kc | kk) != 0);
                wgmma_commit();
                if (kc == 0) {
                    const uint32_t w = *reinterpret_cast<const uint32_t*>(smem_raw + cw * 8192 + (mc << 4) + (mp & 3) * 4);
                    p0 = bf_lo(w); p1 = bf_hi(w);
                }
#pragma unroll
                for (int i = 0; i < 16; i++) {
                    const int kr = 4 * i;
                    const uint32_t w = *reinterpret_cast<const uint32_t*>(sbase + kc * 16384 + kr * 128 + ((mc ^ ((kr + kq) & 7)) << 4));
                    const float d0 = bf_lo(w) - p0, d1 = bf_hi(w) - p1;
                    s0 += d0; s1 += d1; q0 = fmaf(d0, d0, q0); q1 = fmaf(d1, d1, q1);
                }
                wgmma_wait<0>();
                if (tl == 0) mbar_arrive(barE + 8 * st);
                if (++st == G1_STAGES) { st = 0; ph ^= 1; }
            }
            {
#pragma unroll
                for (int o = 8; o <= 16; o <<= 1) {
                    s0 += __shfl_xor_sync(0xffffffffu, s0, o); s1 += __shfl_xor_sync(0xffffffffu, s1, o);
                    q0 += __shfl_xor_sync(0xffffffffu, q0, o); q1 += __shfl_xor_sync(0xffffffffu, q1, o);
                }
                const float md0 = s0 * (1.0f / D_), md1 = s1 * (1.0f / D_);
                const float v0 = bf16r(fmaxf(fmaf(-md0, md0, q0 * (1.0f / D_)), 0.f)), v1 = bf16r(fmaxf(fmaf(-md1, md1, q1 * (1.0f / D_)), 0.f));
                const float ma = bf16r(p0 + md0), mb = bf16r(p1 + md1);
                const float ra = 1.0f / bf16r(sqrtf(bf16r(v0 + 1e-5f))), rbb = 1.0f / bf16r(sqrtf(bf16r(v1 + 1e-5f)));
                const float mA = __shfl_sync(0xffffffffu, ma, g >> 1), mB = __shfl_sync(0xffffffffu, mb, g >> 1);
                const float rA = __shfl_sync(0xffffffffu, ra, g >> 1), rB = __shfl_sync(0xffffffffu, rbb, g >> 1);
                const float mC = __shfl_sync(0xffffffffu, ma, 4 + (g >> 1)), mD = __shfl_sync(0xffffffffu, mb, 4 + (g >> 1));
                const float rC = __shfl_sync(0xffffffffu, ra, 4 + (g >> 1)), rD = __shfl_sync(0xffffffffu, rbb, 4 + (g >> 1));
                st0 = (g & 1) ? make_float2(mB, rB) : make_float2(mA, rA);
                st1 = (g & 1) ? make_float2(mD, rD) : make_float2(mC, rC);
            }
            mbar_wait(barS, 0);
            g1_math<16>(acc, cs, cs + 224, st0, st1, P1, t);
        }
        {
            float acc[96];
#pragma unroll 1
            for (int kc = 0; kc < 8; kc++) {
                mbar_wait(barF + 8 * st, ph);
                wgmma_fence();
                const uint32_t aaddr = sb + kc * 16384 + cw * 8192;
                const uint32_t baddr = sb + G1_OFF_B + st * G1_B_STAGE;
#pragma unroll
                for (int kk = 0; kk < 4; kk++)
                    wgmma_m64n192k16_ss(acc, make_desc(aaddr + kk * 2048, 8192, 1024, 1), make_desc(baddr + kk * 1024, 4096, 512, 2), (kc | kk) != 0);
                wgmma_commit();
                if (kc == 0) g1_store<16>(P1, outp, t);
                wgmma_wait<0>();
                if (tl == 0) mbar_arrive(barE + 8 * st);
                if (++st == G1_STAGES) { st = 0; ph ^= 1; }
            }
            uint32_t P2[24];
            g1_math<12>(acc, cs + 128, cs + 224 + 128, st0, st1, P2, t);
            g1_store<12>(P2, outp + 128, t);
        }
    }
}

constexpr int G2_THREADS = 384;
constexpr int G2_STAGES = 6;
constexpr int G2_STAGE = 32768;
constexpr int G2_OFF_X = G2_STAGES * G2_STAGE;
constexpr int G2_OFF_BAR = G2_OFF_X + 32768;
constexpr int G2_SMEM = G2_OFF_BAR + 128;
constexpr int G2_KSTEPS = 14;
constexpr int G2_PRE = 6;

__device__ __forceinline__ void ldsm_x4_t(uint32_t& r0, uint32_t& r1, uint32_t& r2, uint32_t& r3, uint32_t addr) {
    asm volatile("ldmatrix.sync.aligned.m8n8.x4.trans.shared.b16 {%0,%1,%2,%3}, [%4];" : "=r"(r0), "=r"(r1), "=r"(r2), "=r"(r3) : "r"(addr) : "memory");
}

__global__ void __cluster_dims__(2, 1, 1) __launch_bounds__(G2_THREADS, 1)
gemm2_kernel(const __grid_constant__ CUtensorMap mapHH, const __grid_constant__ CUtensorMap mapWd, const __grid_constant__ CUtensorMap mapH,
             bf16* __restrict__ out) {
    extern __shared__ __align__(1024) uint8_t smem_raw[];
    const uint32_t sb = smem_u32(smem_raw);
    const int tid = threadIdx.x, lane = tid & 31, warp = tid >> 5, wgi = tid >> 7;
    const int ks = blockIdx.x & 1, nb = (blockIdx.x >> 1) & 3, rb = blockIdx.x >> 3;
    if (tid == 32) { prefetch_map(&mapHH); prefetch_map(&mapH); }
    const uint32_t barF = sb + G2_OFF_BAR;
    const uint32_t barE = barF + 8 * G2_STAGES;
    const uint32_t barX = barE + 8 * G2_STAGES;
    if (tid == 0) {
        for (int i = 0; i < G2_STAGES; i++) { mbar_init(barF + 8 * i, 1); mbar_init(barE + 8 * i, 2); }
        mbar_init(barX, 1);
        asm volatile("fence.mbarrier_init.release.cluster;" ::: "memory");
        mbar_expect_tx(barX, 32768);
        for (int it = 0; it < G2_PRE; it++) {
            mbar_expect_tx(barF + 8 * it, 32768);
            tma_load_3d(sb + it * G2_STAGE + 16384, &mapWd, barF + 8 * it, 0, ks * 896 + it * 64, nb * 2);
        }
    }
    __syncthreads();
    cluster_arrive_relaxed();

    if (wgi == 0) {
        if (tid == 0) {
            pdl_wait();
            for (int it = 0; it < G2_STAGES; it++) {
                if (it >= G2_PRE) mbar_expect_tx(barF + 8 * it, 32768);
                tma_load_2d(sb + it * G2_STAGE, &mapHH, barF + 8 * it, ks * 896 + it * 64, rb * 128);
                if (it >= G2_PRE) tma_load_3d(sb + it * G2_STAGE + 16384, &mapWd, barF + 8 * it, 0, ks * 896 + it * 64, nb * 2);
            }
            if (blockIdx.x == 0) g_cnt = 0u;
            int st = 0, ph = 0;
            for (int it = G2_STAGES; it < G2_KSTEPS; it++) {
                mbar_wait(barE + 8 * st, ph);
                const uint32_t dst = sb + st * G2_STAGE;
                const int k0 = ks * 896 + it * 64;
                mbar_expect_tx(barF + 8 * st, 32768);
                tma_load_2d(dst, &mapHH, barF + 8 * st, k0, rb * 128);
                tma_load_3d(dst + 16384, &mapWd, barF + 8 * st, 0, k0, nb * 2);
                if (++st == G2_STAGES) { st = 0; ph ^= 1; }
            }
            mbar_wait(barE + 8 * st, ph);
            mbar_expect_tx(barF + 8 * st, 16384);
            tma_load_2d(sb + st * G2_STAGE, &mapH, barF + 8 * st, rb * 128 + ks * 64, nb * 128);
        }
        __syncwarp();
        cluster_wait();
    } else {
        const int cw = wgi - 1;
        const int g = lane >> 2, t = lane & 3, wl = warp & 3;
        const int tl = tid & 127;
        int st = 0, ph = 0;
        float acc[64];
#pragma unroll 1
        for (int it = 0; it < G2_KSTEPS; it++) {
            mbar_wait(barF + 8 * st, ph);
            wgmma_fence();
            const uint32_t aaddr = sb + st * G2_STAGE + cw * 8192;
            const uint32_t baddr = sb + st * G2_STAGE + 16384;
#pragma unroll
            for (int kk = 0; kk < 4; kk++)
                wgmma_m64n128k16_ss(acc, make_desc(aaddr + kk * 32, 16, 1024, 1), make_desc(baddr + kk * 2048, 8192, 1024, 1), (it | kk) != 0);
            wgmma_commit();
            wgmma_wait<0>();
            if (tl == 0) mbar_arrive(barE + 8 * st);
            if (++st == G2_STAGES) { st = 0; ph ^= 1; }
        }
        cluster_wait();
        if (cw != ks) {
            const uint32_t dst = mapa(sb + G2_OFF_X + tl * 16, (uint32_t)(ks ^ 1));
            const uint32_t rbar = mapa(barX, (uint32_t)(ks ^ 1));
#pragma unroll
            for (int i = 0; i < 16; i++) st_async_v4f(dst + i * 2048, acc[4 * i], acc[4 * i + 1], acc[4 * i + 2], acc[4 * i + 3], rbar);
        } else {
            const float4* xb = reinterpret_cast<const float4*>(smem_raw + G2_OFF_X) + tl;
            const int row0 = rb * 128 + cw * 64 + wl * 16 + g;
            bf16* o0 = out + (size_t)row0 * D_ + nb * 128;
            uint32_t ha[16], hb[16];
            mbar_wait(barF + 8 * st, ph);
            {
                const int chl = 8 * (lane >> 4) + (lane & 7), sb8 = 2 * wl + ((lane >> 3) & 1);
                const uint32_t hbase = sb + st * G2_STAGE + chl * 128 + ((sb8 ^ (lane & 7)) << 4);
#pragma unroll
                for (int j = 0; j < 16; j += 2) ldsm_x4_t(ha[j], hb[j], ha[j + 1], hb[j + 1], hbase + j * 1024);
            }
            mbar_wait_cluster(barX, 0);
#pragma unroll
            for (int j0 = 0; j0 < 16; j0 += 4) {
                uint32_t P0[4], P1[4];
#pragma unroll
                for (int jj = 0; jj < 4; jj++) {
                    const int j = j0 + jj;
                    const float4 x = xb[j * 128];
                    P0[jj] = hadd2(ha[j], pack_bf16(acc[4 * j] + x.x, acc[4 * j + 1] + x.y));
                    P1[jj] = hadd2(hb[j], pack_bf16(acc[4 * j + 2] + x.z, acc[4 * j + 3] + x.w));
                }
                quad_transpose(P0[0], P0[1], P0[2], P0[3], t);
                quad_transpose(P1[0], P1[1], P1[2], P1[3], t);
                *reinterpret_cast<uint4*>(o0 + 8 * (j0 + t)) = make_uint4(P0[0], P0[1], P0[2], P0[3]);
                *reinterpret_cast<uint4*>(o0 + 8 * D_ + 8 * (j0 + t)) = make_uint4(P1[0], P1[1], P1[2], P1[3]);
            }
        }
    }
}

typedef CUresult (*EncodeFn)(CUtensorMap*, CUtensorMapDataType, cuuint32_t, void*, const cuuint64_t*, const cuuint64_t*,
                             const cuuint32_t*, const cuuint32_t*, CUtensorMapInterleave, CUtensorMapSwizzle,
                             CUtensorMapL2promotion, CUtensorMapFloatOOBfill);

static void enc2d(EncodeFn enc, CUtensorMap* m, const void* p, int rows, int cols, int brows, int bcols, int pitch = 0) {
    cuuint64_t dims[2] = {(cuuint64_t)cols, (cuuint64_t)rows};
    cuuint64_t strides[1] = {(cuuint64_t)(pitch ? pitch : cols) * 2};
    cuuint32_t box[2] = {(cuuint32_t)bcols, (cuuint32_t)brows};
    cuuint32_t es[2] = {1, 1};
    enc(m, CU_TENSOR_MAP_DATA_TYPE_BFLOAT16, 2, const_cast<void*>(p), dims, strides, box, es, CU_TENSOR_MAP_INTERLEAVE_NONE,
        bcols == 32 ? CU_TENSOR_MAP_SWIZZLE_64B : CU_TENSOR_MAP_SWIZZLE_128B, CU_TENSOR_MAP_L2_PROMOTION_L2_128B, CU_TENSOR_MAP_FLOAT_OOB_FILL_NONE);
}
static void enc2d_plain(EncodeFn enc, CUtensorMap* m, const void* p, int rows, int cols, int brows, int bcols) {
    cuuint64_t dims[2] = {(cuuint64_t)cols, (cuuint64_t)rows};
    cuuint64_t strides[1] = {(cuuint64_t)cols * 2};
    cuuint32_t box[2] = {(cuuint32_t)bcols, (cuuint32_t)brows};
    cuuint32_t es[2] = {1, 1};
    enc(m, CU_TENSOR_MAP_DATA_TYPE_BFLOAT16, 2, const_cast<void*>(p), dims, strides, box, es, CU_TENSOR_MAP_INTERLEAVE_NONE,
        CU_TENSOR_MAP_SWIZZLE_NONE, CU_TENSOR_MAP_L2_PROMOTION_L2_128B, CU_TENSOR_MAP_FLOAT_OOB_FILL_NONE);
}
static void enc3d(EncodeFn enc, CUtensorMap* m, const void* p, int rows, int cols, int atom, int brows, int natoms, int pitch = 0) {
    cuuint64_t dims[3] = {(cuuint64_t)atom, (cuuint64_t)rows, (cuuint64_t)(cols / atom)};
    cuuint64_t strides[2] = {(cuuint64_t)(pitch ? pitch : cols) * 2, (cuuint64_t)atom * 2};
    cuuint32_t box[3] = {(cuuint32_t)atom, (cuuint32_t)brows, (cuuint32_t)natoms};
    cuuint32_t es[3] = {1, 1, 1};
    enc(m, CU_TENSOR_MAP_DATA_TYPE_BFLOAT16, 3, const_cast<void*>(p), dims, strides, box, es, CU_TENSOR_MAP_INTERLEAVE_NONE,
        atom == 32 ? CU_TENSOR_MAP_SWIZZLE_64B : CU_TENSOR_MAP_SWIZZLE_128B, CU_TENSOR_MAP_L2_PROMOTION_L2_128B, CU_TENSOR_MAP_FLOAT_OOB_FILL_NONE);
}

extern "C" void kernel_launch(void* const* d_in, const int* in_sizes, int n_in, void* d_out, int out_size) {
    const bf16* q = (const bf16*)d_in[0];
    const bf16* k = (const bf16*)d_in[1];
    const bf16* v = (const bf16*)d_in[2];
    const bf16* shift_k = (const bf16*)d_in[3];
    const bf16* ssm_k = (const bf16*)d_in[4];
    const bf16* ssm_D = (const bf16*)d_in[5];
    const bf16* wg = (const bf16*)d_in[7];
    const bf16* wu = (const bf16*)d_in[8];
    const bf16* wd = (const bf16*)d_in[9];
    bf16* out = (bf16*)d_out;

    static EncodeFn enc = nullptr;
    static void *p_hT = nullptr, *p_hh = nullptr;
    if (!enc) {
        void* fn = nullptr; cudaDriverEntryPointQueryResult qr;
        cudaGetDriverEntryPoint("cuTensorMapEncodeTiled", &fn, cudaEnableDefault, &qr);
        enc = (EncodeFn)fn;
        cudaGetSymbolAddress(&p_hT, g_hT);
        cudaGetSymbolAddress(&p_hh, g_hh);
        cudaFuncSetAttribute(conv_kernel, cudaFuncAttributeMaxDynamicSharedMemorySize, (int)sizeof(K1Smem));
        cudaFuncSetAttribute(gemm1_kernel, cudaFuncAttributeMaxDynamicSharedMemorySize, G1_SMEM);
        cudaFuncSetAttribute(gemm2_kernel, cudaFuncAttributeMaxDynamicSharedMemorySize, G2_SMEM);
    }
    CUtensorMap mA, mG64, mU64, mG32, mU32, mHH, mWd, mH, mWgp, mWup;
    enc2d_plain(enc, &mWgp, wg, D_, F_, 256, 32);
    enc2d_plain(enc, &mWup, wu, D_, F_, 256, 32);
    enc3d(enc, &mA, p_hT, D_, S_, 64, 64, 2, HT_PITCH);
    enc2d(enc, &mH, p_hT, D_, S_, 128, 64, HT_PITCH);
    enc2d(enc, &mG64, wg, D_, F_, 64, 64);
    enc2d(enc, &mU64, wu, D_, F_, 64, 64);
    enc3d(enc, &mG32, wg, D_, F_, 32, 64, 3);
    enc3d(enc, &mU32, wu, D_, F_, 32, 64, 3);
    enc2d(enc, &mHH, p_hh, S_, F_, 128, 64);
    enc3d(enc, &mWd, wd, F_, D_, 64, 64, 2);

    cudaStream_t st = cudaStreamPerThread;
    cudaLaunchAttribute at[1];
    at[0].id = cudaLaunchAttributeProgrammaticStreamSerialization;
    at[0].val.programmaticStreamSerializationAllowed = 1;
    cudaLaunchConfig_t cfg = {};
    cfg.stream = st; cfg.attrs = at; cfg.numAttrs = 1;
    conv_kernel<<<128, K1_THREADS, sizeof(K1Smem), st>>>(q, k, v, shift_k, ssm_k, ssm_D, mWgp, mWup, wd);
    cfg.gridDim = dim3(128); cfg.blockDim = dim3(G1_THREADS); cfg.dynamicSmemBytes = G1_SMEM;
    cudaLaunchKernelEx(&cfg, gemm1_kernel, mA, mG64, mU64, mG32, mU32);
    cfg.gridDim = dim3(128); cfg.blockDim = dim3(G2_THREADS); cfg.dynamicSmemBytes = G2_SMEM;
    cudaLaunchKernelEx(&cfg, gemm2_kernel, mHH, mWd, mH, out);
}
```

```cpp
#include <cuda_runtime.h>
#include <cuda_bf16.h>
#include <cuda.h>
#include <stdint.h>

typedef __nv_bfloat16 bf16;
constexpr int S_ = 2048, D_ = 512, F_ = 1792;

constexpr int HT_PITCH = S_ + 64;
__device__ __align__(128) bf16 g_hT[D_ * HT_PITCH];
__device__ __align__(128) bf16 g_hh[S_ * F_];
__device__ __align__(128) float g_st1[S_ + S_ / 2];
__device__ __align__(16) float g_colsum[2 * F_];
__device__ unsigned int g_cnt;

__device__ __forceinline__ uint32_t smem_u32(const void* p) { return (uint32_t)__cvta_generic_to_shared(p); }
__device__ __forceinline__ float bf16r(float x) { return __bfloat162float(__float2bfloat16_rn(x)); }
__device__ __forceinline__ float bf_lo(uint32_t w) { return __uint_as_float(w << 16); }
__device__ __forceinline__ float bf_hi(uint32_t w) { return __uint_as_float(w & 0xffff0000u); }
__device__ __forceinline__ uint32_t pack_bf16(float lo, float hi) {
    __nv_bfloat162 v = __floats2bfloat162_rn(lo, hi);
    return *reinterpret_cast<uint32_t*>(&v);
}
__device__ __forceinline__ uint32_t hmul2(uint32_t a, uint32_t b) {
    __nv_bfloat162 r = __hmul2_rn(*reinterpret_cast<__nv_bfloat162*>(&a), *reinterpret_cast<__nv_bfloat162*>(&b));
    return *reinterpret_cast<uint32_t*>(&r);
}
__device__ __forceinline__ uint32_t hadd2(uint32_t a, uint32_t b) {
    __nv_bfloat162 r = __hadd2_rn(*reinterpret_cast<__nv_bfloat162*>(&a), *reinterpret_cast<__nv_bfloat162*>(&b));
    return *reinterpret_cast<uint32_t*>(&r);
}
__device__ __forceinline__ uint4 ldg128(const void* p) {
    uint4 r; asm volatile("ld.global.nc.v4.u32 {%0,%1,%2,%3}, [%4];" : "=r"(r.x), "=r"(r.y), "=r"(r.z), "=r"(r.w) : "l"(p)); return r;
}
__device__ __forceinline__ uint4 ldg128_l2(const void* p) {
    uint4 r; asm volatile("ld.global.nc.L2::128B.v4.u32 {%0,%1,%2,%3}, [%4];" : "=r"(r.x), "=r"(r.y), "=r"(r.z), "=r"(r.w) : "l"(p)); return r;
}
__device__ __forceinline__ uint4 ldcg128(const void* p) {
    uint4 r; asm volatile("ld.global.cg.v4.u32 {%0,%1,%2,%3}, [%4];" : "=r"(r.x), "=r"(r.y), "=r"(r.z), "=r"(r.w) : "l"(p)); return r;
}
__device__ __forceinline__ uint32_t ldg16(const void* p) {
    unsigned short r; asm volatile("ld.global.nc.u16 %0, [%1];" : "=h"(r) : "l"(p)); return (uint32_t)r;
}
__device__ __forceinline__ void mbar_init(uint32_t bar, int cnt) { asm volatile("mbarrier.init.shared::cta.b64 [%0], %1;" :: "r"(bar), "r"(cnt)); }
__device__ __forceinline__ void mbar_expect_tx(uint32_t bar, uint32_t bytes) { asm volatile("mbarrier.arrive.expect_tx.shared::cta.b64 _, [%0], %1;" :: "r"(bar), "r"(bytes) : "memory"); }
__device__ __forceinline__ void mbar_arrive(uint32_t bar) { asm volatile("mbarrier.arrive.shared::cta.b64 _, [%0];" :: "r"(bar) : "memory"); }
__device__ __forceinline__ void mbar_arrive_cluster(uint32_t bar, uint32_t cta) {
    asm volatile("{\n.reg .b32 ra;\nmapa.shared::cluster.u32 ra, %0, %1;\nmbarrier.arrive.shared::cluster.b64 _, [ra];\n}" :: "r"(bar), "r"(cta) : "memory");
}
__device__ __forceinline__ void mbar_wait(uint32_t bar, uint32_t parity) {
    asm volatile("{\n.reg .pred P1;\nLAB_WAIT:\nmbarrier.try_wait.parity.shared::cta.b64 P1, [%0], %1;\n@P1 bra DONE;\nbra LAB_WAIT;\nDONE:\n}" :: "r"(bar), "r"(parity) : "memory");
}
__device__ __forceinline__ void mbar_wait_cluster(uint32_t bar, uint32_t parity) {
    asm volatile("{\n.reg .pred P1;\nLAB_WAIT:\nmbarrier.try_wait.parity.acquire.cluster.shared::cta.b64 P1, [%0], %1;\n@P1 bra DONE;\nbra LAB_WAIT;\nDONE:\n}" :: "r"(bar), "r"(parity) : "memory");
}
__device__ __forceinline__ void tma_load_2d(uint32_t dst, const CUtensorMap* map, uint32_t bar, int c0, int c1) {
    asm volatile("cp.async.bulk.tensor.2d.shared::cluster.global.mbarrier::complete_tx::bytes [%0], [%1, {%3, %4}], [%2];"
        :: "r"(dst), "l"(map), "r"(bar), "r"(c0), "r"(c1) : "memory");
}
__device__ __forceinline__ void tma_load_2d_mc(uint32_t dst, const CUtensorMap* map, uint32_t bar, int c0, int c1, uint16_t mask) {
    asm volatile("cp.async.bulk.tensor.2d.shared::cluster.global.mbarrier::complete_tx::bytes.multicast::cluster [%0], [%1, {%3, %4}], [%2], %5;"
        :: "r"(dst), "l"(map), "r"(bar), "r"(c0), "r"(c1), "h"(mask) : "memory");
}
__device__ __forceinline__ void tma_load_3d_mc(uint32_t dst, const CUtensorMap* map, uint32_t bar, int c0, int c1, int c2, uint16_t mask) {
    asm volatile("cp.async.bulk.tensor.3d.shared::cluster.global.mbarrier::complete_tx::bytes.multicast::cluster [%0], [%1, {%3, %4, %5}], [%2], %6;"
        :: "r"(dst), "l"(map), "r"(bar), "r"(c0), "r"(c1), "r"(c2), "h"(mask) : "memory");
}
__device__ __forceinline__ void tma_load_3d(uint32_t dst, const CUtensorMap* map, uint32_t bar, int c0, int c1, int c2) {
    asm volatile("cp.async.bulk.tensor.3d.shared::cluster.global.mbarrier::complete_tx::bytes [%0], [%1, {%3, %4, %5}], [%2];"
        :: "r"(dst), "l"(map), "r"(bar), "r"(c0), "r"(c1), "r"(c2) : "memory");
}
__device__ __forceinline__ void cluster_arrive() { asm volatile("barrier.cluster.arrive.aligned;" ::: "memory"); }
__device__ __forceinline__ void cluster_arrive_relaxed() { asm volatile("barrier.cluster.arrive.relaxed.aligned;" ::: "memory"); }
__device__ __forceinline__ void cluster_wait() { asm volatile("barrier.cluster.wait.aligned;" ::: "memory"); }
__device__ __forceinline__ uint32_t mapa(uint32_t addr, uint32_t cta) {
    uint32_t r; asm volatile("mapa.shared::cluster.u32 %0, %1, %2;" : "=r"(r) : "r"(addr), "r"(cta)); return r;
}
__device__ __forceinline__ void st_async_v2(uint32_t addr, uint32_t a, uint32_t b, uint32_t rbar) {
    asm volatile("st.async.weak.shared::cluster.mbarrier::complete_tx::bytes.v2.b32 [%0], {%1, %2}, [%3];" :: "r"(addr), "r"(a), "r"(b), "r"(rbar) : "memory");
}
__device__ __forceinline__ void st_async_v4f(uint32_t addr, float a, float b, float c, float d, uint32_t rbar) {
    asm volatile("st.async.weak.shared::cluster.mbarrier::complete_tx::bytes.v4.f32 [%0], {%1, %2, %3, %4}, [%5];" :: "r"(addr), "f"(a), "f"(b), "f"(c), "f"(d), "r"(rbar) : "memory");
}
__device__ __forceinline__ void wgmma_fence() { asm volatile("wgmma.fence.sync.aligned;" ::: "memory"); }
__device__ __forceinline__ void wgmma_commit() { asm volatile("wgmma.commit_group.sync.aligned;" ::: "memory"); }
template <int N> __device__ __forceinline__ void wgmma_wait() { asm volatile("wgmma.wait_group.sync.aligned %0;" :: "n"(N) : "memory"); }
__device__ __forceinline__ uint64_t make_desc(uint32_t addr, uint32_t lbo_bytes, uint32_t sbo_bytes, uint32_t layout) {
    return (uint64_t)((addr & 0x3FFFF) >> 4) | ((uint64_t)(lbo_bytes >> 4) << 16) | ((uint64_t)(sbo_bytes >> 4) << 32) | ((uint64_t)layout << 62);
}
template <int R> __device__ __forceinline__ void reg_alloc() { asm volatile("setmaxnreg.inc.sync.aligned.u32 %0;" :: "n"(R)); }
template <int R> __device__ __forceinline__ void reg_dealloc() { asm volatile("setmaxnreg.dec.sync.aligned.u32 %0;" :: "n"(R)); }
__device__ __forceinline__ void pdl_launch() { asm volatile("griddepcontrol.launch_dependents;" ::: "memory"); }
__device__ __forceinline__ void pdl_wait() { asm volatile("griddepcontrol.wait;" ::: "memory"); }
__device__ __forceinline__ void prefetch_map(const CUtensorMap* m) { asm volatile("prefetch.tensormap [%0];" :: "l"(m) : "memory"); }
__device__ __forceinline__ void named_bar(int id, int n) { asm volatile("bar.sync %0, %1;" :: "r"(id), "r"(n) : "memory"); }

__device__ __forceinline__ void wgmma_m64n256k16_ss(float (&d)[128], uint64_t descA, uint64_t descB, int scaleD) {
    asm volatile("{\n.reg .pred p;\nsetp.ne.b32 p, %130, 0;\n"
        "wgmma.mma_async.sync.aligned.m64n256k16.f32.bf16.bf16 {%0, %1, %2, %3, %4, %5, %6, %7, %8, %9, %10, %11, %12, %13, %14, %15, %16, %17, %18, %19, %20, %21, %22, %23, %24, %25, %26, %27, %28, %29, %30, %31, %32, %33, %34, %35, %36, %37, %38, %39, %40, %41, %42, %43, %44, %45, %46, %47, %48, %49, %50, %51, %52, %53, %54, %55, %56, %57, %58, %59, %60, %61, %62, %63, %64, %65, %66, %67, %68, %69, %70, %71, %72, %73, %74, %75, %76, %77, %78, %79, %80, %81, %82, %83, %84, %85, %86, %87, %88, %89, %90, %91, %92, %93, %94, %95, %96, %97, %98, %99, %100, %101, %102, %103, %104, %105, %106, %107, %108, %109, %110, %111, %112, %113, %114, %115, %116, %117, %118, %119, %120, %121, %122, %123, %124, %125, %126, %127}, %128, %129, p, 1, 1, 1, 1;\n}\n"
        : "+f"(d[0]), "+f"(d[1]), "+f"(d[2]), "+f"(d[3]), "+f"(d[4]), "+f"(d[5]), "+f"(d[6]), "+f"(d[7]), "+f"(d[8]), "+f"(d[9]), "+f"(d[10]), "+f"(d[11]), "+f"(d[12]), "+f"(d[13]), "+f"(d[14]), "+f"(d[15]), "+f"(d[16]), "+f"(d[17]), "+f"(d[18]), "+f"(d[19]), "+f"(d[20]), "+f"(d[21]), "+f"(d[22]), "+f"(d[23]), "+f"(d[24]), "+f"(d[25]), "+f"(d[26]), "+f"(d[27]), "+f"(d[28]), "+f"(d[29]), "+f"(d[30]), "+f"(d[31]), "+f"(d[32]), "+f"(d[33]), "+f"(d[34]), "+f"(d[35]), "+f"(d[36]), "+f"(d[37]), "+f"(d[38]), "+f"(d[39]), "+f"(d[40]), "+f"(d[41]), "+f"(d[42]), "+f"(d[43]), "+f"(d[44]), "+f"(d[45]), "+f"(d[46]), "+f"(d[47]), "+f"(d[48]), "+f"(d[49]), "+f"(d[50]), "+f"(d[51]), "+f"(d[52]), "+f"(d[53]), "+f"(d[54]), "+f"(d[55]), "+f"(d[56]), "+f"(d[57]), "+f"(d[58]), "+f"(d[59]), "+f"(d[60]), "+f"(d[61]), "+f"(d[62]), "+f"(d[63]), "+f"(d[64]), "+f"(d[65]), "+f"(d[66]), "+f"(d[67]), "+f"(d[68]), "+f"(d[69]), "+f"(d[70]), "+f"(d[71]), "+f"(d[72]), "+f"(d[73]), "+f"(d[74]), "+f"(d[75]), "+f"(d[76]), "+f"(d[77]), "+f"(d[78]), "+f"(d[79]), "+f"(d[80]), "+f"(d[81]), "+f"(d[82]), "+f"(d[83]), "+f"(d[84]), "+f"(d[85]), "+f"(d[86]), "+f"(d[87]), "+f"(d[88]), "+f"(d[89]), "+f"(d[90]), "+f"(d[91]), "+f"(d[92]), "+f"(d[93]), "+f"(d[94]), "+f"(d[95]), "+f"(d[96]), "+f"(d[97]), "+f"(d[98]), "+f"(d[99]), "+f"(d[100]), "+f"(d[101]), "+f"(d[102]), "+f"(d[103]), "+f"(d[104]), "+f"(d[105]), "+f"(d[106]), "+f"(d[107]), "+f"(d[108]), "+f"(d[109]), "+f"(d[110]), "+f"(d[111]), "+f"(d[112]), "+f"(d[113]), "+f"(d[114]), "+f"(d[115]), "+f"(d[116]), "+f"(d[117]), "+f"(d[118]), "+f"(d[119]), "+f"(d[120]), "+f"(d[121]), "+f"(d[122]), "+f"(d[123]), "+f"(d[124]), "+f"(d[125]), "+f"(d[126]), "+f"(d[127])
        : "l"(descA), "l"(descB), "r"(scaleD));
}

__device__ __forceinline__ void wgmma_m64n192k16_ss(float (&d)[96], uint64_t descA, uint64_t descB, int scaleD) {
    asm volatile("{\n.reg .pred p;\nsetp.ne.b32 p, %98, 0;\n"
        "wgmma.mma_async.sync.aligned.m64n192k16.f32.bf16.bf16 {%0, %1, %2, %3, %4, %5, %6, %7, %8, %9, %10, %11, %12, %13, %14, %15, %16, %17, %18, %19, %20, %21, %22, %23, %24, %25, %26, %27, %28, %29, %30, %31, %32, %33, %34, %35, %36, %37, %38, %39, %40, %41, %42, %43, %44, %45, %46, %47, %48, %49, %50, %51, %52, %53, %54, %55, %56, %57, %58, %59, %60, %61, %62, %63, %64, %65, %66, %67, %68, %69, %70, %71, %72, %73, %74, %75, %76, %77, %78, %79, %80, %81, %82, %83, %84, %85, %86, %87, %88, %89, %90, %91, %92, %93, %94, %95}, %96, %97, p, 1, 1, 1, 1;\n}\n"
        : "+f"(d[0]), "+f"(d[1]), "+f"(d[2]), "+f"(d[3]), "+f"(d[4]), "+f"(d[5]), "+f"(d[6]), "+f"(d[7]), "+f"(d[8]), "+f"(d[9]), "+f"(d[10]), "+f"(d[11]), "+f"(d[12]), "+f"(d[13]), "+f"(d[14]), "+f"(d[15]), "+f"(d[16]), "+f"(d[17]), "+f"(d[18]), "+f"(d[19]), "+f"(d[20]), "+f"(d[21]), "+f"(d[22]), "+f"(d[23]), "+f"(d[24]), "+f"(d[25]), "+f"(d[26]), "+f"(d[27]), "+f"(d[28]), "+f"(d[29]), "+f"(d[30]), "+f"(d[31]), "+f"(d[32]), "+f"(d[33]), "+f"(d[34]), "+f"(d[35]), "+f"(d[36]), "+f"(d[37]), "+f"(d[38]), "+f"(d[39]), "+f"(d[40]), "+f"(d[41]), "+f"(d[42]), "+f"(d[43]), "+f"(d[44]), "+f"(d[45]), "+f"(d[46]), "+f"(d[47]), "+f"(d[48]), "+f"(d[49]), "+f"(d[50]), "+f"(d[51]), "+f"(d[52]), "+f"(d[53]), "+f"(d[54]), "+f"(d[55]), "+f"(d[56]), "+f"(d[57]), "+f"(d[58]), "+f"(d[59]), "+f"(d[60]), "+f"(d[61]), "+f"(d[62]), "+f"(d[63]), "+f"(d[64]), "+f"(d[65]), "+f"(d[66]), "+f"(d[67]), "+f"(d[68]), "+f"(d[69]), "+f"(d[70]), "+f"(d[71]), "+f"(d[72]), "+f"(d[73]), "+f"(d[74]), "+f"(d[75]), "+f"(d[76]), "+f"(d[77]), "+f"(d[78]), "+f"(d[79]), "+f"(d[80]), "+f"(d[81]), "+f"(d[82]), "+f"(d[83]), "+f"(d[84]), "+f"(d[85]), "+f"(d[86]), "+f"(d[87]), "+f"(d[88]), "+f"(d[89]), "+f"(d[90]), "+f"(d[91]), "+f"(d[92]), "+f"(d[93]), "+f"(d[94]), "+f"(d[95])
        : "l"(descA), "l"(descB), "r"(scaleD));
}

__device__ __forceinline__ void wgmma_m64n128k16_ss(float (&d)[64], uint64_t descA, uint64_t descB, int scaleD) {
    asm volatile("{\n.reg .pred p;\nsetp.ne.b32 p, %66, 0;\n"
        "wgmma.mma_async.sync.aligned.m64n128k16.f32.bf16.bf16 {%0, %1, %2, %3, %4, %5, %6, %7, %8, %9, %10, %11, %12, %13, %14, %15, %16, %17, %18, %19, %20, %21, %22, %23, %24, %25, %26, %27, %28, %29, %30, %31, %32, %33, %34, %35, %36, %37, %38, %39, %40, %41, %42, %43, %44, %45, %46, %47, %48, %49, %50, %51, %52, %53, %54, %55, %56, %57, %58, %59, %60, %61, %62, %63}, %64, %65, p, 1, 1, 0, 1;\n}\n"
        : "+f"(d[0]), "+f"(d[1]), "+f"(d[2]), "+f"(d[3]), "+f"(d[4]), "+f"(d[5]), "+f"(d[6]), "+f"(d[7]), "+f"(d[8]), "+f"(d[9]), "+f"(d[10]), "+f"(d[11]), "+f"(d[12]), "+f"(d[13]), "+f"(d[14]), "+f"(d[15]), "+f"(d[16]), "+f"(d[17]), "+f"(d[18]), "+f"(d[19]), "+f"(d[20]), "+f"(d[21]), "+f"(d[22]), "+f"(d[23]), "+f"(d[24]), "+f"(d[25]), "+f"(d[26]), "+f"(d[27]), "+f"(d[28]), "+f"(d[29]), "+f"(d[30]), "+f"(d[31]), "+f"(d[32]), "+f"(d[33]), "+f"(d[34]), "+f"(d[35]), "+f"(d[36]), "+f"(d[37]), "+f"(d[38]), "+f"(d[39]), "+f"(d[40]), "+f"(d[41]), "+f"(d[42]), "+f"(d[43]), "+f"(d[44]), "+f"(d[45]), "+f"(d[46]), "+f"(d[47]), "+f"(d[48]), "+f"(d[49]), "+f"(d[50]), "+f"(d[51]), "+f"(d[52]), "+f"(d[53]), "+f"(d[54]), "+f"(d[55]), "+f"(d[56]), "+f"(d[57]), "+f"(d[58]), "+f"(d[59]), "+f"(d[60]), "+f"(d[61]), "+f"(d[62]), "+f"(d[63])
        : "l"(descA), "l"(descB), "r"(scaleD));
}


__device__ __forceinline__ void quad_transpose(uint32_t& r0, uint32_t& r1, uint32_t& r2, uint32_t& r3, int t) {
    const bool o1 = t & 1, o2 = t & 2;
    uint32_t x, y;
    x = o1 ? r0 : r1; y = __shfl_xor_sync(0xffffffffu, x, 1); if (o1) r0 = y; else r1 = y;
    x = o1 ? r2 : r3; y = __shfl_xor_sync(0xffffffffu, x, 1); if (o1) r2 = y; else r3 = y;
    x = o2 ? r0 : r2; y = __shfl_xor_sync(0xffffffffu, x, 2); if (o2) r0 = y; else r2 = y;
    x = o2 ? r1 : r3; y = __shfl_xor_sync(0xffffffffu, x, 2); if (o2) r1 = y; else r3 = y;
}


__device__ __forceinline__ float warp_sum(float s) {
#pragma unroll
    for (int o = 16; o > 0; o >>= 1) s += __shfl_xor_sync(0xffffffffu, s, o);
    return s;
}
__device__ __forceinline__ uint32_t hsub2(uint32_t a, uint32_t b) {
    __nv_bfloat162 r = __hsub2_rn(*reinterpret_cast<__nv_bfloat162*>(&a), *reinterpret_cast<__nv_bfloat162*>(&b));
    return *reinterpret_cast<uint32_t*>(&r);
}
__device__ __forceinline__ void ln_stats2(const uint32_t (&x)[2][8], float2 (&st)[2]) {
    float piv[2], s[2], ss[2];
#pragma unroll
    for (int r = 0; r < 2; r++) piv[r] = __shfl_sync(0xffffffffu, bf_lo(x[r][0]), 0);
#pragma unroll
    for (int r = 0; r < 2; r++) {
        float s0 = 0.f, s1 = 0.f, q0 = 0.f, q1 = 0.f;
#pragma unroll
        for (int i = 0; i < 8; i++) {
            const float d0 = bf_lo(x[r][i]) - piv[r], d1 = bf_hi(x[r][i]) - piv[r];
            s0 += d0; s1 += d1; q0 = fmaf(d0, d0, q0); q1 = fmaf(d1, d1, q1);
        }
        s[r] = s0 + s1; ss[r] = q0 + q1;
    }
#pragma unroll
    for (int o = 16; o > 0; o >>= 1) {
#pragma unroll
        for (int r = 0; r < 2; r++) { s[r] += __shfl_xor_sync(0xffffffffu, s[r], o); ss[r] += __shfl_xor_sync(0xffffffffu, ss[r], o); }
    }
#pragma unroll
    for (int r = 0; r < 2; r++) {
        const float md = s[r] * (1.0f / D_);
        const float var = bf16r(fmaxf(fmaf(-md, md, ss[r] * (1.0f / D_)), 0.f));
        st[r] = make_float2(bf16r(piv[r] + md), 1.0f / bf16r(sqrtf(bf16r(var + 1e-5f))));
    }
}
__device__ __forceinline__ void ln_apply(const uint32_t (&x)[8], float2 st, uint32_t (&o)[8]) {
    const uint32_t m2 = pack_bf16(st.x, st.x);
#pragma unroll
    for (int i = 0; i < 8; i++) {
        const uint32_t d = hsub2(x[i], m2);
        o[i] = pack_bf16(bf_lo(d) * st.y, bf_hi(d) * st.y);
    }
}

constexpr int K1_THREADS = 352;
constexpr int UT_PAD = 128;
constexpr int UT_LEN = UT_PAD + S_;
constexpr int KR_LEN = 2080;
constexpr int YP_LEN = S_ + (S_ / 32) * 8;

struct __align__(128) K1Smem {
    bf16 uT[4][UT_LEN];
    bf16 xT[4][S_];
    bf16 kr[4][2][KR_LEN];
    float yP[2][4][YP_LEN];
    alignas(128) float st[S_ + S_ / 2];
    alignas(128) uint4 wS[512][4];
    float red[8][32];
    uint64_t bar, bar2, bar3, bar4;
};

__device__ __forceinline__ void mma16816(float (&c)[4], uint32_t a0, uint32_t a1, uint32_t a2, uint32_t a3, uint32_t b0, uint32_t b1) {
    asm volatile("mma.sync.aligned.m16n8k16.row.col.f32.bf16.bf16.f32 {%0,%1,%2,%3}, {%4,%5,%6,%7}, {%8,%9}, {%0,%1,%2,%3};"
        : "+f"(c[0]), "+f"(c[1]), "+f"(c[2]), "+f"(c[3])
        : "r"(a0), "r"(a1), "r"(a2), "r"(a3), "r"(b0), "r"(b1));
}
__device__ __forceinline__ void ldsm_x4(uint32_t& r0, uint32_t& r1, uint32_t& r2, uint32_t& r3, uint32_t addr) {
    asm volatile("ldmatrix.sync.aligned.m8n8.x4.shared.b16 {%0,%1,%2,%3}, [%4];" : "=r"(r0), "=r"(r1), "=r"(r2), "=r"(r3) : "r"(addr) : "memory");
}

__device__ __forceinline__ void conv_mma(const bf16* uTc, const bf16* krlane, float (&acc)[16][4], int lane, int half) {
    const int lrow = lane & 7, lk = (lane >> 3) & 1, lt = lane >> 4;
    const uint32_t ubase = smem_u32(uTc) + (UT_PAD + 16 * (8 * lt + lrow) + 8 * lk) * 2;
#pragma unroll 1
    for (int pp = 0; pp < 4; pp++) {
        const int p = half * 4 + pp;
        uint32_t U[16][2];
#pragma unroll
        for (int j = 0; j < 16; j += 2) ldsm_x4(U[j][0], U[j][1], U[j + 1][0], U[j + 1][1], ubase + (j * 128 - p * 16) * 2);
        const uint32_t* kp = reinterpret_cast<const uint32_t*>(krlane - 16 * p);
        const volatile uint32_t* kpv = kp;
        uint32_t a0 = kp[0], a1 = kp[-4], a2 = kp[4], a3 = kpv[0];
#pragma unroll
        for (int q = 0; q < 16; q++) {
            uint32_t b0 = 0, b1 = 0, b2 = 0, b3 = 0;
            if (q < 15) { b0 = kp[-64 * (q + 1)]; b1 = kp[-64 * (q + 1) - 4]; b2 = kp[-64 * (q + 1) + 4]; b3 = kpv[-64 * (q + 1)]; }
#pragma unroll
            for (int n = 15; n >= q; n--) mma16816(acc[n], a0, a1, a2, a3, U[n - q][0], U[n - q][1]);
            a0 = b0; a1 = b1; a2 = b2; a3 = b3;
        }
    }
}

__device__ __forceinline__ void cp_async16(uint32_t dst, const void* src) {
    asm volatile("cp.async.cg.shared.global [%0], [%1], 16;" :: "r"(dst), "l"(src) : "memory");
}

__global__ void __cluster_dims__(2, 1, 1) __launch_bounds__(K1_THREADS, 1)
conv_kernel(const bf16* __restrict__ q, const bf16* __restrict__ k, const bf16* __restrict__ v,
            const bf16* __restrict__ shift_k, const bf16* __restrict__ ssm_k, const bf16* __restrict__ ssm_D,
            const __grid_constant__ CUtensorMap mapWg, const __grid_constant__ CUtensorMap mapWu, const bf16* __restrict__ wd) {
    extern __shared__ __align__(1024) uint8_t smem_raw[];
    pdl_launch();
    K1Smem& sm = *reinterpret_cast<K1Smem*>(smem_raw);
    const int tid = threadIdx.x, lane = tid & 31, warp = tid >> 5;
    const int bid = blockIdx.x;
    const int rank = bid & 1;
    const int c0 = 8 * (bid >> 1);
    const int cown = c0 + 4 * rank;
    const uint32_t bar = smem_u32(&sm.bar);
    if (tid == 0) {
        mbar_init(bar, 1);
        mbar_init(bar + 8, 1);
        mbar_init(bar + 16, 1);
        mbar_init(bar + 24, 1);
        asm volatile("fence.mbarrier_init.release.cluster;" ::: "memory");
        mbar_expect_tx(bar, 1024 * 4 * 2);
        mbar_expect_tx(bar + 8, 1024 * 4 * 2);
    }
    cluster_arrive_relaxed();

    if (warp < 8) {
        const int s0 = 1024 * rank + 4 * tid;
        uint4 kk[7], vv[4], qq[4], sw[4];
#pragma unroll
        for (int i = 0; i < 4; i++) kk[3 + i] = ldg128_l2(k + (size_t)(s0 + i) * D_ + c0);
#pragma unroll
        for (int i = 0; i < 4; i++) vv[i] = ldg128_l2(v + (size_t)(s0 + i) * D_ + c0);
        if (lane == 0) {
#pragma unroll
            for (int i = 0; i < 3; i++) {
                const int s = s0 - 3 + i;
                kk[i] = make_uint4(0, 0, 0, 0);
                if (s >= 0) kk[i] = ldg128(k + (size_t)s * D_ + c0);
            }
        }
#pragma unroll
        for (int i = 0; i < 4; i++) sw[i] = ldg128(shift_k + (size_t)c0 * 4 + 8 * i);
        uint4 kq[4]; uint32_t nx[4];
#pragma unroll
        for (int c = 0; c < 4; c++) {
            const bf16* kr = ssm_k + (size_t)(cown + c) * S_;
            kq[c] = ldg128(kr + 8 * tid);
            nx[c] = 0u;
            if (tid < 255) nx[c] = ldg16(kr + 8 * tid + 8);
        }
        const uint32_t dval = ldg16(ssm_D + cown + (warp >> 1));
        if (tid < 64) *reinterpret_cast<uint4*>(&sm.uT[tid >> 4][(tid & 15) * 8]) = make_uint4(0, 0, 0, 0);
#pragma unroll
        for (int i = 0; i < 3; i++) {
            uint4 t;
            t.x = __shfl_up_sync(0xffffffffu, kk[4 + i].x, 1); t.y = __shfl_up_sync(0xffffffffu, kk[4 + i].y, 1);
            t.z = __shfl_up_sync(0xffffffffu, kk[4 + i].z, 1); t.w = __shfl_up_sync(0xffffffffu, kk[4 + i].w, 1);
            if (lane != 0) kk[i] = t;
        }
        uint32_t kvw[4][4];
        const uint32_t* kkw = reinterpret_cast<const uint32_t*>(kk);
        const uint32_t* vvw = reinterpret_cast<const uint32_t*>(vv);
        const uint32_t* qqw = reinterpret_cast<const uint32_t*>(qq);
#pragma unroll
        for (int i2 = 0; i2 < 4; i2++) {
            const uint32_t t0 = __byte_perm(sw[i2].x, sw[i2].z, 0x5410), t1 = __byte_perm(sw[i2].x, sw[i2].z, 0x7632);
            const uint32_t t2 = __byte_perm(sw[i2].y, sw[i2].w, 0x5410), t3 = __byte_perm(sw[i2].y, sw[i2].w, 0x7632);
#pragma unroll
            for (int r = 0; r < 4; r++) {
                uint32_t a = hmul2(kkw[(r + 0) * 4 + i2], t3);
                a = hadd2(a, hmul2(kkw[(r + 1) * 4 + i2], t2));
                a = hadd2(a, hmul2(kkw[(r + 2) * 4 + i2], t1));
                a = hadd2(a, hmul2(kkw[(r + 3) * 4 + i2], t0));
                kvw[r][i2] = hmul2(a, vvw[r * 4 + i2]);
            }
        }
        cluster_wait();
        const uint32_t rbar = mapa(bar, (uint32_t)(rank ^ 1));
#pragma unroll
        for (int i2 = 0; i2 < 4; i2++) {
#pragma unroll
            for (int e = 0; e < 2; e++) {
                const uint32_t sel = e ? 0x7632 : 0x5410;
                const uint32_t w0 = __byte_perm(kvw[0][i2], kvw[1][i2], sel), w1 = __byte_perm(kvw[2][i2], kvw[3][i2], sel);
                const int cc = 2 * i2 + e;
                if ((cc >> 2) == rank) *reinterpret_cast<uint2*>(&sm.uT[cc & 3][UT_PAD + s0]) = make_uint2(w0, w1);
                else st_async_v2(mapa(smem_u32(&sm.uT[cc & 3][UT_PAD + s0]), (uint32_t)(rank ^ 1)), w0, w1, rbar);
            }
        }
#pragma unroll
        for (int c = 0; c < 4; c++) {
            uint4 a, b;
            a.x = __byte_perm(kq[c].w, 0, 0x1032); a.y = __byte_perm(kq[c].z, 0, 0x1032);
            a.z = __byte_perm(kq[c].y, 0, 0x1032); a.w = __byte_perm(kq[c].x, 0, 0x1032);
            b.x = __byte_perm(nx[c], kq[c].w, 0x7610); b.y = __byte_perm(kq[c].w, kq[c].z, 0x7610);
            b.z = __byte_perm(kq[c].z, kq[c].y, 0x7610); b.w = __byte_perm(kq[c].y, kq[c].x, 0x7610);
            *reinterpret_cast<uint4*>(&sm.kr[c][0][2040 - 8 * tid]) = a;
            *reinterpret_cast<uint4*>(&sm.kr[c][1][2040 - 8 * tid]) = b;
            if (tid == 0) {
                *reinterpret_cast<uint4*>(&sm.kr[c][1][2048]) = make_uint4(kq[c].x & 0xffffu, 0, 0, 0);
            } else if (tid < 8) {
                if (tid < 4) *reinterpret_cast<uint4*>(&sm.kr[c][1][2048 + 8 * tid]) = make_uint4(0, 0, 0, 0);
                else *reinterpret_cast<uint4*>(&sm.kr[c][0][2048 + 8 * (tid - 4)]) = make_uint4(0, 0, 0, 0);
            }
        }
#pragma unroll
        for (int i = 0; i < 4; i++) qq[i] = ldg128(q + (size_t)(s0 + i) * D_ + c0);
        named_bar(6, 288);
        mbar_wait_cluster(bar, 0);

        const int ch = warp >> 1, half = warp & 1;
        const int g = lane >> 2, t = lane & 3;
        float acc[16][4];
#pragma unroll
        for (int i = 0; i < 16; i++) { acc[i][0] = acc[i][1] = acc[i][2] = acc[i][3] = 0.f; }
        const bf16* krlane = (g & 1) ? &sm.kr[ch][0][2047 - g + 2 * t] : &sm.kr[ch][1][2048 - g + 2 * t];
        conv_mma(sm.uT[ch], krlane, acc, lane, half);
#pragma unroll
        for (int i2 = 0; i2 < 4; i2++) {
#pragma unroll
            for (int e = 0; e < 2; e++) {
                const uint32_t sel = e ? 0x7632 : 0x5410;
                const uint32_t w0 = __byte_perm(qqw[i2], qqw[4 + i2], sel), w1 = __byte_perm(qqw[8 + i2], qqw[12 + i2], sel);
                const int cc = 2 * i2 + e;
                if ((cc >> 2) == rank) *reinterpret_cast<uint2*>(&sm.xT[cc & 3][s0]) = make_uint2(w0, w1);
                else st_async_v2(mapa(smem_u32(&sm.xT[cc & 3][s0]), (uint32_t)(rank ^ 1)), w0, w1, rbar + 8);
            }
        }
        float* yp = &sm.yP[half][ch][40 * t + g];
#pragma unroll
        for (int n = 0; n < 16; n++) {
            yp[160 * n] = acc[n][0];
            yp[160 * n + 16] = acc[n][1];
            yp[160 * n + 8] = acc[n][2];
            yp[160 * n + 24] = acc[n][3];
        }
        named_bar(7, 288);
        mbar_wait_cluster(bar + 8, 0);
        {
            const int tt = tid & 63;
            bf16* dst = g_hT + (size_t)(cown + ch) * HT_PITCH;
            const uint32_t d2 = dval * 0x10001u;
#pragma unroll
            for (int j = 0; j < 8; j++) {
                const int s = (j * 64 + tt) * 4;
                float4 a = *reinterpret_cast<const float4*>(&sm.yP[0][ch][s + (s >> 5) * 8]);
                const float4 a2 = *reinterpret_cast<const float4*>(&sm.yP[1][ch][s + (s >> 5) * 8]);
                const uint2 kv2 = *reinterpret_cast<const uint2*>(&sm.uT[ch][UT_PAD + s]);
                const uint2 x2 = *reinterpret_cast<const uint2*>(&sm.xT[ch][s]);
                const uint2 m2 = *reinterpret_cast<const uint2*>(&sm.st[S_ + s / 2]);
                const float4 r4 = *reinterpret_cast<const float4*>(&sm.st[s]);
                const uint32_t ya = hadd2(pack_bf16(a.x + a2.x, a.y + a2.y), hmul2(kv2.x, d2));
                const uint32_t yb = hadd2(pack_bf16(a.z + a2.z, a.w + a2.w), hmul2(kv2.y, d2));
                const uint32_t da = hsub2(x2.x, m2.x), db = hsub2(x2.y, m2.y);
                const uint32_t qa = pack_bf16(bf_lo(da) * r4.x, bf_hi(da) * r4.y), qb = pack_bf16(bf_lo(db) * r4.z, bf_hi(db) * r4.w);
                *reinterpret_cast<uint2*>(dst + s) = make_uint2(hadd2(x2.x, hmul2(qa, ya)), hadd2(x2.y, hmul2(qb, yb)));
            }
        }
    } else {
        cluster_wait();
        const uint32_t hbar = bar + 16;
        if (warp < 10) {
            {
                const int rr = 8 * (warp - 8);
                uint32_t xq[4][2][8];
#pragma unroll
                for (int r = 0; r < 8; r++) {
                    const uint4 qa = ldg128(q + (size_t)(16 * bid + rr + r) * D_ + 8 * lane);
                    const uint4 qb = ldg128(q + (size_t)(16 * bid + rr + r) * D_ + 8 * (lane + 32));
                    uint32_t* x = xq[r >> 1][r & 1];
                    x[0] = qa.x; x[1] = qa.y; x[2] = qa.z; x[3] = qa.w; x[4] = qb.x; x[5] = qb.y; x[6] = qb.z; x[7] = qb.w;
                }
#pragma unroll
                for (int r2 = 0; r2 < 4; r2++) {
                    float2 sa[2];
                    ln_stats2(xq[r2], sa);
                    if (lane == 0) {
                        *reinterpret_cast<float2*>(&g_st1[16 * bid + rr + 2 * r2]) = make_float2(sa[0].y, sa[1].y);
                        reinterpret_cast<uint32_t*>(&g_st1[S_])[(16 * bid + rr) / 2 + r2] = pack_bf16(sa[0].x, sa[1].x);
                    }
                }
            }
            if (lane == 0) { __threadfence(); atomicAdd(&g_cnt, 1u); }
            if (warp == 9) return;
            if (lane == 0) {
                unsigned int c; int spins = 0;
                while (true) {
                    asm volatile("ld.acquire.gpu.global.u32 %0, [%1];" : "=r"(c) : "l"(&g_cnt) : "memory");
                    if (c >= 2 * gridDim.x || ++spins > (1 << 22)) break;
                    __nanosleep(200);
                }
                asm volatile("fence.proxy.async;" ::: "memory");
                mbar_expect_tx(hbar + 8, 12288);
                asm volatile("cp.async.bulk.shared::cluster.global.mbarrier::complete_tx::bytes [%0], [%1], %2, [%3];"
                    :: "r"(smem_u32(&sm.st[0])), "l"(&g_st1[0]), "r"(12288), "r"(hbar + 8) : "memory");
            }
            mbar_wait(hbar + 8, 0);
            named_bar(7, 288);
        } else {
            named_bar(6, 288);
            if (lane == 0) asm volatile("cp.async.bulk.prefetch.L2.global [%0], %1;" :: "l"(wd + (size_t)bid * 7168), "r"(14336) : "memory");
            if (bid < 112) {
                if (lane == 0) {
                    mbar_expect_tx(hbar, 32768);
                    const CUtensorMap* mw = (bid < 56) ? &mapWg : &mapWu;
                    const int col = 32 * ((bid < 56) ? bid : bid - 56);
                    tma_load_2d(smem_u32(&sm.wS[0][0]), mw, hbar, col, 0);
                    tma_load_2d(smem_u32(&sm.wS[256][0]), mw, hbar, col, 256);
                }
                mbar_wait(hbar, 0);
                const int cq = lane & 3, rgp = lane >> 2;
                float cs[8];
#pragma unroll
                for (int i = 0; i < 8; i++) cs[i] = 0.f;
#pragma unroll 4
                for (int r = 0; r < 64; r++) {
                    const uint4 w = sm.wS[r * 8 + rgp][cq];
                    cs[0] += bf_lo(w.x); cs[1] += bf_hi(w.x); cs[2] += bf_lo(w.y); cs[3] += bf_hi(w.y);
                    cs[4] += bf_lo(w.z); cs[5] += bf_hi(w.z); cs[6] += bf_lo(w.w); cs[7] += bf_hi(w.w);
                }
#pragma unroll
                for (int i = 0; i < 8; i++) {
                    cs[i] += __shfl_xor_sync(0xffffffffu, cs[i], 4);
                    cs[i] += __shfl_xor_sync(0xffffffffu, cs[i], 8);
                    cs[i] += __shfl_xor_sync(0xffffffffu, cs[i], 16);
                }
                if (lane < 4) {
                    *reinterpret_cast<float4*>(&g_colsum[32 * bid + lane * 8]) = make_float4(cs[0], cs[1], cs[2], cs[3]);
                    *reinterpret_cast<float4*>(&g_colsum[32 * bid + lane * 8 + 4]) = make_float4(cs[4], cs[5], cs[6], cs[7]);
                }
            }
        }
    }
}

constexpr int G1_THREADS = 384;
constexpr int G1_STAGES = 3;
constexpr int G1_A_BYTES = 8 * 16384;
constexpr int G1_B_STAGE = 32768;
constexpr int G1_OFF_B = G1_A_BYTES;
constexpr int G1_OFF_STATS = G1_OFF_B + G1_STAGES * G1_B_STAGE;
constexpr int G1_OFF_CS = G1_OFF_STATS + 1024;
constexpr int G1_OFF_BAR = G1_OFF_CS + 1792;
constexpr int G1_SMEM = G1_OFF_BAR + 128;

__device__ __forceinline__ float tanh_fast(float x) { float t; asm("tanh.approx.f32 %0, %1;" : "=f"(t) : "f"(x)); return t; }

template <int NT>
__device__ __forceinline__ void g1_math(const float (&acc)[NT * 8], const float* cs_g, const float* cs_u, float2 st0, float2 st1, uint32_t (&P)[NT * 2], int t) {
    const float r0 = st0.y, r1 = st1.y, m0 = -st0.x * st0.y, m1 = -st1.x * st1.y;
#pragma unroll
    for (int j = 0; j < NT; j++) {
        const float2 cg = *reinterpret_cast<const float2*>(cs_g + 8 * j + 2 * t);
        const float2 cu = *reinterpret_cast<const float2*>(cs_u + 8 * j + 2 * t);
        float r[4];
#pragma unroll
        for (int e = 0; e < 4; e++) {
            const float rr = (e < 2) ? r0 : r1, mm = (e < 2) ? m0 : m1;
            const float gh = fmaf(acc[4 * j + e], 0.5f * rr, (0.5f * mm) * ((e & 1) ? cg.y : cg.x));
            const float uv = fmaf(acc[4 * (NT + j) + e], rr, mm * ((e & 1) ? cu.y : cu.x));
            r[e] = fmaf(tanh_fast(gh), 0.5f, 0.5f) * uv;
        }
        P[2 * j] = pack_bf16(r[0], r[1]);
        P[2 * j + 1] = pack_bf16(r[2], r[3]);
    }
}
template <int NT>
__device__ __forceinline__ void g1_store(uint32_t (&P)[NT * 2], bf16* out0, int t) {
#pragma unroll
    for (int j0 = 0; j0 < NT; j0 += 4) {
        quad_transpose(P[2 * j0], P[2 * j0 + 2], P[2 * j0 + 4], P[2 * j0 + 6], t);
        quad_transpose(P[2 * j0 + 1], P[2 * j0 + 3], P[2 * j0 + 5], P[2 * j0 + 7], t);
        *reinterpret_cast<uint4*>(out0 + 8 * (j0 + t)) = make_uint4(P[2 * j0], P[2 * j0 + 2], P[2 * j0 + 4], P[2 * j0 + 6]);
        *reinterpret_cast<uint4*>(out0 + 8 * F_ + 8 * (j0 + t)) = make_uint4(P[2 * j0 + 1], P[2 * j0 + 3], P[2 * j0 + 5], P[2 * j0 + 7]);
    }
}

__global__ void __cluster_dims__(2, 1, 1) __launch_bounds__(G1_THREADS, 1)
gemm1_kernel(const __grid_constant__ CUtensorMap mapA, const __grid_constant__ CUtensorMap mapG4, const __grid_constant__ CUtensorMap mapU4,
             const __grid_constant__ CUtensorMap mapG3, const __grid_constant__ CUtensorMap mapU3) {
    extern __shared__ __align__(1024) uint8_t smem_raw[];
    const uint32_t sb = smem_u32(smem_raw);
    const int tid = threadIdx.x, lane = tid & 31, warp = tid >> 5, wgi = tid >> 7;
    const int rank = blockIdx.x & 1;
    const int cb = blockIdx.x & 7, rb = blockIdx.x >> 3;
    pdl_launch();
    if (tid == 32) { prefetch_map(&mapA); prefetch_map(&mapG3); prefetch_map(&mapU3); }
    const uint32_t barA = sb + G1_OFF_BAR;
    const uint32_t barF = barA + 64;
    const uint32_t barE = barF + 8 * G1_STAGES;
    const uint32_t barS = barE + 8 * G1_STAGES;
    if (tid == 0) {
        for (int i = 0; i < 8; i++) mbar_init(barA + 8 * i, 1);
        for (int i = 0; i < G1_STAGES; i++) { mbar_init(barF + 8 * i, 1); mbar_init(barE + 8 * i, 2); }
        mbar_init(barS, 1);
        for (int i = 0; i < 8; i++) mbar_expect_tx(barA + 8 * i, 16384);
        asm volatile("fence.mbarrier_init.release.cluster;" ::: "memory");
    }
    __syncthreads();
    cluster_arrive_relaxed();

    if (wgi == 0) {
        reg_dealloc<40>();
        if (warp == 0) {
            cluster_wait();
            if (lane == 0) {
                int st = 0, ph = 1;
                for (int it = 0; it < 16; it++) {
                    const int kc = it & 7;
                    if (it == 2) {
                        pdl_wait();
                        for (int i = 0; i < 4; i++) {
                            const int c = 2 * i + rank;
                            tma_load_3d_mc(sb + c * 16384, &mapA, barA + 8 * c, 0, c * 64, rb * 2, (uint16_t)3);
                        }
                    }
                    mbar_wait(barE + 8 * st, ph);
                    const uint32_t dst = sb + G1_OFF_B + st * G1_B_STAGE;
                    if (it < 8) {
                        mbar_expect_tx(barF + 8 * st, 32768);
                        tma_load_2d(dst, &mapG4, barF + 8 * st, cb * 224, kc * 64);
                        tma_load_2d(dst + 8192, &mapG4, barF + 8 * st, cb * 224 + 64, kc * 64);
                        tma_load_2d(dst + 16384, &mapU4, barF + 8 * st, cb * 224, kc * 64);
                        tma_load_2d(dst + 24576, &mapU4, barF + 8 * st, cb * 224 + 64, kc * 64);
                    } else {
                        mbar_expect_tx(barF + 8 * st, 24576);
                        tma_load_3d(dst, &mapG3, barF + 8 * st, 0, kc * 64, cb * 7 + 4);
                        tma_load_3d(dst + 12288, &mapU3, barF + 8 * st, 0, kc * 64, cb * 7 + 4);
                    }
                    if (++st == G1_STAGES) { st = 0; ph ^= 1; }
                }
            }
            __syncwarp();
        } else if (warp == 1) {
            cluster_wait();
            pdl_wait();
            float* cs = reinterpret_cast<float*>(smem_raw + G1_OFF_CS);
            for (int i = lane; i < 448; i += 32) cs[i] = __ldcg((i < 224) ? &g_colsum[cb * 224 + i] : &g_colsum[F_ + cb * 224 + (i - 224)]);
            __syncwarp();
            if (lane == 0) mbar_arrive(barS);
        } else {
            cluster_wait();
        }
    } else {
        reg_alloc<232>();
        cluster_wait();
        const int cw = wgi - 1;
        const int g = lane >> 2, t = lane & 3, wl = warp & 3, tl = tid & 127;
        bf16* outp = g_hh + (size_t)(rb * 128 + cw * 64 + wl * 16 + g) * F_ + cb * 224;
        const float* cs = reinterpret_cast<const float*>(smem_raw + G1_OFF_CS);
        int st = 0, ph = 0;
        float2 st0, st1;
        uint32_t P1[32];
        {
            float acc[128];
            const int kq = lane >> 3, mp = lane & 7;
            const uint8_t* sbase = smem_raw + cw * 8192 + kq * 128 + (mp & 3) * 4;
            const int mc = 2 * wl + (mp >> 2);
            float p0 = 0.f, p1 = 0.f, s0 = 0.f, s1 = 0.f, q0 = 0.f, q1 = 0.f;
#pragma unroll 1
            for (int kc = 0; kc < 8; kc++) {
                mbar_wait(barA + 8 * kc, 0);
                mbar_wait(barF + 8 * st, ph);
                wgmma_fence();
                const uint32_t aaddr = sb + kc * 16384 + cw * 8192;
                const uint32_t baddr = sb + G1_OFF_B + st * G1_B_STAGE;
#pragma unroll
                for (int kk = 0; kk < 4; kk++)
                    wgmma_m64n256k16_ss(acc, make_desc(aaddr + kk * 2048, 8192, 1024, 1), make_desc(baddr + kk * 2048, 8192, 1024, 1), (kc | kk) != 0);
                wgmma_commit();
                if (kc == 0) {
                    const uint32_t w = *reinterpret_cast<const uint32_t*>(smem_raw + cw * 8192 + (mc << 4) + (mp & 3) * 4);
                    p0 = bf_lo(w); p1 = bf_hi(w);
                }
#pragma unroll
                for (int i = 0; i < 16; i++) {
                    const int kr = 4 * i;
                    const uint32_t w = *reinterpret_cast<const uint32_t*>(sbase + kc * 16384 + kr * 128 + ((mc ^ ((kr + kq) & 7)) << 4));
                    const float d0 = bf_lo(w) - p0, d1 = bf_hi(w) - p1;
                    s0 += d0; s1 += d1; q0 = fmaf(d0, d0, q0); q1 = fmaf(d1, d1, q1);
                }
                wgmma_wait<0>();
                if (tl == 0) mbar_arrive(barE + 8 * st);
                if (++st == G1_STAGES) { st = 0; ph ^= 1; }
            }
            {
#pragma unroll
                for (int o = 8; o <= 16; o <<= 1) {
                    s0 += __shfl_xor_sync(0xffffffffu, s0, o); s1 += __shfl_xor_sync(0xffffffffu, s1, o);
                    q0 += __shfl_xor_sync(0xffffffffu, q0, o); q1 += __shfl_xor_sync(0xffffffffu, q1, o);
                }
                const float md0 = s0 * (1.0f / D_), md1 = s1 * (1.0f / D_);
                const float v0 = bf16r(fmaxf(fmaf(-md0, md0, q0 * (1.0f / D_)), 0.f)), v1 = bf16r(fmaxf(fmaf(-md1, md1, q1 * (1.0f / D_)), 0.f));
                const float ma = bf16r(p0 + md0), mb = bf16r(p1 + md1);
                const float ra = 1.0f / bf16r(sqrtf(bf16r(v0 + 1e-5f))), rbb = 1.0f / bf16r(sqrtf(bf16r(v1 + 1e-5f)));
                const float mA = __shfl_sync(0xffffffffu, ma, g >> 1), mB = __shfl_sync(0xffffffffu, mb, g >> 1);
                const float rA = __shfl_sync(0xffffffffu, ra, g >> 1), rB = __shfl_sync(0xffffffffu, rbb, g >> 1);
                const float mC = __shfl_sync(0xffffffffu, ma, 4 + (g >> 1)), mD = __shfl_sync(0xffffffffu, mb, 4 + (g >> 1));
                const float rC = __shfl_sync(0xffffffffu, ra, 4 + (g >> 1)), rD = __shfl_sync(0xffffffffu, rbb, 4 + (g >> 1));
                st0 = (g & 1) ? make_float2(mB, rB) : make_float2(mA, rA);
                st1 = (g & 1) ? make_float2(mD, rD) : make_float2(mC, rC);
            }
            mbar_wait(barS, 0);
            g1_math<16>(acc, cs, cs + 224, st0, st1, P1, t);
        }
        {
            float acc[96];
#pragma unroll 1
            for (int kc = 0; kc < 8; kc++) {
                mbar_wait(barF + 8 * st, ph);
                wgmma_fence();
                const uint32_t aaddr = sb + kc * 16384 + cw * 8192;
                const uint32_t baddr = sb + G1_OFF_B + st * G1_B_STAGE;
#pragma unroll
                for (int kk = 0; kk < 4; kk++)
                    wgmma_m64n192k16_ss(acc, make_desc(aaddr + kk * 2048, 8192, 1024, 1), make_desc(baddr + kk * 1024, 4096, 512, 2), (kc | kk) != 0);
                wgmma_commit();
                if (kc == 0) g1_store<16>(P1, outp, t);
                wgmma_wait<0>();
                if (tl == 0) mbar_arrive(barE + 8 * st);
                if (++st == G1_STAGES) { st = 0; ph ^= 1; }
            }
            uint32_t P2[24];
            g1_math<12>(acc, cs + 128, cs + 224 + 128, st0, st1, P2, t);
            g1_store<12>(P2, outp + 128, t);
        }
    }
}

constexpr int G2_THREADS = 384;
constexpr int G2_STAGES = 6;
constexpr int G2_STAGE = 32768;
constexpr int G2_OFF_X = G2_STAGES * G2_STAGE;
constexpr int G2_OFF_BAR = G2_OFF_X + 32768;
constexpr int G2_SMEM = G2_OFF_BAR + 128;
constexpr int G2_KSTEPS = 14;
constexpr int G2_PRE = 6;

__device__ __forceinline__ void ldsm_x4_t(uint32_t& r0, uint32_t& r1, uint32_t& r2, uint32_t& r3, uint32_t addr) {
    asm volatile("ldmatrix.sync.aligned.m8n8.x4.trans.shared.b16 {%0,%1,%2,%3}, [%4];" : "=r"(r0), "=r"(r1), "=r"(r2), "=r"(r3) : "r"(addr) : "memory");
}

template <int KS>
__device__ __forceinline__ void g2_finish(const float (&acc)[64], const uint8_t* smem_raw, uint32_t sb, uint32_t barX, uint32_t barH, int phH,
                                          uint32_t hslot, bf16* out, int rb, int nb, int cw, int wl, int lane, int tl) {
    const int g = lane >> 2, t = lane & 3;
    {
        const uint32_t dst = mapa(sb + G2_OFF_X + cw * 16384 + tl * 16, (uint32_t)(KS ^ 1));
        const uint32_t rbar = mapa(barX + 8 * cw, (uint32_t)(KS ^ 1));
#pragma unroll
        for (int i = 0; i < 8; i++) {
            const int j = 8 * (KS ^ 1) + i;
            st_async_v4f(dst + i * 2048, acc[4 * j], acc[4 * j + 1], acc[4 * j + 2], acc[4 * j + 3], rbar);
        }
    }
    const float4* xb = reinterpret_cast<const float4*>(smem_raw + G2_OFF_X + cw * 16384) + tl;
    bf16* o0 = out + (size_t)(rb * 128 + cw * 64 + wl * 16 + g) * D_ + nb * 128 + 64 * KS;
    uint32_t ha[8], hb[8];
    mbar_wait(barH, phH);
    {
        const int chl = 8 * (lane >> 4) + (lane & 7), sb8 = 2 * wl + ((lane >> 3) & 1);
        const uint32_t hbase = hslot + cw * 8192 + chl * 128 + ((sb8 ^ (lane & 7)) << 4);
#pragma unroll
        for (int j = 0; j < 8; j += 2) ldsm_x4_t(ha[j], hb[j], ha[j + 1], hb[j + 1], hbase + j * 1024);
    }
    mbar_wait_cluster(barX + 8 * cw, 0);
#pragma unroll
    for (int j0 = 0; j0 < 8; j0 += 4) {
        uint32_t P0[4], P1[4];
#pragma unroll
        for (int jj = 0; jj < 4; jj++) {
            const int j = j0 + jj, ja = 8 * KS + j;
            const float4 x = xb[j * 128];
            P0[jj] = hadd2(ha[j], pack_bf16(acc[4 * ja] + x.x, acc[4 * ja + 1] + x.y));
            P1[jj] = hadd2(hb[j], pack_bf16(acc[4 * ja + 2] + x.z, acc[4 * ja + 3] + x.w));
        }
        quad_transpose(P0[0], P0[1], P0[2], P0[3], t);
        quad_transpose(P1[0], P1[1], P1[2], P1[3], t);
        *reinterpret_cast<uint4*>(o0 + 8 * (j0 + t)) = make_uint4(P0[0], P0[1], P0[2], P0[3]);
        *reinterpret_cast<uint4*>(o0 + 8 * D_ + 8 * (j0 + t)) = make_uint4(P1[0], P1[1], P1[2], P1[3]);
    }
}

__global__ void __cluster_dims__(2, 1, 1) __launch_bounds__(G2_THREADS, 1)
gemm2_kernel(const __grid_constant__ CUtensorMap mapHH, const __grid_constant__ CUtensorMap mapWd, const __grid_constant__ CUtensorMap mapH,
             bf16* __restrict__ out) {
    extern __shared__ __align__(1024) uint8_t smem_raw[];
    const uint32_t sb = smem_u32(smem_raw);
    const int tid = threadIdx.x, lane = tid & 31, warp = tid >> 5, wgi = tid >> 7;
    const int ks = blockIdx.x & 1, nb = (blockIdx.x >> 1) & 3, rb = blockIdx.x >> 3;
    if (tid == 32) { prefetch_map(&mapHH); prefetch_map(&mapH); }
    const uint32_t barF = sb + G2_OFF_BAR;
    const uint32_t barE = barF + 8 * G2_STAGES;
    const uint32_t barX = barE + 8 * G2_STAGES;
    if (tid == 0) {
        for (int i = 0; i < G2_STAGES; i++) { mbar_init(barF + 8 * i, 1); mbar_init(barE + 8 * i, 2); }
        mbar_init(barX, 1);
        mbar_init(barX + 8, 1);
        asm volatile("fence.mbarrier_init.release.cluster;" ::: "memory");
        mbar_expect_tx(barX, 16384);
        mbar_expect_tx(barX + 8, 16384);
        for (int it = 0; it < G2_PRE; it++) {
            mbar_expect_tx(barF + 8 * it, 32768);
            tma_load_3d(sb + it * G2_STAGE + 16384, &mapWd, barF + 8 * it, 0, ks * 896 + it * 64, nb * 2);
        }
    }
    __syncthreads();
    cluster_arrive_relaxed();

    if (wgi == 0) {
        if (tid == 0) {
            pdl_wait();
            for (int it = 0; it < G2_STAGES; it++) {
                if (it >= G2_PRE) mbar_expect_tx(barF + 8 * it, 32768);
                tma_load_2d(sb + it * G2_STAGE, &mapHH, barF + 8 * it, ks * 896 + it * 64, rb * 128);
                if (it >= G2_PRE) tma_load_3d(sb + it * G2_STAGE + 16384, &mapWd, barF + 8 * it, 0, ks * 896 + it * 64, nb * 2);
            }
            if (blockIdx.x == 0) g_cnt = 0u;
            int st = 0, ph = 0;
            for (int it = G2_STAGES; it < G2_KSTEPS; it++) {
                mbar_wait(barE + 8 * st, ph);
                const uint32_t dst = sb + st * G2_STAGE;
                const int k0 = ks * 896 + it * 64;
                mbar_expect_tx(barF + 8 * st, 32768);
                tma_load_2d(dst, &mapHH, barF + 8 * st, k0, rb * 128);
                tma_load_3d(dst + 16384, &mapWd, barF + 8 * st, 0, k0, nb * 2);
                if (++st == G2_STAGES) { st = 0; ph ^= 1; }
            }
            mbar_wait(barE + 8 * st, ph);
            mbar_expect_tx(barF + 8 * st, 16384);
            tma_load_3d(sb + st * G2_STAGE, &mapH, barF + 8 * st, 0, nb * 128 + ks * 64, rb * 2);
        }
        __syncwarp();
        cluster_wait();
    } else {
        const int cw = wgi - 1;
        const int wl = warp & 3;
        const int tl = tid & 127;
        int st = 0, ph = 0;
        float acc[64];
#pragma unroll 1
        for (int it = 0; it < G2_KSTEPS; it++) {
            mbar_wait(barF + 8 * st, ph);
            wgmma_fence();
            const uint32_t aaddr = sb + st * G2_STAGE + cw * 8192;
            const uint32_t baddr = sb + st * G2_STAGE + 16384;
#pragma unroll
            for (int kk = 0; kk < 4; kk++)
                wgmma_m64n128k16_ss(acc, make_desc(aaddr + kk * 32, 16, 1024, 1), make_desc(baddr + kk * 2048, 8192, 1024, 1), (it | kk) != 0);
            wgmma_commit();
            wgmma_wait<0>();
            if (tl == 0) mbar_arrive(barE + 8 * st);
            if (++st == G2_STAGES) { st = 0; ph ^= 1; }
        }
        cluster_wait();
        if (ks == 0) g2_finish<0>(acc, smem_raw, sb, barX, barF + 8 * st, ph, sb + st * G2_STAGE, out, rb, nb, cw, wl, lane, tl);
        else g2_finish<1>(acc, smem_raw, sb, barX, barF + 8 * st, ph, sb + st * G2_STAGE, out, rb, nb, cw, wl, lane, tl);
    }
}

typedef CUresult (*EncodeFn)(CUtensorMap*, CUtensorMapDataType, cuuint32_t, void*, const cuuint64_t*, const cuuint64_t*,
                             const cuuint32_t*, const cuuint32_t*, CUtensorMapInterleave, CUtensorMapSwizzle,
                             CUtensorMapL2promotion, CUtensorMapFloatOOBfill);

static void enc2d(EncodeFn enc, CUtensorMap* m, const void* p, int rows, int cols, int brows, int bcols, int pitch = 0) {
    cuuint64_t dims[2] = {(cuuint64_t)cols, (cuuint64_t)rows};
    cuuint64_t strides[1] = {(cuuint64_t)(pitch ? pitch : cols) * 2};
    cuuint32_t box[2] = {(cuuint32_t)bcols, (cuuint32_t)brows};
    cuuint32_t es[2] = {1, 1};
    enc(m, CU_TENSOR_MAP_DATA_TYPE_BFLOAT16, 2, const_cast<void*>(p), dims, strides, box, es, CU_TENSOR_MAP_INTERLEAVE_NONE,
        bcols == 32 ? CU_TENSOR_MAP_SWIZZLE_64B : CU_TENSOR_MAP_SWIZZLE_128B, CU_TENSOR_MAP_L2_PROMOTION_L2_128B, CU_TENSOR_MAP_FLOAT_OOB_FILL_NONE);
}
static void enc2d_plain(EncodeFn enc, CUtensorMap* m, const void* p, int rows, int cols, int brows, int bcols) {
    cuuint64_t dims[2] = {(cuuint64_t)cols, (cuuint64_t)rows};
    cuuint64_t strides[1] = {(cuuint64_t)cols * 2};
    cuuint32_t box[2] = {(cuuint32_t)bcols, (cuuint32_t)brows};
    cuuint32_t es[2] = {1, 1};
    enc(m, CU_TENSOR_MAP_DATA_TYPE_BFLOAT16, 2, const_cast<void*>(p), dims, strides, box, es, CU_TENSOR_MAP_INTERLEAVE_NONE,
        CU_TENSOR_MAP_SWIZZLE_NONE, CU_TENSOR_MAP_L2_PROMOTION_L2_128B, CU_TENSOR_MAP_FLOAT_OOB_FILL_NONE);
}
static void enc3d(EncodeFn enc, CUtensorMap* m, const void* p, int rows, int cols, int atom, int brows, int natoms, int pitch = 0) {
    cuuint64_t dims[3] = {(cuuint64_t)atom, (cuuint64_t)rows, (cuuint64_t)(cols / atom)};
    cuuint64_t strides[2] = {(cuuint64_t)(pitch ? pitch : cols) * 2, (cuuint64_t)atom * 2};
    cuuint32_t box[3] = {(cuuint32_t)atom, (cuuint32_t)brows, (cuuint32_t)natoms};
    cuuint32_t es[3] = {1, 1, 1};
    enc(m, CU_TENSOR_MAP_DATA_TYPE_BFLOAT16, 3, const_cast<void*>(p), dims, strides, box, es, CU_TENSOR_MAP_INTERLEAVE_NONE,
        atom == 32 ? CU_TENSOR_MAP_SWIZZLE_64B : CU_TENSOR_MAP_SWIZZLE_128B, CU_TENSOR_MAP_L2_PROMOTION_L2_128B, CU_TENSOR_MAP_FLOAT_OOB_FILL_NONE);
}

extern "C" void kernel_launch(void* const* d_in, const int* in_sizes, int n_in, void* d_out, int out_size) {
    const bf16* q = (const bf16*)d_in[0];
    const bf16* k = (const bf16*)d_in[1];
    const bf16* v = (const bf16*)d_in[2];
    const bf16* shift_k = (const bf16*)d_in[3];
    const bf16* ssm_k = (const bf16*)d_in[4];
    const bf16* ssm_D = (const bf16*)d_in[5];
    const bf16* wg = (const bf16*)d_in[7];
    const bf16* wu = (const bf16*)d_in[8];
    const bf16* wd = (const bf16*)d_in[9];
    bf16* out = (bf16*)d_out;

    static EncodeFn enc = nullptr;
    static void *p_hT = nullptr, *p_hh = nullptr;
    if (!enc) {
        void* fn = nullptr; cudaDriverEntryPointQueryResult qr;
        cudaGetDriverEntryPoint("cuTensorMapEncodeTiled", &fn, cudaEnableDefault, &qr);
        enc = (EncodeFn)fn;
        cudaGetSymbolAddress(&p_hT, g_hT);
        cudaGetSymbolAddress(&p_hh, g_hh);
        cudaFuncSetAttribute(conv_kernel, cudaFuncAttributeMaxDynamicSharedMemorySize, (int)sizeof(K1Smem));
        cudaFuncSetAttribute(gemm1_kernel, cudaFuncAttributeMaxDynamicSharedMemorySize, G1_SMEM);
        cudaFuncSetAttribute(gemm2_kernel, cudaFuncAttributeMaxDynamicSharedMemorySize, G2_SMEM);
    }
    CUtensorMap mA, mG64, mU64, mG32, mU32, mHH, mWd, mH, mWgp, mWup;
    enc2d_plain(enc, &mWgp, wg, D_, F_, 256, 32);
    enc2d_plain(enc, &mWup, wu, D_, F_, 256, 32);
    enc3d(enc, &mA, p_hT, D_, S_, 64, 64, 2, HT_PITCH);
    enc2d(enc, &mH, p_hT, D_, S_, 128, 64, HT_PITCH);
    enc2d(enc, &mG64, wg, D_, F_, 64, 64);
    enc2d(enc, &mU64, wu, D_, F_, 64, 64);
    enc3d(enc, &mG32, wg, D_, F_, 32, 64, 3);
    enc3d(enc, &mU32, wu, D_, F_, 32, 64, 3);
    enc2d(enc, &mHH, p_hh, S_, F_, 128, 64);
    enc3d(enc, &mWd, wd, F_, D_, 64, 64, 2);

    cudaStream_t st = cudaStreamPerThread;
    cudaLaunchAttribute at[1];
    at[0].id = cudaLaunchAttributeProgrammaticStreamSerialization;
    at[0].val.programmaticStreamSerializationAllowed = 1;
    cudaLaunchConfig_t cfg = {};
    cfg.stream = st; cfg.attrs = at; cfg.numAttrs = 1;
    conv_kernel<<<128, K1_THREADS, sizeof(K1Smem), st>>>(q, k, v, shift_k, ssm_k, ssm_D, mWgp, mWup, wd);
    cfg.gridDim = dim3(128); cfg.blockDim = dim3(G1_THREADS); cfg.dynamicSmemBytes = G1_SMEM;
    cudaLaunchKernelEx(&cfg, gemm1_kernel, mA, mG64, mU64, mG32, mU32);
    cfg.gridDim = dim3(128); cfg.blockDim = dim3(G2_THREADS); cfg.dynamicSmemBytes = G2_SMEM;
    cudaLaunchKernelEx(&cfg, gemm2_kernel, mHH, mWd, mA, out);
}
```
